```python
import torch

def _softmax(x, axis=-1):
    return torch.softmax(x, dim=axis)
def _gelu(x):
    return torch.nn.functional.gelu(x, approximate="tanh")
def _silu(x):
    return torch.nn.functional.silu(x)
def _sigmoid(x):
    return torch.sigmoid(x)
def _layernorm(x, axis=-1, eps=1e-5):
    m = x.mean(dim=axis, keepdim=True)
    v = x.var(dim=axis, keepdim=True, unbiased=False)
    return (x - m) / torch.sqrt(v + eps)
def _scatter_add(tgt, idx, src, axis=0):
    return tgt.clone().index_add_(axis, idx, src)
def _segment_sum(src, seg, n):
    out = torch.zeros((n,) + src.shape[1:], dtype=src.dtype)
    return out.index_add_(0, seg, src)
def _pad(x, pw):
    flat = tuple(v for pair in reversed(pw) for v in pair)
    return torch.nn.functional.pad(x, flat)

kernel_name = 'concat_heads__compressed_kv_cla__gqa_block_cached__decode'

def setup_inputs():

    _w = (lambda a: (lambda t: t.to(torch.bfloat16) if t.is_floating_point() else t)(torch.as_tensor(a)))
    def _A_setup():
        B, H, Sq, Sk, D, M = 2, 32, 1, 4096, 128, 512
        Dc = 4 * D
        return {
            "x": _w((lambda *s: torch.randn(*s, dtype=torch.bfloat16) * 3.2)(B, Sq, M)),
            "c_kv": _w((lambda *s: torch.randn(*s, dtype=torch.bfloat16) * 0.1)(B, Sk, Dc)),
            "w_q": _w((lambda *s: torch.randn(*s, dtype=torch.bfloat16) * 6.4)(M, H, D) * (M ** -0.5)),
            "w_uk": _w((lambda *s: torch.randn(*s, dtype=torch.bfloat16) * 6.4)(Dc, H, D) * (Dc ** -0.5)),
            "w_uv": _w((lambda *s: torch.randn(*s, dtype=torch.bfloat16) * 0.1)(Dc, H, D) * (Dc ** -0.5)),
            "w_o": _w((lambda *s: torch.randn(*s, dtype=torch.bfloat16) * 0.1)(H, D, M) * ((H * D) ** -0.5)),
        }
    _A_in = _A_setup()

    def _B_setup():
        B, Sq, D = 2, 1, 512
        Hq, Hkv, Sk, Dh = 32, 32, 4096, 128
        assert Hq % Hkv == 0, (Hq, Hkv)
        return {
            "x": _w((lambda *s: torch.randn(*s, dtype=torch.bfloat16) * 1.6)(B, Sq, D)),
            "k_cache": _w((lambda *s: torch.randn(*s, dtype=torch.bfloat16) * 1.6)(B, Hkv, Sk, Dh)),
            "v_cache": _w((lambda *s: torch.randn(*s, dtype=torch.bfloat16) * 0.05)(B, Hkv, Sk, Dh)),
            "wq": _w((lambda *s: torch.randn(*s, dtype=torch.bfloat16) * 1.6)(D, Hq * Dh) * (D ** -0.5)),
            "wo": _w((lambda *s: torch.randn(*s, dtype=torch.bfloat16) * 0.05)(Hq * Dh, D) * ((Hq * Dh) ** -0.5)),
        }
    _B_in = _B_setup()

    return {
        "A_x": _A_in["x"],
        "A_c_kv": _A_in["c_kv"],
        "A_w_q": _A_in["w_q"],
        "A_w_uk": _A_in["w_uk"],
        "A_w_uv": _A_in["w_uv"],
        "A_w_o": _A_in["w_o"],
        "B_x": _B_in["x"],
        "B_k_cache": _B_in["k_cache"],
        "B_v_cache": _B_in["v_cache"],
        "B_wq": _B_in["wq"],
        "B_wo": _B_in["wo"],
    }

def reference(A_x, A_c_kv, A_w_q, A_w_uk, A_w_uv, A_w_o, B_x, B_k_cache, B_v_cache, B_wq, B_wo):
    def _A_ref(x, c_kv, w_q, w_uk, w_uv, w_o):
        B, Sq, M = x.shape[0], x.shape[1], x.shape[2]
        Sk = c_kv.shape[1]
        H, D = w_q.shape[1], w_q.shape[2]
        q = torch.einsum("bqm,mhd->bhqd", x, w_q)
        k = torch.einsum("bkc,chd->bhkd", c_kv, w_uk)
        v = torch.einsum("bkc,chd->bhkd", c_kv, w_uv)
        scores = torch.einsum("bhqd,bhkd->bhqk", q, k) * (D ** -0.5)
        off = Sk - Sq
        qi = torch.arange(Sq)[:, None]
        kj = torch.arange(Sk)[None, :]
        cmask = kj <= (qi + off)
        scores = torch.where(cmask[None, None], scores, -1e9)
        p = _softmax(scores, axis=-1)
        ctx = torch.einsum("bhqk,bhkd->bhqd", p, v)
        return torch.einsum("bhqd,hdm->bqm", ctx, w_o)

    def _B_ref(x, k_cache, v_cache, wq, wo):
        B, Sq, D = x.shape
        Hq, Dh = 32, 128
        Hkv = k_cache.shape[1]
        rep = Hq // Hkv
        q = (lambda x, *d: x.permute(*d))((x @ wq).reshape(B, Sq, Hq, Dh), 0, 2, 1, 3)
        k = (lambda x, n, axis: torch.repeat_interleave(x, n, dim=axis))(k_cache, rep, axis=1)
        v = (lambda x, n, axis: torch.repeat_interleave(x, n, dim=axis))(v_cache, rep, axis=1)
        scores = torch.einsum("bhqd,bhkd->bhqk", q, k) * (Dh ** -0.5)
        p = _softmax(scores, axis=-1)
        o = torch.einsum("bhqk,bhkd->bhqd", p, v)
        return (lambda x, *d: x.permute(*d))(o, 0, 2, 1, 3).reshape(B, Sq, Hq * Dh) @ wo

    a = _A_ref(A_x, A_c_kv, A_w_q, A_w_uk, A_w_uv, A_w_o)
    b = _B_ref(B_x, B_k_cache, B_v_cache, B_wq, B_wo)
    return torch.concatenate([a, b], axis=-1)
```

```cpp
#include <cuda_runtime.h>
#include <cuda.h>
#include <cuda_bf16.h>
#include <stdint.h>

#define RING 7
#define WIN 4
#define WHI 5
#define THETA 64
#define END_V 40
#define GATE_W 64
#define PREWIN 2
#define TAILWIN 3
#define WOPROMO CU_TENSOR_MAP_L2_PROMOTION_L2_256B
#define POLL_DELAY 2500
#define POLL_DELAY2 4000
#define ST_SPLIT 8
#define ST_GAP 500
#define BACKOFF 200
#define BACKOFF2 100

namespace {

constexpr int NCTA = 128;
constexpr int NTHREADS = 448;
constexpr uint32_t CH = 16384;
constexpr int NTILE = 32;

constexpr uint32_t OFF_RING = 0;
constexpr uint32_t OFF_S0 = RING * CH;
constexpr uint32_t OFF_S1 = OFF_S0 + 2 * CH;
constexpr uint32_t OFF_S2 = OFF_S1 + 2 * CH;
constexpr uint32_t OFF_P = OFF_S2 + 2 * CH;
constexpr uint32_t OFF_SC = OFF_P + 4096;
constexpr uint32_t VROW = 272;
constexpr uint32_t OFF_XB = OFF_SC + 8704;
constexpr uint32_t OFF_XA = OFF_XB + 2 * VROW;
constexpr uint32_t OFF_QA = OFF_XA + 2 * VROW;
constexpr uint32_t OFF_QS = OFF_QA + 2 * VROW;
constexpr uint32_t OFF_CC = OFF_QS + 2 * VROW;
constexpr uint32_t OFF_CA = OFF_P;
constexpr uint32_t OFF_OB = OFF_XB;
constexpr uint32_t OFF_RA = OFF_P + 9 * 256;
constexpr uint32_t OFF_RB = OFF_CC + 4 * VROW;
constexpr uint32_t OFF_QB = OFF_RB + 1024;
constexpr uint32_t OFF_LSE = OFF_QB + 256;
constexpr uint32_t OFF_ML = OFF_LSE + 512;
constexpr uint32_t OFF_TAG = OFF_ML + 32;
constexpr uint32_t OFF_NOW = OFF_TAG + 4;
constexpr uint32_t OFF_WIN = OFF_TAG + 8;
constexpr uint32_t OFF_TWIN = OFF_TAG + 12;
constexpr uint32_t OFF_BAR = OFF_TAG + 16;
constexpr int B_EMPTY = RING;
constexpr int B_WQB = 2 * RING;
constexpr int B_WQA = B_WQB + 2;
constexpr int B_WUK = B_WQA + 2;
constexpr int B_WUV = B_WUK + 2;
constexpr int B_CKV = B_WUV + 2;
constexpr int B_WO = B_CKV + 4;
constexpr int B_FREE = B_WO + 8;
constexpr int B_GATH = B_FREE + 1;
constexpr int B_S2 = B_GATH + 1;
constexpr int NBAR = B_S2 + 1;
constexpr uint32_t TS_OFF = OFF_BAR + NBAR * 8;
constexpr uint32_t SMEM_USED = TS_OFF;
constexpr uint32_t SMEM_BYTES = SMEM_USED + 1024;
static_assert(SMEM_BYTES <= 232448, "smem");
static_assert(RING >= WHI && WHI >= WIN && WIN >= 3 && WIN <= 6, "windows");

constexpr float LOG2E = 1.4426950408889634f;
constexpr float SCALE = 0.08838834764831845f;
#define SPIN_LOG 22
constexpr uint32_t SPIN_MAX = 1u << SPIN_LOG;

struct Maps { CUtensorMap wqB, wqA, wuk, wuv, woA, woB, ckv, ctxp; };

__device__ unsigned g_epoch;
__device__ __align__(256) unsigned g_cnt[96];
__device__ __align__(256) ulonglong2 g_e1[2][NCTA][128];
__device__ __align__(256) uint4 g_qabs[2 * 32 * 64];
__device__ __align__(256) uint4 g_ctxp[NCTA * 128 * 16];
__device__ __align__(256) float4 g_lse[32 * 32];
__device__ __align__(256) uint4 g_e4[NCTA][64];
__device__ __align__(256) uint4 g_e5[NCTA][32];
__device__ __align__(256) uint4 g_l5[32][8];
constexpr uint32_t EMPTY = 0xffffffffu;

#define TS(k) do {} while (0)

__device__ __forceinline__ void mbar_init(uint32_t b, int c) { asm volatile("mbarrier.init.shared::cta.b64 [%0], %1;" ::"r"(b), "r"(c) : "memory"); }
__device__ __forceinline__ void mbar_expect(uint32_t b, uint32_t bytes) { asm volatile("mbarrier.arrive.expect_tx.shared::cta.b64 _, [%0], %1;" ::"r"(b), "r"(bytes) : "memory"); }
__device__ __forceinline__ void mbar_arrive(uint32_t b) { asm volatile("mbarrier.arrive.shared::cta.b64 _, [%0];" ::"r"(b) : "memory"); }
__device__ __forceinline__ void mbar_wait(uint32_t b, uint32_t ph) {
    uint32_t ok, it = 0;
    do {
        asm volatile("{\n.reg .pred p;\nmbarrier.try_wait.parity.shared::cta.b64 p, [%1], %2;\nselp.u32 %0, 1, 0, p;\n}" : "=r"(ok) : "r"(b), "r"(ph) : "memory");
        if (++it > SPIN_MAX) __trap();
    } while (!ok);
}
__device__ __forceinline__ uint32_t mbar_test(uint32_t b, uint32_t ph) {
    uint32_t ok;
    asm volatile("{\n.reg .pred p;\nmbarrier.test_wait.parity.shared::cta.b64 p, [%1], %2;\nselp.u32 %0, 1, 0, p;\n}" : "=r"(ok) : "r"(b), "r"(ph) : "memory");
    return ok;
}
__device__ __forceinline__ void bulk1d(uint32_t dst, const void* src, uint32_t bar, uint64_t pol) {
    asm volatile("cp.async.bulk.shared::cluster.global.mbarrier::complete_tx::bytes.L2::cache_hint [%0], [%1], %2, [%3], %4;"
                 ::"r"(dst), "l"(src), "n"(CH), "r"(bar), "l"(pol) : "memory");
}
__device__ __forceinline__ void bulk1d_n(uint32_t dst, const void* src, uint32_t bytes, uint32_t bar) {
    asm volatile("cp.async.bulk.shared::cluster.global.mbarrier::complete_tx::bytes [%0], [%1], %2, [%3];"
                 ::"r"(dst), "l"(src), "r"(bytes), "r"(bar) : "memory");
}
__device__ __forceinline__ void tma3d(uint32_t dst, const CUtensorMap* map, int c1, int c2, uint32_t bar, uint64_t pol, int c0 = 0) {
    asm volatile("cp.async.bulk.tensor.3d.shared::cluster.global.mbarrier::complete_tx::bytes.L2::cache_hint [%0], [%1, {%3,%4,%5}], [%2], %6;"
                 ::"r"(dst), "l"(map), "r"(bar), "r"(c0), "r"(c1), "r"(c2), "l"(pol) : "memory");
}
__device__ __forceinline__ void bar_sync(int id, int n) { asm volatile("barrier.cta.sync %0, %1;" ::"r"(id), "r"(n) : "memory"); }
__device__ __forceinline__ void bar_arrive(int id, int n) { asm volatile("barrier.cta.arrive %0, %1;" ::"r"(id), "r"(n) : "memory"); }
__device__ __forceinline__ void ldsm4(uint32_t (&r)[4], uint32_t a) {
    asm volatile("ldmatrix.sync.aligned.m8n8.x4.shared.b16 {%0,%1,%2,%3}, [%4];" : "=r"(r[0]), "=r"(r[1]), "=r"(r[2]), "=r"(r[3]) : "r"(a) : "memory");
}
__device__ __forceinline__ void ldsm4t(uint32_t (&r)[4], uint32_t a) {
    asm volatile("ldmatrix.sync.aligned.m8n8.x4.trans.shared.b16 {%0,%1,%2,%3}, [%4];" : "=r"(r[0]), "=r"(r[1]), "=r"(r[2]), "=r"(r[3]) : "r"(a) : "memory");
}
__device__ __forceinline__ void mma(float (&c)[4], const uint32_t (&a)[4], uint32_t b0, uint32_t b1) {
    asm volatile("mma.sync.aligned.m16n8k16.row.col.f32.bf16.bf16.f32 {%0,%1,%2,%3}, {%4,%5,%6,%7}, {%8,%9}, {%0,%1,%2,%3};"
                 : "+f"(c[0]), "+f"(c[1]), "+f"(c[2]), "+f"(c[3]) : "r"(a[0]), "r"(a[1]), "r"(a[2]), "r"(a[3]), "r"(b0), "r"(b1));
}
__device__ __forceinline__ uint32_t lds32(uint32_t a) { uint32_t v; asm volatile("ld.shared.b32 %0, [%1];" : "=r"(v) : "r"(a) : "memory"); return v; }
__device__ __forceinline__ uint32_t ldsv(uint32_t a) { uint32_t v; asm volatile("ld.volatile.shared.b32 %0, [%1];" : "=r"(v) : "r"(a) : "memory"); return v; }
__device__ __forceinline__ void stsv(uint32_t a, uint32_t v) { asm volatile("st.volatile.shared.b32 [%0], %1;" ::"r"(a), "r"(v) : "memory"); }
__device__ __forceinline__ float ldsf(uint32_t a) { float v; asm volatile("ld.shared.f32 %0, [%1];" : "=f"(v) : "r"(a) : "memory"); return v; }
__device__ __forceinline__ uint4 lds128(uint32_t a) { uint4 v; asm volatile("ld.shared.v4.b32 {%0,%1,%2,%3}, [%4];" : "=r"(v.x), "=r"(v.y), "=r"(v.z), "=r"(v.w) : "r"(a) : "memory"); return v; }
__device__ __forceinline__ void sts16(uint32_t a, uint16_t v) { asm volatile("st.shared.b16 [%0], %1;" ::"r"(a), "h"(v) : "memory"); }
__device__ __forceinline__ void sts32(uint32_t a, uint32_t v) { asm volatile("st.shared.b32 [%0], %1;" ::"r"(a), "r"(v) : "memory"); }
__device__ __forceinline__ void stsf2(uint32_t a, float x, float y) { asm volatile("st.shared.v2.f32 [%0], {%1,%2};" ::"r"(a), "f"(x), "f"(y) : "memory"); }
__device__ __forceinline__ void sts128(uint32_t a, uint4 v) { asm volatile("st.shared.v4.b32 [%0], {%1,%2,%3,%4};" ::"r"(a), "r"(v.x), "r"(v.y), "r"(v.z), "r"(v.w) : "memory"); }
__device__ __forceinline__ uint16_t f2bf(float x) { return __bfloat16_as_ushort(__float2bfloat16_rn(x)); }
__device__ __forceinline__ float bfround(float x) { return __bfloat162float(__float2bfloat16_rn(x)); }
__device__ __forceinline__ uint32_t pack2(float lo, float hi) { uint32_t r; asm("cvt.rn.bf16x2.f32 %0, %1, %2;" : "=r"(r) : "f"(hi), "f"(lo)); return r; }
__device__ __forceinline__ float ex2(float x) { float r; asm("ex2.approx.ftz.f32 %0, %1;" : "=f"(r) : "f"(x)); return r; }
__device__ __forceinline__ float lg2(float x) { float r; asm("lg2.approx.ftz.f32 %0, %1;" : "=f"(r) : "f"(x)); return r; }

__device__ __forceinline__ float rcp(float x) { float r; asm("rcp.approx.ftz.f32 %0, %1;" : "=f"(r) : "f"(x)); return r; }
__device__ __forceinline__ void merge_weights(uint32_t l0, uint32_t l1, float& w0, float& w1) {
    const float a = __uint_as_float(l0), b = __uint_as_float(l1), mx = fmaxf(a, b), e0 = ex2(a - mx), e1 = ex2(b - mx), r = rcp(e0 + e1);
    w0 = e0 * r; w1 = e1 * r;
}

__device__ __forceinline__ void sleep_ns(uint32_t ns) {
    uint32_t t0, t;
    asm volatile("mov.u32 %0, %clock;" : "=r"(t0));
    do { __nanosleep(200); asm volatile("mov.u32 %0, %clock;" : "=r"(t)); } while (t - t0 < 2 * ns);
}

__device__ __forceinline__ void ll_store2(ulonglong2* p, float a, float b, uint32_t tag) {
    unsigned long long x = ((unsigned long long)tag << 32) | __float_as_uint(a);
    unsigned long long y = ((unsigned long long)tag << 32) | __float_as_uint(b);
    asm volatile("st.relaxed.gpu.global.v2.b64 [%0], {%1,%2};" ::"l"(p), "l"(x), "l"(y) : "memory");
}
__device__ __forceinline__ void ll_ld2(const void* p, unsigned long long& x, unsigned long long& y) {
    asm volatile("ld.relaxed.gpu.global.v2.b64 {%0,%1}, [%2];" : "=l"(x), "=l"(y) : "l"(p) : "memory");
}
__device__ __forceinline__ void ll_gather4(const ulonglong2* p, uint32_t tag, float& r0, float& r1) {
    unsigned long long x[4], y[4]; uint32_t it = 0;
    while (true) {
        bool ok = true;
#pragma unroll
        for (int k = 0; k < 4; k++) ll_ld2(p + k * 128, x[k], y[k]);
#pragma unroll
        for (int k = 0; k < 4; k++) ok = ok && (uint32_t)(x[k] >> 32) == tag && (uint32_t)(y[k] >> 32) == tag;
        if (ok) break;
        if (++it > SPIN_MAX) __trap();
        __nanosleep(BACKOFF);
    }
    r0 = (__uint_as_float((uint32_t)x[0]) + __uint_as_float((uint32_t)x[1])) + (__uint_as_float((uint32_t)x[2]) + __uint_as_float((uint32_t)x[3]));
    r1 = (__uint_as_float((uint32_t)y[0]) + __uint_as_float((uint32_t)y[1])) + (__uint_as_float((uint32_t)y[2]) + __uint_as_float((uint32_t)y[3]));
}
__device__ __forceinline__ void cnt_rendezvous(unsigned* c, uint32_t target, int tsk) {
    TS(tsk);
    asm volatile("red.release.gpu.global.add.u32 [%0], 1;" ::"l"(c) : "memory");
    if (tsk == 18) TS(tsk + 1);
    uint32_t v, it = 0;
    while (true) {
        asm volatile("ld.acquire.gpu.global.u32 %0, [%1];" : "=r"(v) : "l"(c) : "memory");
        if ((int)(v - target) >= 0) break;
        if (++it > SPIN_MAX) __trap();
        __nanosleep(BACKOFF);
    }
    asm volatile("fence.proxy.async.global;" ::: "memory");
}

__device__ __forceinline__ void matvec_loadA(uint32_t (&a)[8][4], uint32_t tile, uint32_t bar, int w, int lane) {
    const int i = lane >> 3, rr = lane & 7, chunk = 2 * w + (i & 1);
    const uint32_t a0 = tile + (chunk >> 3) * 8192 + (rr + 8 * (i >> 1)) * 128 + (((chunk & 7) ^ rr) << 4);
#pragma unroll
    for (int hh = 0; hh < 2; hh++) {
        mbar_wait(bar + hh * 8, 0);
#pragma unroll
        for (int k = 0; k < 4; k++) ldsm4t(a[hh * 4 + k], a0 + hh * CH + k * 2048);
    }
}
__device__ __forceinline__ void matvec_mma(float (&c)[4], const uint32_t (&a)[8][4], uint32_t vec, int nvec, int lane) {
    const uint32_t va = vec + (lane & (nvec - 1)) * VROW + (lane >> 3) * 16;
    float d[4][4];
#pragma unroll
    for (int q = 0; q < 4; q++) {
        uint32_t b[4];
        ldsm4(b, va + q * 64);
        d[q][0] = d[q][1] = d[q][2] = d[q][3] = 0.f;
        mma(d[q], a[2 * q], b[0], b[1]);
        mma(d[q], a[2 * q + 1], b[2], b[3]);
    }
#pragma unroll
    for (int k = 0; k < 4; k++) c[k] = (d[0][k] + d[1][k]) + (d[2][k] + d[3][k]);
}
__device__ __forceinline__ void matvecT(float (&c)[4], uint32_t tile, uint32_t vec, int nvec, uint32_t bar, int w, int lane) {
    uint32_t a[8][4];
    matvec_loadA(a, tile, bar, w, lane);
    matvec_mma(c, a, vec, nvec, lane);
}
template <class T> __device__ __forceinline__ T* pin(T* p) { asm volatile("" : "+l"(p)); return p; }
__device__ __forceinline__ void mail_put(void* p, float v) { asm volatile("st.relaxed.gpu.global.f32 [%0], %1;" ::"l"(p), "f"(v) : "memory"); }
__device__ __forceinline__ bool mail_missing(const uint4& v) { return v.x == EMPTY || v.y == EMPTY || v.z == EMPTY || v.w == EMPTY; }
__device__ __forceinline__ void mail_get(uint4& v, const uint4* p, bool need = true) {
    asm volatile("{\n.reg .pred q;\nsetp.ne.u32 q, %5, 0;\n@q ld.relaxed.gpu.global.v4.b32 {%0,%1,%2,%3}, [%4];\n}"
                 : "+r"(v.x), "+r"(v.y), "+r"(v.z), "+r"(v.w) : "l"(p), "r"((uint32_t)need) : "memory");
}
__device__ __forceinline__ void sts64(uint32_t a, uint32_t x, uint32_t y) { asm volatile("st.shared.v2.b32 [%0], {%1,%2};" ::"r"(a), "r"(x), "r"(y) : "memory"); }
__device__ __forceinline__ float2 ldsf2(uint32_t a) { float2 v; asm volatile("ld.shared.v2.f32 {%0,%1}, [%2];" : "=f"(v.x), "=f"(v.y) : "r"(a) : "memory"); return v; }

__global__ void __launch_bounds__(NTHREADS, 1)
fused_decode_kernel(const char* __restrict__ wqraw, const __grid_constant__ Maps maps, const char* __restrict__ Kc, const char* __restrict__ Vc,
                    const __nv_bfloat16* __restrict__ xA, const __nv_bfloat16* __restrict__ xB,
                    __nv_bfloat16* __restrict__ out, const uint32_t zero) {
    if (threadIdx.x - 32u < 64u) {
        const uint32_t r = threadIdx.x - 32u;
        const uint32_t off = ((blockIdx.x & 3) << 20) + ((blockIdx.x >> 2) << 8) + ((r >> 1) << 13) + ((r & 1) << 7);
        asm volatile("prefetch.global.L2 [%0];" ::"l"(wqraw + off) : "memory");
    }
    extern __shared__ char smem_raw[];
    const uint32_t sm = ((uint32_t)__cvta_generic_to_shared(smem_raw) + 1023u) & ~1023u;
    const uint32_t bars = sm + OFF_BAR;
    const int cta = blockIdx.x, h = cta >> 2, j = cta & 3;
    uint64_t pol = 0;
    if (threadIdx.x == 0) {
        TS(0);
        asm volatile("createpolicy.fractional.L2::evict_first.b64 %0, 1.0;" : "=l"(pol));
#pragma unroll
        for (int i = 0; i < WIN; i++) mbar_init(bars + (B_WQB + i) * 8, 1);
        asm volatile("fence.mbarrier_init.release.cluster;" ::: "memory");
#pragma unroll
        for (int i = 0; i < WIN; i++) {
            mbar_expect(bars + (B_WQB + i) * 8, CH);
            tma3d(sm + OFF_S0 + i * CH, &maps.wqB + (i >> 1), j * 128 + (i & 1) * 64, h * 2, bars + (B_WQB + i) * 8, pol);
        }
    }
    const int tid = threadIdx.x < 64 ? threadIdx.x + 384 : threadIdx.x - 64, warp = tid >> 5, lane = tid & 31;

    if (warp == 12) {
        const size_t kvoff = ((size_t)(((j >> 1) * 32 + h) * 4096 + (j & 1) * 2048)) * 256;
        const char* kp = Kc + kvoff;
        const char* vp = Vc + kvoff;
        __syncwarp();
        bar_arrive(0, NTHREADS);
        bar_sync(3, 64);
        if (lane == 0) {
            uint32_t pb[WHI];
#pragma unroll
            for (int i = 0; i < WHI; i++) pb[i] = i < WHI - WIN ? (bars + B_WO * 8) | 1u : bars + (B_WQB + i - (WHI - WIN)) * 8;
            auto pace = [&](uint32_t bar, uint32_t par, uint32_t wina) {
                uint32_t it = 0;
                while (true) {
                    const uint32_t win = ldsv(wina);
                    uint32_t busy = 0;
#pragma unroll
                    for (int i = 0; i < WHI; i++) busy += mbar_test(pb[i] & ~1u, pb[i] & 1u) ^ 1u;
                    if (busy < win) break;
                    if (++it > SPIN_MAX) __trap();
                }
#pragma unroll
                for (int i = 0; i + 1 < WHI; i++) pb[i] = pb[i + 1];
                pb[WHI - 1] = bar | par;
            };
            auto side = [&](const CUtensorMap* m, uint32_t dst, int bidx, int c1, int c2, uint32_t wina) {
                const uint32_t bar = bars + bidx * 8;
                pace(bar, 0, wina);
                mbar_expect(bar, CH);
                tma3d(dst, m, c1, c2, bar, pol);
            };
#pragma unroll 1
            for (int i = WIN; i < 6; i++)
                side(&maps.wqB + (i >> 1), sm + OFF_S0 + i * CH, B_WQB + i, j * 128 + (i & 1) * 64, h * 2, sm + OFF_WIN);
            TS(1);
            uint32_t slot = 0, use = 0;
            int nuv = 0;
#pragma unroll 1
            for (int n = 0; n < 2 * NTILE; n++) {
                if (n == RING) {
                    mbar_wait(bars + B_FREE * 8, 0);
#pragma unroll 1
                    for (int q = 0; q < 4; q++) side(&maps.ckv, sm + OFF_S0 + q * CH, B_CKV + q, cta * 64 + q * 16, 0, sm + OFF_WIN);
                }
                if (nuv < 2 && n > RING && (n >= 2 * NTILE - 8 || mbar_test(bars + B_FREE * 8, 1))) {
                    mbar_wait(bars + B_FREE * 8, 1);
                    side(&maps.wuv, sm + OFF_S1 + nuv * CH, B_WUV + nuv, j * 128 + nuv * 64, h * 2, sm + OFF_WIN);
                    nuv++;
                }
                const uint32_t fb = bars + slot * 8;
                pace(fb, use & 1, sm + OFF_WIN);
                mbar_wait(fb + B_EMPTY * 8, (use & 1) ^ 1);
                mbar_expect(fb, CH);
                bulk1d(sm + OFF_RING + slot * CH, ((n & 1) ? vp : kp) + (size_t)(n >> 1) * CH, fb, pol);
                asm volatile("red.relaxed.gpu.global.add.u32 [%0], 1;" ::"l"(&g_cnt[64]) : "memory");
                stsv(sm + OFF_NOW, n + 1);
                if (++slot == RING) { slot = 0; use++; }
            }
            TS(2);
            mbar_wait(bars + B_FREE * 8, 0);
#pragma unroll 1
            for (int i = 0; i < 4; i++) {
                const uint32_t bar = bars + (B_WO + 2 * i) * 8;
                pace(bar + 8, 0, sm + OFF_TWIN);
#pragma unroll
                for (int k = 0; k < 2; k++) {
                    mbar_expect(bar + k * 8, CH / 2);
                    tma3d(sm + OFF_S0 + i * CH + k * (CH / 2), &maps.woA + (i >> 1), (i & 1) * 64 + k * 32, h & ~3, bar + k * 8, pol, (cta & 15) * 32);
                }
            }
            TS(3);
        }
    } else if (warp == 13) {
        if (lane == 0) {
#pragma unroll
            for (int i = 0; i < NBAR; i++)
                if (i < B_WQB || i >= B_WQB + WIN)
                    mbar_init(bars + i * 8, i == B_FREE ? 8 : (i >= B_EMPTY && i < B_EMPTY + RING) ? 4 : 1);
            asm volatile("fence.mbarrier_init.release.cluster;" ::: "memory");
#pragma unroll
            for (int i = 2; i < 8; i++) asm volatile("prefetch.tensormap [%0];" ::"l"(&maps.wqB + i) : "memory");
            stsv(sm + OFF_NOW, 0); stsv(sm + OFF_WIN, WIN); stsv(sm + OFF_TWIN, PREWIN);
        }
        __syncwarp();
        bar_arrive(3, 64);
        bar_sync(0, NTHREADS);
        if (lane == 0) {
            const uint32_t base = (lds32(sm + OFF_TAG) - 1u) * (NCTA * 2 * NTILE);
            mbar_wait(bars + (B_WUK + 1) * 8, 0);
            uint32_t it = 0;
            while (true) {
                const uint32_t n = ldsv(sm + OFF_NOW);
                uint32_t v;
                asm volatile("ld.relaxed.gpu.global.u32 %0, [%1];" : "=r"(v) : "l"(&g_cnt[64]) : "memory");
                v -= base;
                if (v >= NCTA * 2 * NTILE - GATE_W) break;
                const int diff = (int)(n * NCTA) - (int)v;
                stsv(sm + OFF_WIN, diff < -THETA ? WHI : WIN - (diff > THETA) - (v >= NCTA * END_V));
                if (++it > SPIN_MAX) __trap();
                __nanosleep(BACKOFF2);
            }
            stsv(sm + OFF_WIN, WHI); stsv(sm + OFF_TWIN, TAILWIN);
            TS(24);
        }
    } else if (warp < 4) {
        const int g = lane >> 2, t = lane & 3, i = lane >> 3, rr = lane & 7;
        if (tid == 0) {
            const unsigned e = atomicAdd(&g_epoch, 1u);
            sts32(sm + OFF_TAG, (e >> 7) + 1u);
        }
        bar_sync(0, NTHREADS);
        const uint32_t tag = lds32(sm + OFF_TAG);
        {
            mbar_wait(bars + 8, 0);
            float q0, q1;
            ll_gather4(&g_e1[0][h * 4][tid], tag, q0, q1);
            sts16(sm + OFF_QB + tid * 2, f2bf((j >> 1) ? q1 : q0));
        }
        bar_sync(1, 128);
        if (tid == 0) TS(4);
        uint32_t qf[8][2];
#pragma unroll
        for (int c = 0; c < 8; c++) {
            const uint32_t a = sm + OFF_QB + (((c + g) & 7) * 8 + 2 * t) * 2;
            qf[c][0] = lds32(a); qf[c][1] = lds32(a + 128);
        }
        float acc[8][4];
#pragma unroll
        for (int c = 0; c < 8; c++) { acc[c][0] = acc[c][1] = acc[c][2] = acc[c][3] = 0.f; }
        float m = -INFINITY, l = 0.f;
        const bool diag = (t == (g >> 1));
        const uint32_t krow = sm + OFF_RING + (warp * 16 + rr + 8 * (i & 1)) * 256 + (i >> 1) * 128;
        const uint32_t vrow = sm + OFF_RING + (warp * 16 + rr + 8 * (i >> 1)) * 256 + (i & 1) * 128;
        uint32_t slot = 0, ph = 0;
        float* const e5own = pin((float*)g_e5[cta] + tid);
        uint32_t a[8][4], b0, b1;
#pragma unroll 1
        for (int tile = 0;; tile++) {
            mbar_wait(bars + slot * 8, ph);
#pragma unroll
            for (int c = 0; c < 8; c++) ldsm4(a[c], krow + slot * CH + (((c + rr) & 7) << 4));
            __syncwarp();
            if (lane == 0) mbar_arrive(bars + (B_EMPTY + slot) * 8 + ((a[0][0] | a[1][0] | a[2][0] | a[3][0] | a[4][0] | a[5][0] | a[6][0] | a[7][0]) & zero));
            if (++slot == RING) { slot = 0; ph ^= 1; }
            float s0[4] = {0.f, 0.f, 0.f, 0.f}, s1[4] = {0.f, 0.f, 0.f, 0.f};
#pragma unroll
            for (int c = 0; c < 8; c += 2) { mma(s0, a[c], qf[c][0], qf[c][1]); mma(s1, a[c + 1], qf[c + 1][0], qf[c + 1][1]); }
            float slo = (g & 1) ? s0[1] + s1[1] : s0[0] + s1[0];
            float shi = (g & 1) ? s0[3] + s1[3] : s0[2] + s1[2];
            slo = diag ? bfround(bfround(slo) * SCALE) : -INFINITY;
            shi = diag ? bfround(bfround(shi) * SCALE) : -INFINITY;
            int key = __float_as_int(fmaxf(slo, shi));
            key ^= (key >> 31) & 0x7fffffff;
            key = __reduce_max_sync(0xffffffffu, key);
            key ^= (key >> 31) & 0x7fffffff;
            const float mn = fmaxf(m, __int_as_float(key));
            const float alpha = ex2((m - mn) * LOG2E);
            m = mn;
            const float plo = ex2((slo - mn) * LOG2E), phi = ex2((shi - mn) * LOG2E);
            l = l * alpha + (plo + phi);
            b0 = (g & 1) ? pack2(0.f, plo) : pack2(plo, 0.f);
            b1 = (g & 1) ? pack2(0.f, phi) : pack2(phi, 0.f);
#pragma unroll
            for (int c = 0; c < 8; c++) { acc[c][0] *= alpha; acc[c][1] *= alpha; acc[c][2] *= alpha; acc[c][3] *= alpha; }
            if (tile == NTILE - 1) break;
            mbar_wait(bars + slot * 8, ph);
#pragma unroll
            for (int c = 0; c < 8; c++) ldsm4t(a[c], vrow + slot * CH + (((c + rr) & 7) << 4));
            __syncwarp();
            if (lane == 0) mbar_arrive(bars + (B_EMPTY + slot) * 8 + ((a[0][0] | a[1][0] | a[2][0] | a[3][0] | a[4][0] | a[5][0] | a[6][0] | a[7][0]) & zero));
            if (++slot == RING) { slot = 0; ph ^= 1; }
#pragma unroll
            for (int c = 0; c < 8; c++) mma(acc[c], a[c], b0, b1);
        }
#pragma unroll
        for (int o = 16; o; o >>= 1) l += __shfl_xor_sync(0xffffffffu, l, o);
        if (lane == 0) stsf2(sm + OFF_ML + warp * 8, m, l);
        mbar_wait(bars + B_S2 * 8, 0);
        const uint4* const pv = pin(&g_e5[(cta & ~15) + warp * 4][lane]);
        const uint4* const pl = pin(g_l5[(h & ~3) + warp]);
        uint4 x[4], xl;
#pragma unroll
        for (int k = 0; k < 4; k++) { x[k].x = EMPTY; x[k].y = x[k].z = x[k].w = 0u; mail_get(x[k], pv + k * 32, warp * 4 + k != (cta & 15)); }
        bar_sync(1, 128);
        {
            const uint4 ml0 = lds128(sm + OFF_ML), ml1 = lds128(sm + OFF_ML + 16);
            const float m0 = __uint_as_float(ml0.x), m1 = __uint_as_float(ml0.z), m2 = __uint_as_float(ml1.x), m3 = __uint_as_float(ml1.z);
            const float M = fmaxf(fmaxf(m0, m1), fmaxf(m2, m3));
            const float L = (ex2((m0 - M) * LOG2E) * __uint_as_float(ml0.y) + ex2((m1 - M) * LOG2E) * __uint_as_float(ml0.w))
                          + (ex2((m2 - M) * LOG2E) * __uint_as_float(ml1.y) + ex2((m3 - M) * LOG2E) * __uint_as_float(ml1.w));
            const float f = ex2((m - M) * LOG2E) * rcp(L);
            if (tid == (h & 3) * 32) mail_put((float*)g_l5[h] + j, M * LOG2E + lg2(L));
            __syncwarp();
            xl.x = xl.y = xl.z = xl.w = 0u;
            mail_get(xl, pl);
            const uint32_t wa = sm + OFF_S2 + warp * 512 + (t * 8 + ((g + 2 * t) & 7)) * 16;
            const int dt = (tid >> 4) & 3;
            const uint32_t ra = sm + OFF_S2 + (dt * 8 + ((tid + 2 * dt) & 7)) * 16 + (((tid >> 6) ^ dt) & 1) * 8 + (tid >> 3 & 1) * 4;
            mbar_wait(bars + slot * 8, ph);
#pragma unroll
            for (int c = 0; c < 8; c++) ldsm4t(a[c], vrow + slot * CH + (((c + rr) & 7) << 4));
#pragma unroll
            for (int c = 0; c < 8; c++) mma(acc[c], a[c], b0, b1);
            if (tid == 0) TS(5);
            float v[2][8];
#pragma unroll
            for (int c = 0; c < 8; c++) { v[0][c] = acc[c][0] + acc[(c + 7) & 7][1]; v[1][c] = acc[c][2] + acc[(c + 7) & 7][3]; }
#pragma unroll
            for (int c = 0; c < 4; c++) { v[0][c] += __shfl_xor_sync(0xffffffffu, v[0][c + 4], 2); v[1][c] += __shfl_xor_sync(0xffffffffu, v[1][c + 4], 2); }
            const int src = (lane & ~3) | ((lane + 3) & 3);
#pragma unroll
            for (int c = 0; c < 2; c++) { v[0][c] += __shfl_sync(0xffffffffu, v[0][c + 2], src); v[1][c] += __shfl_sync(0xffffffffu, v[1][c + 2], src); }
            stsf2(wa + (t & 1) * 8, v[0][0] * f, v[0][1] * f);
            stsf2(wa + ((t & 1) ^ 1) * 8, v[1][0] * f, v[1][1] * f);
            bar_sync(1, 128);
            mail_put(e5own, (ldsf(ra) + ldsf(ra + 512)) + (ldsf(ra + 1024) + ldsf(ra + 1536)));
        }
        if (tid == 0) TS(6);
        {
            uint32_t it = 0;
            while (true) {
                const bool n0 = mail_missing(x[0]), n1 = mail_missing(x[1]), n2 = mail_missing(x[2]), n3 = mail_missing(x[3]), nl = mail_missing(xl);
                if (!__any_sync(0xffffffffu, n0 | n1 | n2 | n3 | nl)) break;
                mail_get(x[0], pv, n0); mail_get(x[1], pv + 32, n1); mail_get(x[2], pv + 64, n2); mail_get(x[3], pv + 96, n3); mail_get(xl, pl, nl);
                if (++it > SPIN_MAX) __trap();
            }
            float wt[4];
            merge_weights(xl.x, xl.y, wt[0], wt[1]);
            merge_weights(xl.z, xl.w, wt[2], wt[3]);
#pragma unroll
            for (int b = 0; b < 2; b++) {
                const uint4 &p = x[2 * b], &q = x[2 * b + 1];
                const float wp = wt[2 * b], wq = wt[2 * b + 1];
                sts64(sm + OFF_OB + (warp * 2 + b) * VROW + lane * 8,
                      pack2(wp * __uint_as_float(p.x) + wq * __uint_as_float(q.x), wp * __uint_as_float(p.y) + wq * __uint_as_float(q.y)),
                      pack2(wp * __uint_as_float(p.z) + wq * __uint_as_float(q.z), wp * __uint_as_float(p.w) + wq * __uint_as_float(q.w)));
            }
        }
        bar_arrive(4 + warp, 32 + 64);
        if (tid == 0) TS(16);
    } else {
        const int st = tid - 128, w = warp - 4;
        const int g = lane >> 2, t = lane & 3, i = lane >> 3, rr = lane & 7;
        if (t == 0) {
#pragma unroll
            for (int k = 0; k < 4; k++) ll_store2(&g_e1[k >> 1][cta][w * 16 + g + (k & 1) * 8], 0.f, 0.f, 0u);
        }
        if (st < 64) {
            const int which = st >> 5, b = (st >> 4) & 1, c = st & 15;
            const uint4 v = __ldg((const uint4*)((which ? xA : xB) + b * 512 + j * 128) + c);
            sts128(sm + OFF_XB + (which * 2 + b) * VROW + c * 16, v);
        }
        bar_sync(0, NTHREADS);
        const uint32_t tag = lds32(sm + OFF_TAG);
        float c[4];
#pragma unroll 1
        for (int which = 0; which < 2; which++) {
            matvecT(c, sm + OFF_S0 + which * 2 * CH, sm + OFF_XB + which * 2 * VROW, 2, bars + (B_WQB + which * 2) * 8, w, lane);
            if (t == 0) {
                ll_store2(&g_e1[which][cta][w * 16 + g], c[0], c[1], tag);
                ll_store2(&g_e1[which][cta][w * 16 + g + 8], c[2], c[3], tag);
            }
        }
        __syncwarp();
        if (lane == 0) mbar_arrive(bars + B_FREE * 8);
        if (st == 0) TS(8);
        if (st < 128) {
            float q0, q1;
            sleep_ns(POLL_DELAY);
            ll_gather4(&g_e1[1][h * 4][st], tag, q0, q1);
            sts16(sm + OFF_QA + st * 2, f2bf(q0)); sts16(sm + OFF_QA + VROW + st * 2, f2bf(q1));
        }
        bar_sync(2, 256);
        if (st == 0) TS(9);
        {
            const int row = w * 16 + rr + 8 * (i & 1);
            const uint32_t a0 = sm + OFF_S2 + (row >> 6) * CH + (row & 63) * 128;
            const uint32_t va = sm + OFF_QA + g * VROW + t * 4;
            float d[4] = {0.f, 0.f, 0.f, 0.f};
            c[0] = c[1] = c[2] = c[3] = 0.f;
            mbar_wait(bars + (B_WUK + (w >> 2)) * 8, 0);
#pragma unroll
            for (int ks = 0; ks < 8; ks++) {
                const int chunk = 2 * ks + (i >> 1);
                uint32_t a[4];
                ldsm4(a, a0 + (chunk >> 3) * 8192 + (((chunk & 7) ^ rr) << 4));
                const uint32_t b0 = (g < 2) ? lds32(va + ks * 32) : 0u, b1 = (g < 2) ? lds32(va + ks * 32 + 16) : 0u;
                if (ks & 1) mma(d, a, b0, b1); else mma(c, a, b0, b1);
            }
            if (t == 0) {
                const uint32_t qs = sm + OFF_QS + (w * 16 + g) * 2;
                sts16(qs, f2bf(c[0] + d[0])); sts16(qs + VROW, f2bf(c[1] + d[1]));
                sts16(qs + 16, f2bf(c[2] + d[2])); sts16(qs + VROW + 16, f2bf(c[3] + d[3]));
            }
            bar_sync(2, 256);
            if (w == 0) {
                const int b = lane >> 4, cc = lane & 15;
                g_qabs[(b * 32 + h) * 64 + ((j * 16 + cc) ^ (h & 7))] = lds128(sm + OFF_QS + b * VROW + cc * 16);
                __syncwarp();
                if (lane == 0) {
                    cnt_rendezvous(&g_cnt[0], tag * 128u, 18);
                    TS(10);
                    mbar_expect(bars + B_GATH * 8, 2 * CH);
                    bulk1d_n(sm + OFF_S2, g_qabs + (cta >> 6) * 2048, 2 * CH, bars + B_GATH * 8);
                }
                __syncwarp();
            }
        }
        mbar_wait(bars + B_GATH * 8, 0);
        if (st == 0) TS(11);
        {
            const int mt = w & 1, kg = w >> 1;
            const uint32_t qa = sm + OFF_S2 + (mt * 16 + rr + 8 * (i & 1)) * 1024;
            const uint32_t ka = sm + OFF_S0 + kg * CH + (rr + 8 * (i >> 1)) * 128;
            float s0[4] = {0.f, 0.f, 0.f, 0.f}, s1[4] = {0.f, 0.f, 0.f, 0.f};
            mbar_wait(bars + (B_CKV + kg) * 8, 0);
#pragma unroll 2
            for (int gq = 0; gq < 8; gq++) {
#pragma unroll
                for (int k4 = 0; k4 < 4; k4++) {
                    uint32_t a[4], b[4];
                    ldsm4(a, qa + gq * 128 + (((2 * k4 + (i >> 1)) ^ rr) << 4));
                    ldsm4(b, ka + gq * 2048 + (((2 * k4 + (i & 1)) ^ rr) << 4));
                    mma(s0, a, b[0], b[1]);
                    mma(s1, a, b[2], b[3]);
                }
            }
            const uint32_t sa = sm + OFF_SC + ((mt * 16 + g) * 68 + kg * 16 + 2 * t) * 4;
            stsf2(sa, s0[0], s0[1]); stsf2(sa + 32, s1[0], s1[1]);
            stsf2(sa + 8 * 68 * 4, s0[2], s0[3]); stsf2(sa + 8 * 68 * 4 + 32, s1[2], s1[3]);
        }
        bar_sync(2, 256);
        {
            const int head = w * 4 + i;
            const uint32_t sa = sm + OFF_SC + (head * 68 + rr * 8) * 4;
            const uint4 u0 = lds128(sa), u1 = lds128(sa + 16);
            float s[8] = {__uint_as_float(u0.x), __uint_as_float(u0.y), __uint_as_float(u0.z), __uint_as_float(u0.w),
                          __uint_as_float(u1.x), __uint_as_float(u1.y), __uint_as_float(u1.z), __uint_as_float(u1.w)};
            float mx = s[0];
#pragma unroll
            for (int k = 1; k < 8; k++) mx = fmaxf(mx, s[k]);
#pragma unroll
            for (int o = 1; o < 8; o <<= 1) mx = fmaxf(mx, __shfl_xor_sync(0xffffffffu, mx, o));
            float sum = 0.f;
#pragma unroll
            for (int k = 0; k < 8; k++) { s[k] = ex2((s[k] - mx) * (SCALE * LOG2E)); sum += s[k]; }
#pragma unroll
            for (int o = 1; o < 8; o <<= 1) sum += __shfl_xor_sync(0xffffffffu, sum, o);
            const float inv = __fdividef(1.f, sum);
            uint4 p;
            p.x = pack2(s[0] * inv, s[1] * inv); p.y = pack2(s[2] * inv, s[3] * inv);
            p.z = pack2(s[4] * inv, s[5] * inv); p.w = pack2(s[6] * inv, s[7] * inv);
            sts128(sm + OFF_P + head * 128 + ((rr ^ (head & 7)) << 4), p);
            if (rr == 0) ((float*)g_lse)[head * 128 + cta] = mx * (SCALE * LOG2E) + lg2(sum);
        }
        bar_sync(2, 256);
        {
            float o[2][8][4];
#pragma unroll
            for (int mt = 0; mt < 2; mt++)
#pragma unroll
                for (int n = 0; n < 8; n++) { o[mt][n][0] = o[mt][n][1] = o[mt][n][2] = o[mt][n][3] = 0.f; }
            const uint32_t pa = sm + OFF_P + (rr + 8 * (i & 1)) * 128;
            const uint32_t va = sm + OFF_S0 + w * 2048 + (rr + 8 * (i & 1)) * 128;
#pragma unroll 1
            for (int kq = 0; kq < 4; kq++) {
                uint32_t a0[4], a1[4];
                ldsm4(a0, pa + (((2 * kq + (i >> 1)) ^ rr) << 4));
                ldsm4(a1, pa + 2048 + (((2 * kq + (i >> 1)) ^ rr) << 4));
#pragma unroll
                for (int n = 0; n < 8; n += 2) {
                    uint32_t b[4];
                    ldsm4t(b, va + kq * CH + (((n + (i >> 1)) ^ rr) << 4));
                    mma(o[0][n], a0, b[0], b[1]); mma(o[1][n], a1, b[0], b[1]);
                    mma(o[0][n + 1], a0, b[2], b[3]); mma(o[1][n + 1], a1, b[2], b[3]);
                }
            }
#pragma unroll
            for (int mt = 0; mt < 2; mt++)
#pragma unroll
                for (int hf = 0; hf < 2; hf++) {
                    const uint32_t dst = sm + OFF_S2 + (mt * 16 + hf * 8 + g) * 1024 + w * 128 + t * 16;
#pragma unroll
                    for (int nb = 0; nb < 2; nb++) {
                        uint4 v;
                        v.x = pack2(o[mt][nb * 4 + 0][hf * 2], o[mt][nb * 4 + 0][hf * 2 + 1]);
                        v.y = pack2(o[mt][nb * 4 + 1][hf * 2], o[mt][nb * 4 + 1][hf * 2 + 1]);
                        v.z = pack2(o[mt][nb * 4 + 2][hf * 2], o[mt][nb * 4 + 2][hf * 2 + 1]);
                        v.w = pack2(o[mt][nb * 4 + 3][hf * 2], o[mt][nb * 4 + 3][hf * 2 + 1]);
                        sts128(dst + nb * 64, v);
                    }
                }
            asm volatile("fence.proxy.async.shared::cta;" ::: "memory");
            __syncwarp();
            if (lane == 0) mbar_arrive(bars + B_FREE * 8);
            if (st < 98) *(st < 64 ? &g_e4[cta][st] : st < 96 ? &g_e5[cta][st - 64] : &g_l5[h][j * 2 + st - 96]) = make_uint4(EMPTY, EMPTY, EMPTY, EMPTY);
            else if (st < 100) ((uint4*)out)[cta * 2 + st - 98] = make_uint4(0u, 0u, 0u, 0u);
        }
        bar_sync(2, 256);
        if (st == 0) {
            TS(12);
#pragma unroll 1
            for (int k = 0; k < ST_SPLIT; k++) {
                asm volatile("cp.async.bulk.tensor.3d.global.shared::cta.bulk_group [%0, {%2,%3,%4}], [%1];"
                             ::"l"(&maps.ctxp), "r"(sm + OFF_S2 + k * (2 * CH / ST_SPLIT)), "r"(0), "r"(cta), "r"(k * (128 / ST_SPLIT)) : "memory");
                if (k + 1 < ST_SPLIT) __nanosleep(ST_GAP);
            }
            asm volatile("cp.async.bulk.commit_group;" ::: "memory");
            asm volatile("cp.async.bulk.wait_group 0;" ::: "memory");
            cnt_rendezvous(&g_cnt[32], tag * 128u, 20);
            TS(13);
            mbar_expect(bars + B_GATH * 8, 2 * CH + 512);
            bulk1d_n(sm + OFF_LSE, g_lse + h * 32, 512, bars + B_GATH * 8);
            bulk1d_n(sm + OFF_S2, g_ctxp + cta * 2048, 2 * CH, bars + B_GATH * 8);
        }
        __syncwarp();
        {
            mbar_wait(bars + B_GATH * 8, 1);
            if (st == 0) TS(22);
            uint4 v[8];
#pragma unroll
            for (int k = 0; k < 8; k++) v[k] = lds128(sm + OFF_S2 + (k * 256 + st) * 16);
            float ls[4];
#pragma unroll
            for (int k = 0; k < 4; k++) ls[k] = ldsf(sm + OFF_LSE + (k * 32 + lane) * 4);
            float m0 = fmaxf(ls[0], ls[1]), m1 = fmaxf(ls[2], ls[3]);
#pragma unroll
            for (int o = 16; o; o >>= 1) { m0 = fmaxf(m0, __shfl_xor_sync(0xffffffffu, m0, o)); m1 = fmaxf(m1, __shfl_xor_sync(0xffffffffu, m1, o)); }
            ls[0] = ex2(ls[0] - m0); ls[1] = ex2(ls[1] - m0); ls[2] = ex2(ls[2] - m1); ls[3] = ex2(ls[3] - m1);
            float z0 = ls[0] + ls[1], z1 = ls[2] + ls[3];
#pragma unroll
            for (int o = 16; o; o >>= 1) { z0 += __shfl_xor_sync(0xffffffffu, z0, o); z1 += __shfl_xor_sync(0xffffffffu, z1, o); }
            z0 = __fdividef(1.f, z0); z1 = __fdividef(1.f, z1);
            ls[0] *= z0; ls[1] *= z0; ls[2] *= z1; ls[3] *= z1;
            float a[2][8];
#pragma unroll
            for (int e = 0; e < 8; e++) a[0][e] = a[1][e] = 0.f;
            const int rg = st >> 4;
#pragma unroll
            for (int k = 0; k < 8; k++) {
                const float wt = __shfl_sync(0xffffffffu, ls[k >> 1], rg + 16 * (k & 1));
                const uint32_t u[4] = {v[k].x, v[k].y, v[k].z, v[k].w};
#pragma unroll
                for (int e = 0; e < 4; e++) {
                    a[k >> 2][2 * e] += wt * __uint_as_float(u[e] << 16);
                    a[k >> 2][2 * e + 1] += wt * __uint_as_float(u[e] & 0xffff0000u);
                }
            }
            const int b = lane >> 4, u16 = lane & 15;
            const uint32_t ra = sm + OFF_SC + (w * 256 + b * 128 + (u16 >> 3) * 64 + ((u16 >> 2) & 1) * 32 + (u16 & 3) * 2) * 4;
#pragma unroll
            for (int e = 0; e < 8; e += 2) {
                const float k0 = b ? a[1][e] : a[0][e], k1 = b ? a[1][e + 1] : a[0][e + 1];
                const float s0 = b ? a[0][e] : a[1][e], s1 = b ? a[0][e + 1] : a[1][e + 1];
                stsf2(ra + (e >> 1) * 32, k0 + __shfl_xor_sync(0xffffffffu, s0, 16), k1 + __shfl_xor_sync(0xffffffffu, s1, 16));
            }
            bar_sync(2, 256);
            if (st == 0) mbar_arrive(bars + B_S2 * 8);
            float s = 0.f;
#pragma unroll
            for (int k = 0; k < 8; k++) s += ldsf(sm + OFF_SC + (k * 256 + st) * 4);
            const float hi = bfround(s);
            const uint32_t ca = sm + OFF_CC + (st >> 7) * VROW + (st & 127) * 2;
            sts16(ca, f2bf(hi)); sts16(ca + 2 * VROW, f2bf(s - hi));
            bar_sync(2, 256);
        }
        matvecT(c, sm + OFF_S1, sm + OFF_CC, 4, bars + B_WUV * 8, w, lane);
#pragma unroll
        for (int k = 0; k < 4; k++) c[k] += __shfl_down_sync(0xffffffffu, c[k], 1);
        if (t == 0) {
            float* const e = (float*)g_e4[cta] + w * 16 + g;
            mail_put(e, c[0]); mail_put(e + 128, c[1]); mail_put(e + 8, c[2]); mail_put(e + 136, c[3]);
        }
        __syncwarp();
        if (lane == 0) mbar_arrive(bars + B_FREE * 8);
        if (st == 0) TS(23);
        {
            const uint4* const pv = &g_e4[(cta & ~15) + (w >> 1) * 4][(w & 1) * 32 + lane];
            uint4 x[4];
            uint32_t it = 0;
            sleep_ns(POLL_DELAY2);
            while (true) {
#pragma unroll
                for (int k = 0; k < 4; k++) { x[k].x = x[k].y = x[k].z = x[k].w = 0u; mail_get(x[k], pv + k * 64); }
                if (!__any_sync(0xffffffffu, mail_missing(x[0]) | mail_missing(x[1]) | mail_missing(x[2]) | mail_missing(x[3]))) break;
                if (++it > SPIN_MAX) __trap();
                __nanosleep(BACKOFF);
            }
#define SUM4(e) ((__uint_as_float(x[0].e) + __uint_as_float(x[1].e)) + (__uint_as_float(x[2].e) + __uint_as_float(x[3].e)))
            sts64(sm + OFF_CA + w * VROW + lane * 8, pack2(SUM4(x), SUM4(y)), pack2(SUM4(z), SUM4(w)));
#undef SUM4
        }
        if (st == 0) TS(14);
        bar_sync(2, 256);
        {
            const uint32_t a0 = sm + OFF_S0 + (w >> 1) * 2048 + (rr + 8 * (i >> 1)) * 64 + ((((w & 1) * 2 + (i & 1)) ^ (rr >> 1)) << 4);
            const uint32_t va = sm + ((w & 6) + (lane & 1)) * VROW + i * 16;
            const uint32_t wa = sm + (w * 32 + (t & 1) * 16 + (t >> 1) * 8 + g) * 4;
            __nv_bfloat16* const outp = pin(out + (i & 1) * 1024 + (w ^ 1) * 512 + (cta & 15) * 32 + (i >> 1) * 16 + rr * 2);
            int tp = t;
            asm volatile("" : "+r"(tp));
#pragma unroll
            for (int ab = 0; ab < 2; ab++) {
                uint32_t a[4][4], b[4][4];
                float d[4][4];
#pragma unroll
                for (int k = 0; k < 4; k++) {
                    if (!(k & 1)) mbar_wait(bars + (B_WO + ab * 4 + (k >> 1)) * 8, 0);
                    ldsm4t(a[k], a0 + ab * 2 * CH + (k >> 1) * 8192 + (k & 1) * 1024);
                }
                if (ab) bar_sync(4 + (w >> 1), 32 + 64);
#pragma unroll
                for (int q = 0; q < 4; q++) ldsm4(b[q], va + (ab ? OFF_OB : OFF_CA) + q * 64);
#pragma unroll
                for (int k = 0; k < 4; k++) {
                    d[k][0] = d[k][1] = d[k][2] = d[k][3] = 0.f;
                    mma(d[k], a[k], b[k >> 1][(k & 1) * 2], b[k >> 1][(k & 1) * 2 + 1]);
                }
#pragma unroll
                for (int k = 0; k < 4; k += 2) {
                    mbar_wait(bars + (B_WO + ab * 4 + 2 + (k >> 1)) * 8, 0);
                    if (k && st == 0) TS(25 + ab);
                    ldsm4t(a[k], a0 + ab * 2 * CH + CH + k * 4096);
                    ldsm4t(a[k + 1], a0 + ab * 2 * CH + CH + k * 4096 + 1024);
                    mma(d[k], a[k], b[2 + (k >> 1)][0], b[2 + (k >> 1)][1]);
                    mma(d[k + 1], a[k + 1], b[2 + (k >> 1)][2], b[2 + (k >> 1)][3]);
                }
                float z[4];
#pragma unroll
                for (int k = 0; k < 4; k++) z[k] = (d[0][k] + d[1][k]) + (d[2][k] + d[3][k]);
                sts32(wa + (ab ? OFF_RB : OFF_RA), __float_as_uint(tp == 0 ? z[0] : tp == 1 ? z[1] : tp == 2 ? z[2] : z[3]));
                if (st == 0) TS(15 + 2 * ab);
                if (w == (ab ^ 1)) {
                    bar_sync(8 + ab, 256);
                    const uint32_t ra = sm + (ab ? OFF_RB : OFF_RA) + lane * 8;
                    const float2 r0 = ldsf2(ra), r1 = ldsf2(ra + 256), r2 = ldsf2(ra + 512), r3 = ldsf2(ra + 768);
                    asm volatile("red.relaxed.gpu.global.add.noftz.bf16x2 [%0], %1;"
                                 ::"l"(outp), "r"(pack2((r0.x + r1.x) + (r2.x + r3.x), (r0.y + r1.y) + (r2.y + r3.y))) : "memory");
                } else {
                    bar_arrive(8 + ab, 256);
                }
            }
        }
    }
}

typedef CUresult (*EncodeFn)(CUtensorMap*, CUtensorMapDataType, cuuint32_t, void*, const cuuint64_t*, const cuuint64_t*,
                             const cuuint32_t*, const cuuint32_t*, CUtensorMapInterleave, CUtensorMapSwizzle,
                             CUtensorMapL2promotion, CUtensorMapFloatOOBfill);

void make_map(EncodeFn enc, CUtensorMap* m, void* p, unsigned rows, unsigned cols, unsigned br, unsigned bg) {
    cuuint64_t gd[3] = {64, rows, cols / 64};
    cuuint64_t gs[2] = {(cuuint64_t)cols * 2, 128};
    cuuint32_t bx[3] = {64, br, bg};
    cuuint32_t es[3] = {1, 1, 1};
    enc(m, CU_TENSOR_MAP_DATA_TYPE_BFLOAT16, 3, p, gd, gs, bx, es, CU_TENSOR_MAP_INTERLEAVE_NONE,
        CU_TENSOR_MAP_SWIZZLE_128B, CU_TENSOR_MAP_L2_PROMOTION_L2_128B, CU_TENSOR_MAP_FLOAT_OOB_FILL_NONE);
}

}

extern "C" void kernel_launch(void* const* d_in, const int* in_sizes, int n_in, void* d_out, int out_size) {
    static EncodeFn enc = nullptr;
    if (!enc) {
        void* fn = nullptr;
        cudaDriverEntryPointQueryResult qr;
        cudaGetDriverEntryPoint("cuTensorMapEncodeTiled", &fn, cudaEnableDefault, &qr);
        enc = (EncodeFn)fn;
        cudaFuncSetAttribute(fused_decode_kernel, cudaFuncAttributeMaxDynamicSharedMemorySize, SMEM_BYTES);
    }
    Maps maps;
    make_map(enc, &maps.wqB, d_in[9], 512, 4096, 64, 2);
    make_map(enc, &maps.wqA, d_in[2], 512, 4096, 64, 2);
    make_map(enc, &maps.wuk, d_in[3], 512, 4096, 64, 2);
    make_map(enc, &maps.wuv, d_in[4], 512, 4096, 64, 2);
    for (int k = 0; k < 2; k++) {
        cuuint64_t gd[3] = {512, 128, 32};
        cuuint64_t gs[2] = {1024, 131072};
        cuuint32_t bx[3] = {32, 32, 4};
        cuuint32_t es[3] = {1, 1, 1};
        enc(&maps.woA + k, CU_TENSOR_MAP_DATA_TYPE_BFLOAT16, 3, d_in[k ? 10 : 5], gd, gs, bx, es, CU_TENSOR_MAP_INTERLEAVE_NONE,
            CU_TENSOR_MAP_SWIZZLE_64B, (CUtensorMapL2promotion)WOPROMO, CU_TENSOR_MAP_FLOAT_OOB_FILL_NONE);
    }
    make_map(enc, &maps.ckv, d_in[1], 8192, 512, 16, 8);
    {
        void* p = nullptr;
        cudaGetSymbolAddress(&p, g_ctxp);
        cuuint64_t gd[3] = {128, 128, 128};
        cuuint64_t gs[2] = {256, 32768};
        cuuint32_t bx[3] = {128, 1, 128 / ST_SPLIT};
        cuuint32_t es[3] = {1, 1, 1};
        enc(&maps.ctxp, CU_TENSOR_MAP_DATA_TYPE_BFLOAT16, 3, p, gd, gs, bx, es, CU_TENSOR_MAP_INTERLEAVE_NONE,
            CU_TENSOR_MAP_SWIZZLE_NONE, CU_TENSOR_MAP_L2_PROMOTION_NONE, CU_TENSOR_MAP_FLOAT_OOB_FILL_NONE);
    }
    fused_decode_kernel<<<NCTA, NTHREADS, SMEM_BYTES>>>((const char*)d_in[9], maps, (const char*)d_in[7], (const char*)d_in[8],
                                                         (const __nv_bfloat16*)d_in[0], (const __nv_bfloat16*)d_in[6],
                                                         (__nv_bfloat16*)d_out, 0u);
}
```

```cpp
#include <cuda_runtime.h>
#include <cuda.h>
#include <cuda_bf16.h>
#include <stdint.h>

#define RING 7
#define WIN 4
#define WHI 5
#define THETA 64
#define END_V 40
#define GATE_W 64
#define PREWIN 2
#define TAILWIN 3
#define POLL_Q 3
#define POLL_GAP 0
#define WOPROMO CU_TENSOR_MAP_L2_PROMOTION_L2_256B
#define POLL_DELAY 2500
#define POLL_DELAY2 4000
#define ST_SPLIT 8
#define ST_GAP 500
#define BACKOFF 200
#define BACKOFF2 100

namespace {

constexpr int NCTA = 128;
constexpr int NTHREADS = 448;
constexpr uint32_t CH = 16384;
constexpr int NTILE = 32;

constexpr uint32_t OFF_RING = 0;
constexpr uint32_t OFF_S0 = RING * CH;
constexpr uint32_t OFF_S1 = OFF_S0 + 2 * CH;
constexpr uint32_t OFF_S2 = OFF_S1 + 2 * CH;
constexpr uint32_t OFF_P = OFF_S2 + 2 * CH;
constexpr uint32_t OFF_SC = OFF_P + 4096;
constexpr uint32_t VROW = 272;
constexpr uint32_t OFF_XB = OFF_SC + 8704;
constexpr uint32_t OFF_XA = OFF_XB + 2 * VROW;
constexpr uint32_t OFF_QA = OFF_XA + 2 * VROW;
constexpr uint32_t OFF_QS = OFF_QA + 2 * VROW;
constexpr uint32_t OFF_CC = OFF_QS + 2 * VROW;
constexpr uint32_t OFF_CA = OFF_P;
constexpr uint32_t OFF_QB = OFF_CC + 4 * VROW;
constexpr uint32_t OFF_LSE = OFF_QB + 256;
constexpr uint32_t OFF_ML = OFF_LSE + 512;
constexpr uint32_t OFF_TAG = OFF_ML + 32;
constexpr uint32_t OFF_NOW = OFF_TAG + 4;
constexpr uint32_t OFF_WIN = OFF_TAG + 8;
constexpr uint32_t OFF_TWIN = OFF_TAG + 12;
constexpr uint32_t OFF_BAR = OFF_TAG + 16;
constexpr int B_EMPTY = RING;
constexpr int B_WQB = 2 * RING;
constexpr int B_WQA = B_WQB + 2;
constexpr int B_WUK = B_WQA + 2;
constexpr int B_WUV = B_WUK + 2;
constexpr int B_CKV = B_WUV + 2;
constexpr int B_WO = B_CKV + 4;
constexpr int B_FREE = B_WO + 8;
constexpr int B_GATH = B_FREE + 1;
constexpr int B_S2 = B_GATH + 1;
constexpr int NBAR = B_S2 + 1;
constexpr uint32_t TS_OFF = OFF_BAR + NBAR * 8;
constexpr uint32_t SMEM_USED = TS_OFF;
constexpr uint32_t SMEM_BYTES = SMEM_USED + 1024;
static_assert(SMEM_BYTES <= 232448, "smem");
static_assert(RING >= WHI && WHI >= WIN && WIN >= 3 && WIN <= 6, "windows");

constexpr float LOG2E = 1.4426950408889634f;
constexpr float SCALE = 0.08838834764831845f;
#define SPIN_LOG 22
constexpr uint32_t SPIN_MAX = 1u << SPIN_LOG;

struct Maps { CUtensorMap wqB, wqA, wuk, wuv, woB, woA, ckv, ctxp; };

__device__ unsigned g_epoch;
__device__ __align__(256) unsigned g_cnt[96];
__device__ __align__(256) ulonglong2 g_e1[2][NCTA][128];
__device__ __align__(256) uint4 g_qabs[2 * 32 * 64];
__device__ __align__(256) uint4 g_ctxp[NCTA * 128 * 16];
__device__ __align__(256) float4 g_lse[32 * 32];
__device__ __align__(256) uint4 g_e4[NCTA][64];
__device__ __align__(256) uint4 g_e5[NCTA][16];
__device__ __align__(256) uint4 g_l5[32][8];
constexpr uint32_t EMPTY = 0xffffffffu;

#define TS(k) do {} while (0)

__device__ __forceinline__ void mbar_init(uint32_t b, int c) { asm volatile("mbarrier.init.shared::cta.b64 [%0], %1;" ::"r"(b), "r"(c) : "memory"); }
__device__ __forceinline__ void mbar_expect(uint32_t b, uint32_t bytes) { asm volatile("mbarrier.arrive.expect_tx.shared::cta.b64 _, [%0], %1;" ::"r"(b), "r"(bytes) : "memory"); }
__device__ __forceinline__ void mbar_arrive(uint32_t b) { asm volatile("mbarrier.arrive.shared::cta.b64 _, [%0];" ::"r"(b) : "memory"); }
__device__ __forceinline__ void mbar_wait(uint32_t b, uint32_t ph) {
    uint32_t ok, it = 0;
    do {
        asm volatile("{\n.reg .pred p;\nmbarrier.try_wait.parity.shared::cta.b64 p, [%1], %2;\nselp.u32 %0, 1, 0, p;\n}" : "=r"(ok) : "r"(b), "r"(ph) : "memory");
        if (++it > SPIN_MAX) __trap();
    } while (!ok);
}
__device__ __forceinline__ uint32_t mbar_test(uint32_t b, uint32_t ph) {
    uint32_t ok;
    asm volatile("{\n.reg .pred p;\nmbarrier.test_wait.parity.shared::cta.b64 p, [%1], %2;\nselp.u32 %0, 1, 0, p;\n}" : "=r"(ok) : "r"(b), "r"(ph) : "memory");
    return ok;
}
__device__ __forceinline__ void bulk1d(uint32_t dst, const void* src, uint32_t bar, uint64_t pol) {
    asm volatile("cp.async.bulk.shared::cluster.global.mbarrier::complete_tx::bytes.L2::cache_hint [%0], [%1], %2, [%3], %4;"
                 ::"r"(dst), "l"(src), "n"(CH), "r"(bar), "l"(pol) : "memory");
}
__device__ __forceinline__ void bulk1d_n(uint32_t dst, const void* src, uint32_t bytes, uint32_t bar) {
    asm volatile("cp.async.bulk.shared::cluster.global.mbarrier::complete_tx::bytes [%0], [%1], %2, [%3];"
                 ::"r"(dst), "l"(src), "r"(bytes), "r"(bar) : "memory");
}
__device__ __forceinline__ void tma3d(uint32_t dst, const CUtensorMap* map, int c1, int c2, uint32_t bar, uint64_t pol, int c0 = 0) {
    asm volatile("cp.async.bulk.tensor.3d.shared::cluster.global.mbarrier::complete_tx::bytes.L2::cache_hint [%0], [%1, {%3,%4,%5}], [%2], %6;"
                 ::"r"(dst), "l"(map), "r"(bar), "r"(c0), "r"(c1), "r"(c2), "l"(pol) : "memory");
}
__device__ __forceinline__ void bar_sync(int id, int n) { asm volatile("barrier.cta.sync %0, %1;" ::"r"(id), "r"(n) : "memory"); }
__device__ __forceinline__ void bar_arrive(int id, int n) { asm volatile("barrier.cta.arrive %0, %1;" ::"r"(id), "r"(n) : "memory"); }
__device__ __forceinline__ void ldsm4(uint32_t (&r)[4], uint32_t a) {
    asm volatile("ldmatrix.sync.aligned.m8n8.x4.shared.b16 {%0,%1,%2,%3}, [%4];" : "=r"(r[0]), "=r"(r[1]), "=r"(r[2]), "=r"(r[3]) : "r"(a) : "memory");
}
__device__ __forceinline__ void ldsm4t(uint32_t (&r)[4], uint32_t a) {
    asm volatile("ldmatrix.sync.aligned.m8n8.x4.trans.shared.b16 {%0,%1,%2,%3}, [%4];" : "=r"(r[0]), "=r"(r[1]), "=r"(r[2]), "=r"(r[3]) : "r"(a) : "memory");
}
__device__ __forceinline__ void mma(float (&c)[4], const uint32_t (&a)[4], uint32_t b0, uint32_t b1) {
    asm volatile("mma.sync.aligned.m16n8k16.row.col.f32.bf16.bf16.f32 {%0,%1,%2,%3}, {%4,%5,%6,%7}, {%8,%9}, {%0,%1,%2,%3};"
                 : "+f"(c[0]), "+f"(c[1]), "+f"(c[2]), "+f"(c[3]) : "r"(a[0]), "r"(a[1]), "r"(a[2]), "r"(a[3]), "r"(b0), "r"(b1));
}
__device__ __forceinline__ uint32_t lds32(uint32_t a) { uint32_t v; asm volatile("ld.shared.b32 %0, [%1];" : "=r"(v) : "r"(a) : "memory"); return v; }
__device__ __forceinline__ uint32_t ldsv(uint32_t a) { uint32_t v; asm volatile("ld.volatile.shared.b32 %0, [%1];" : "=r"(v) : "r"(a) : "memory"); return v; }
__device__ __forceinline__ void stsv(uint32_t a, uint32_t v) { asm volatile("st.volatile.shared.b32 [%0], %1;" ::"r"(a), "r"(v) : "memory"); }
__device__ __forceinline__ float ldsf(uint32_t a) { float v; asm volatile("ld.shared.f32 %0, [%1];" : "=f"(v) : "r"(a) : "memory"); return v; }
__device__ __forceinline__ uint4 lds128(uint32_t a) { uint4 v; asm volatile("ld.shared.v4.b32 {%0,%1,%2,%3}, [%4];" : "=r"(v.x), "=r"(v.y), "=r"(v.z), "=r"(v.w) : "r"(a) : "memory"); return v; }
__device__ __forceinline__ void sts16(uint32_t a, uint16_t v) { asm volatile("st.shared.b16 [%0], %1;" ::"r"(a), "h"(v) : "memory"); }
__device__ __forceinline__ void sts32(uint32_t a, uint32_t v) { asm volatile("st.shared.b32 [%0], %1;" ::"r"(a), "r"(v) : "memory"); }
__device__ __forceinline__ void stsf2(uint32_t a, float x, float y) { asm volatile("st.shared.v2.f32 [%0], {%1,%2};" ::"r"(a), "f"(x), "f"(y) : "memory"); }
__device__ __forceinline__ void sts128(uint32_t a, uint4 v) { asm volatile("st.shared.v4.b32 [%0], {%1,%2,%3,%4};" ::"r"(a), "r"(v.x), "r"(v.y), "r"(v.z), "r"(v.w) : "memory"); }
__device__ __forceinline__ uint16_t f2bf(float x) { return __bfloat16_as_ushort(__float2bfloat16_rn(x)); }
__device__ __forceinline__ float bfround(float x) { return __bfloat162float(__float2bfloat16_rn(x)); }
__device__ __forceinline__ uint32_t pack2(float lo, float hi) { uint32_t r; asm("cvt.rn.bf16x2.f32 %0, %1, %2;" : "=r"(r) : "f"(hi), "f"(lo)); return r; }
__device__ __forceinline__ float ex2(float x) { float r; asm("ex2.approx.ftz.f32 %0, %1;" : "=f"(r) : "f"(x)); return r; }
__device__ __forceinline__ float lg2(float x) { float r; asm("lg2.approx.ftz.f32 %0, %1;" : "=f"(r) : "f"(x)); return r; }

__device__ __forceinline__ float rcp(float x) { float r; asm("rcp.approx.ftz.f32 %0, %1;" : "=f"(r) : "f"(x)); return r; }
__device__ __forceinline__ void merge_weights(uint32_t l0, uint32_t l1, float& w0, float& w1) {
    const float a = __uint_as_float(l0), b = __uint_as_float(l1), mx = fmaxf(a, b), e0 = ex2(a - mx), e1 = ex2(b - mx), r = rcp(e0 + e1);
    w0 = e0 * r; w1 = e1 * r;
}

__device__ __forceinline__ void sleep_ns(uint32_t ns) {
    uint32_t t0, t;
    asm volatile("mov.u32 %0, %clock;" : "=r"(t0));
    do { __nanosleep(200); asm volatile("mov.u32 %0, %clock;" : "=r"(t)); } while (t - t0 < 2 * ns);
}

__device__ __forceinline__ void ll_store2(ulonglong2* p, float a, float b, uint32_t tag) {
    unsigned long long x = ((unsigned long long)tag << 32) | __float_as_uint(a);
    unsigned long long y = ((unsigned long long)tag << 32) | __float_as_uint(b);
    asm volatile("st.relaxed.gpu.global.v2.b64 [%0], {%1,%2};" ::"l"(p), "l"(x), "l"(y) : "memory");
}
__device__ __forceinline__ void ll_ld2(const void* p, unsigned long long& x, unsigned long long& y) {
    asm volatile("ld.relaxed.gpu.global.v2.b64 {%0,%1}, [%2];" : "=l"(x), "=l"(y) : "l"(p) : "memory");
}
__device__ __forceinline__ void ll_gather4(const ulonglong2* p, uint32_t tag, float& r0, float& r1) {
    unsigned long long x[4], y[4]; uint32_t it = 0;
    while (true) {
        bool ok = true;
#pragma unroll
        for (int k = 0; k < 4; k++) ll_ld2(p + k * 128, x[k], y[k]);
#pragma unroll
        for (int k = 0; k < 4; k++) ok = ok && (uint32_t)(x[k] >> 32) == tag && (uint32_t)(y[k] >> 32) == tag;
        if (ok) break;
        if (++it > SPIN_MAX) __trap();
        __nanosleep(BACKOFF);
    }
    r0 = (__uint_as_float((uint32_t)x[0]) + __uint_as_float((uint32_t)x[1])) + (__uint_as_float((uint32_t)x[2]) + __uint_as_float((uint32_t)x[3]));
    r1 = (__uint_as_float((uint32_t)y[0]) + __uint_as_float((uint32_t)y[1])) + (__uint_as_float((uint32_t)y[2]) + __uint_as_float((uint32_t)y[3]));
}
__device__ __forceinline__ void cnt_rendezvous(unsigned* c, uint32_t target, int tsk) {
    TS(tsk);
    asm volatile("red.release.gpu.global.add.u32 [%0], 1;" ::"l"(c) : "memory");
    if (tsk == 18) TS(tsk + 1);
    uint32_t v, it = 0;
    while (true) {
        asm volatile("ld.acquire.gpu.global.u32 %0, [%1];" : "=r"(v) : "l"(c) : "memory");
        if ((int)(v - target) >= 0) break;
        if (++it > SPIN_MAX) __trap();
        __nanosleep(BACKOFF);
    }
    asm volatile("fence.proxy.async.global;" ::: "memory");
}

__device__ __forceinline__ void matvec_loadA(uint32_t (&a)[8][4], uint32_t tile, uint32_t bar, int w, int lane) {
    const int i = lane >> 3, rr = lane & 7, chunk = 2 * w + (i & 1);
    const uint32_t a0 = tile + (chunk >> 3) * 8192 + (rr + 8 * (i >> 1)) * 128 + (((chunk & 7) ^ rr) << 4);
#pragma unroll
    for (int hh = 0; hh < 2; hh++) {
        mbar_wait(bar + hh * 8, 0);
#pragma unroll
        for (int k = 0; k < 4; k++) ldsm4t(a[hh * 4 + k], a0 + hh * CH + k * 2048);
    }
}
__device__ __forceinline__ void matvec_mma(float (&c)[4], const uint32_t (&a)[8][4], uint32_t vec, int nvec, int lane) {
    const uint32_t va = vec + (lane & (nvec - 1)) * VROW + (lane >> 3) * 16;
    float d[4][4];
#pragma unroll
    for (int q = 0; q < 4; q++) {
        uint32_t b[4];
        ldsm4(b, va + q * 64);
        d[q][0] = d[q][1] = d[q][2] = d[q][3] = 0.f;
        mma(d[q], a[2 * q], b[0], b[1]);
        mma(d[q], a[2 * q + 1], b[2], b[3]);
    }
#pragma unroll
    for (int k = 0; k < 4; k++) c[k] = (d[0][k] + d[1][k]) + (d[2][k] + d[3][k]);
}
__device__ __forceinline__ void matvecT(float (&c)[4], uint32_t tile, uint32_t vec, int nvec, uint32_t bar, int w, int lane) {
    uint32_t a[8][4];
    matvec_loadA(a, tile, bar, w, lane);
    matvec_mma(c, a, vec, nvec, lane);
}
template <class T> __device__ __forceinline__ T* pin(T* p) { asm volatile("" : "+l"(p)); return p; }
__device__ __forceinline__ void mail_put(void* p, uint32_t v) { asm volatile("st.relaxed.gpu.global.b32 [%0], %1;" ::"l"(p), "r"(v) : "memory"); }
__device__ __forceinline__ void mail_put(void* p, float v) { mail_put(p, __float_as_uint(v)); }
__device__ __forceinline__ void out_add(__nv_bfloat16* p, float x, float y) {
    asm volatile("red.relaxed.gpu.global.add.noftz.bf16x2 [%0], %1;" ::"l"(p), "r"(pack2(x, y)) : "memory");
}
__device__ __forceinline__ bool mail_missing(const uint4& v) { return v.x == EMPTY || v.y == EMPTY || v.z == EMPTY || v.w == EMPTY; }
__device__ __forceinline__ void mail_get(uint4& v, const uint4* p, bool need = true) {
    asm volatile("{\n.reg .pred q;\nsetp.ne.u32 q, %5, 0;\n@q ld.relaxed.gpu.global.v4.b32 {%0,%1,%2,%3}, [%4];\n}"
                 : "+r"(v.x), "+r"(v.y), "+r"(v.z), "+r"(v.w) : "l"(p), "r"((uint32_t)need) : "memory");
}
__device__ __forceinline__ void sts64(uint32_t a, uint32_t x, uint32_t y) { asm volatile("st.shared.v2.b32 [%0], {%1,%2};" ::"r"(a), "r"(x), "r"(y) : "memory"); }
__device__ __forceinline__ float2 ldsf2(uint32_t a) { float2 v; asm volatile("ld.shared.v2.f32 {%0,%1}, [%2];" : "=f"(v.x), "=f"(v.y) : "r"(a) : "memory"); return v; }

__global__ void __launch_bounds__(NTHREADS, 1)
fused_decode_kernel(const char* __restrict__ wqraw, const __grid_constant__ Maps maps, const char* __restrict__ Kc, const char* __restrict__ Vc,
                    const __nv_bfloat16* __restrict__ xA, const __nv_bfloat16* __restrict__ xB,
                    __nv_bfloat16* __restrict__ out, const uint32_t zero) {
    if (threadIdx.x - 32u < 64u) {
        const uint32_t r = threadIdx.x - 32u;
        const uint32_t off = ((blockIdx.x & 3) << 20) + ((blockIdx.x >> 2) << 8) + ((r >> 1) << 13) + ((r & 1) << 7);
        asm volatile("prefetch.global.L2 [%0];" ::"l"(wqraw + off) : "memory");
    }
    extern __shared__ char smem_raw[];
    const uint32_t sm = ((uint32_t)__cvta_generic_to_shared(smem_raw) + 1023u) & ~1023u;
    const uint32_t bars = sm + OFF_BAR;
    const int cta = blockIdx.x, h = cta >> 2, j = cta & 3;
    uint64_t pol = 0;
    if (threadIdx.x == 0) {
        TS(0);
        asm volatile("createpolicy.fractional.L2::evict_first.b64 %0, 1.0;" : "=l"(pol));
#pragma unroll
        for (int i = 0; i < WIN; i++) mbar_init(bars + (B_WQB + i) * 8, 1);
        asm volatile("fence.mbarrier_init.release.cluster;" ::: "memory");
#pragma unroll
        for (int i = 0; i < WIN; i++) {
            mbar_expect(bars + (B_WQB + i) * 8, CH);
            tma3d(sm + OFF_S0 + i * CH, &maps.wqB + (i >> 1), j * 128 + (i & 1) * 64, h * 2, bars + (B_WQB + i) * 8, pol);
        }
    }
    const int tid = threadIdx.x < 64 ? threadIdx.x + 384 : threadIdx.x - 64, warp = tid >> 5, lane = tid & 31;

    if (warp == 12) {
        const size_t kvoff = ((size_t)(((j >> 1) * 32 + h) * 4096 + (j & 1) * 2048)) * 256;
        const char* kp = Kc + kvoff;
        const char* vp = Vc + kvoff;
        __syncwarp();
        bar_arrive(0, NTHREADS);
        bar_sync(3, 64);
        if (lane == 0) {
            uint32_t pb[WHI];
#pragma unroll
            for (int i = 0; i < WHI; i++) pb[i] = i < WHI - WIN ? (bars + B_WO * 8) | 1u : bars + (B_WQB + i - (WHI - WIN)) * 8;
            auto pace = [&](uint32_t bar, uint32_t par, uint32_t wina) {
                uint32_t it = 0;
                while (true) {
                    const uint32_t win = ldsv(wina);
                    uint32_t busy = 0;
#pragma unroll
                    for (int i = 0; i < WHI; i++) busy += mbar_test(pb[i] & ~1u, pb[i] & 1u) ^ 1u;
                    if (busy < win) break;
                    if (++it > SPIN_MAX) __trap();
                }
#pragma unroll
                for (int i = 0; i + 1 < WHI; i++) pb[i] = pb[i + 1];
                pb[WHI - 1] = bar | par;
            };
            auto side = [&](const CUtensorMap* m, uint32_t dst, int bidx, int c1, int c2, uint32_t wina) {
                const uint32_t bar = bars + bidx * 8;
                pace(bar, 0, wina);
                mbar_expect(bar, CH);
                tma3d(dst, m, c1, c2, bar, pol);
            };
#pragma unroll 1
            for (int i = WIN; i < 6; i++)
                side(&maps.wqB + (i >> 1), sm + OFF_S0 + i * CH, B_WQB + i, j * 128 + (i & 1) * 64, h * 2, sm + OFF_WIN);
            TS(1);
            uint32_t slot = 0, use = 0;
            int nuv = 0;
#pragma unroll 1
            for (int n = 0; n < 2 * NTILE; n++) {
                if (n == RING) {
                    mbar_wait(bars + B_FREE * 8, 0);
#pragma unroll 1
                    for (int q = 0; q < 4; q++) side(&maps.ckv, sm + OFF_S0 + q * CH, B_CKV + q, cta * 64 + q * 16, 0, sm + OFF_WIN);
                }
                if (nuv < 2 && n > RING && (n >= 2 * NTILE - 8 || mbar_test(bars + B_FREE * 8, 1))) {
                    mbar_wait(bars + B_FREE * 8, 1);
                    side(&maps.wuv, sm + OFF_S1 + nuv * CH, B_WUV + nuv, j * 128 + nuv * 64, h * 2, sm + OFF_WIN);
                    nuv++;
                }
                const uint32_t fb = bars + slot * 8;
                pace(fb, use & 1, sm + OFF_WIN);
                mbar_wait(fb + B_EMPTY * 8, (use & 1) ^ 1);
                mbar_expect(fb, CH);
                bulk1d(sm + OFF_RING + slot * CH, ((n & 1) ? vp : kp) + (size_t)(n >> 1) * CH, fb, pol);
                asm volatile("red.relaxed.gpu.global.add.u32 [%0], 1;" ::"l"(&g_cnt[64]) : "memory");
                stsv(sm + OFF_NOW, n + 1);
                if (++slot == RING) { slot = 0; use++; }
            }
            TS(2);
            mbar_wait(bars + B_FREE * 8, 0);
#pragma unroll 1
            for (int i = 0; i < 4; i++) {
                const uint32_t bar = bars + (B_WO + 2 * i) * 8;
                pace(bar + 8, 0, sm + OFF_TWIN);
#pragma unroll
                for (int k = 0; k < 2; k++) {
                    mbar_expect(bar + k * 8, CH / 2);
                    tma3d(sm + OFF_S0 + i * CH + k * (CH / 2), &maps.woB + (i >> 1), (i & 1) * 64 + k * 32, h & ~3, bar + k * 8, pol, (cta & 15) * 32);
                }
            }
            TS(3);
        }
    } else if (warp == 13) {
        if (lane == 0) {
#pragma unroll
            for (int i = 0; i < NBAR; i++)
                if (i < B_WQB || i >= B_WQB + WIN)
                    mbar_init(bars + i * 8, i == B_FREE ? 8 : (i >= B_EMPTY && i < B_EMPTY + RING) ? 4 : 1);
            asm volatile("fence.mbarrier_init.release.cluster;" ::: "memory");
#pragma unroll
            for (int i = 2; i < 8; i++) asm volatile("prefetch.tensormap [%0];" ::"l"(&maps.wqB + i) : "memory");
            stsv(sm + OFF_NOW, 0); stsv(sm + OFF_WIN, WIN); stsv(sm + OFF_TWIN, PREWIN);
        }
        __syncwarp();
        bar_arrive(3, 64);
        bar_sync(0, NTHREADS);
        if (lane == 0) {
            const uint32_t base = (lds32(sm + OFF_TAG) - 1u) * (NCTA * 2 * NTILE);
            mbar_wait(bars + (B_WUK + 1) * 8, 0);
            uint32_t it = 0;
            while (true) {
                const uint32_t n = ldsv(sm + OFF_NOW);
                uint32_t v;
                asm volatile("ld.relaxed.gpu.global.u32 %0, [%1];" : "=r"(v) : "l"(&g_cnt[64]) : "memory");
                v -= base;
                if (v >= NCTA * 2 * NTILE - GATE_W) break;
                const int diff = (int)(n * NCTA) - (int)v;
                stsv(sm + OFF_WIN, diff < -THETA ? WHI : WIN - (diff > THETA) - (v >= NCTA * END_V));
                if (++it > SPIN_MAX) __trap();
                __nanosleep(BACKOFF2);
            }
            stsv(sm + OFF_WIN, WHI); stsv(sm + OFF_TWIN, TAILWIN);
            TS(24);
        }
    } else if (warp < 4) {
        const int g = lane >> 2, t = lane & 3, i = lane >> 3, rr = lane & 7;
        if (tid == 0) {
            const unsigned e = atomicAdd(&g_epoch, 1u);
            sts32(sm + OFF_TAG, (e >> 7) + 1u);
        }
        bar_sync(0, NTHREADS);
        const uint32_t tag = lds32(sm + OFF_TAG);
        {
            mbar_wait(bars + 8, 0);
            float q0, q1;
            ll_gather4(&g_e1[0][h * 4][tid], tag, q0, q1);
            sts16(sm + OFF_QB + tid * 2, f2bf((j >> 1) ? q1 : q0));
        }
        bar_sync(1, 128);
        if (tid == 0) TS(4);
        uint32_t qf[8][2];
#pragma unroll
        for (int c = 0; c < 8; c++) {
            const uint32_t a = sm + OFF_QB + (((c + g) & 7) * 8 + 2 * t) * 2;
            qf[c][0] = lds32(a); qf[c][1] = lds32(a + 128);
        }
        float acc[8][4];
#pragma unroll
        for (int c = 0; c < 8; c++) { acc[c][0] = acc[c][1] = acc[c][2] = acc[c][3] = 0.f; }
        float m = -INFINITY, l = 0.f;
        const bool diag = (t == (g >> 1));
        const uint32_t krow = sm + OFF_RING + (warp * 16 + rr + 8 * (i & 1)) * 256 + (i >> 1) * 128;
        const uint32_t vrow = sm + OFF_RING + (warp * 16 + rr + 8 * (i >> 1)) * 256 + (i & 1) * 128;
        uint32_t slot = 0, ph = 0;
        uint32_t* const e5own = pin((uint32_t*)g_e5[cta] + tid);
        uint32_t a[8][4], b0, b1;
#pragma unroll 1
        for (int tile = 0;; tile++) {
            mbar_wait(bars + slot * 8, ph);
#pragma unroll
            for (int c = 0; c < 8; c++) ldsm4(a[c], krow + slot * CH + (((c + rr) & 7) << 4));
            __syncwarp();
            if (lane == 0) mbar_arrive(bars + (B_EMPTY + slot) * 8 + ((a[0][0] | a[1][0] | a[2][0] | a[3][0] | a[4][0] | a[5][0] | a[6][0] | a[7][0]) & zero));
            if (++slot == RING) { slot = 0; ph ^= 1; }
            float s0[4] = {0.f, 0.f, 0.f, 0.f}, s1[4] = {0.f, 0.f, 0.f, 0.f};
#pragma unroll
            for (int c = 0; c < 8; c += 2) { mma(s0, a[c], qf[c][0], qf[c][1]); mma(s1, a[c + 1], qf[c + 1][0], qf[c + 1][1]); }
            float slo = (g & 1) ? s0[1] + s1[1] : s0[0] + s1[0];
            float shi = (g & 1) ? s0[3] + s1[3] : s0[2] + s1[2];
            slo = diag ? bfround(bfround(slo) * SCALE) : -INFINITY;
            shi = diag ? bfround(bfround(shi) * SCALE) : -INFINITY;
            int key = __float_as_int(fmaxf(slo, shi));
            key ^= (key >> 31) & 0x7fffffff;
            key = __reduce_max_sync(0xffffffffu, key);
            key ^= (key >> 31) & 0x7fffffff;
            const float mn = fmaxf(m, __int_as_float(key));
            const float alpha = ex2((m - mn) * LOG2E);
            m = mn;
            const float plo = ex2((slo - mn) * LOG2E), phi = ex2((shi - mn) * LOG2E);
            l = l * alpha + (plo + phi);
            b0 = (g & 1) ? pack2(0.f, plo) : pack2(plo, 0.f);
            b1 = (g & 1) ? pack2(0.f, phi) : pack2(phi, 0.f);
#pragma unroll
            for (int c = 0; c < 8; c++) { acc[c][0] *= alpha; acc[c][1] *= alpha; acc[c][2] *= alpha; acc[c][3] *= alpha; }
            if (tile == NTILE - 1) break;
            mbar_wait(bars + slot * 8, ph);
#pragma unroll
            for (int c = 0; c < 8; c++) ldsm4t(a[c], vrow + slot * CH + (((c + rr) & 7) << 4));
            __syncwarp();
            if (lane == 0) mbar_arrive(bars + (B_EMPTY + slot) * 8 + ((a[0][0] | a[1][0] | a[2][0] | a[3][0] | a[4][0] | a[5][0] | a[6][0] | a[7][0]) & zero));
            if (++slot == RING) { slot = 0; ph ^= 1; }
#pragma unroll
            for (int c = 0; c < 8; c++) mma(acc[c], a[c], b0, b1);
        }
#pragma unroll
        for (int o = 16; o; o >>= 1) l += __shfl_xor_sync(0xffffffffu, l, o);
        if (lane == 0) stsf2(sm + OFF_ML + warp * 8, m, l);
        mbar_wait(bars + B_S2 * 8, 0);
        bar_sync(1, 128);
        {
            const uint4 ml0 = lds128(sm + OFF_ML), ml1 = lds128(sm + OFF_ML + 16);
            const float m0 = __uint_as_float(ml0.x), m1 = __uint_as_float(ml0.z), m2 = __uint_as_float(ml1.x), m3 = __uint_as_float(ml1.z);
            const float M = fmaxf(fmaxf(m0, m1), fmaxf(m2, m3));
            const float L = (ex2((m0 - M) * LOG2E) * __uint_as_float(ml0.y) + ex2((m1 - M) * LOG2E) * __uint_as_float(ml0.w))
                          + (ex2((m2 - M) * LOG2E) * __uint_as_float(ml1.y) + ex2((m3 - M) * LOG2E) * __uint_as_float(ml1.w));
            const float f = ex2((m - M) * LOG2E) * rcp(L);
            if (tid == 0) mail_put((float*)g_l5[h] + j, M * LOG2E + lg2(L));
            const uint32_t wa = sm + OFF_S2 + warp * 640 + (t * 16 + (t >> 1) * 8 + g) * 4;
            const uint32_t ra = sm + OFF_S2 + ((tid >> 4 & 1) * 40 + (tid & 2) * 40 + (tid >> 5) * 16 + (tid & 1) * 8 + (tid >> 2 & 3) * 2) * 4;
            mbar_wait(bars + slot * 8, ph);
#pragma unroll
            for (int c = 0; c < 8; c++) ldsm4t(a[c], vrow + slot * CH + (((c + rr) & 7) << 4));
#pragma unroll
            for (int c = 0; c < 8; c++) mma(acc[c], a[c], b0, b1);
            if (tid == 0) TS(5);
            float v[2][8];
#pragma unroll
            for (int c = 0; c < 8; c++) { v[0][c] = acc[c][0] + acc[(c + 7) & 7][1]; v[1][c] = acc[c][2] + acc[(c + 7) & 7][3]; }
#pragma unroll
            for (int c = 0; c < 4; c++) { v[0][c] += __shfl_xor_sync(0xffffffffu, v[0][c + 4], 2); v[1][c] += __shfl_xor_sync(0xffffffffu, v[1][c + 4], 2); }
            const int src = (lane & ~3) | ((lane + 3) & 3);
#pragma unroll
            for (int c = 0; c < 2; c++) { v[0][c] += __shfl_sync(0xffffffffu, v[0][c + 2], src); v[1][c] += __shfl_sync(0xffffffffu, v[1][c + 2], src); }
#pragma unroll
            for (int c = 0; c < 4; c++) sts32(wa + (c >> 1) * 320 + (c & 1) * 32, __float_as_uint(v[c >> 1][c & 1] * f));
            if (warp < 2) {
                bar_sync(1, 128);
                const float2 r0 = ldsf2(ra), r1 = ldsf2(ra + 640), r2 = ldsf2(ra + 1280), r3 = ldsf2(ra + 1920);
                mail_put(e5own, pack2((r0.x + r1.x) + (r2.x + r3.x), (r0.y + r1.y) + (r2.y + r3.y)));
            } else {
                bar_arrive(1, 128);
            }
        }
        if (tid == 0) TS(6);
        {
            uint32_t x[4][4][4];
            float d[4][4];
            bar_sync(4, 256 + 128);
#pragma unroll
            for (int k = 0; k < 16; k++) ldsm4(x[k >> 2][k & 3], sm + OFF_CA + ((k >> 2) * 2 + (lane & 1)) * VROW + (k & 3) * 64 + i * 16);
#pragma unroll
            for (int k = 0; k < 4; k++) d[k][0] = d[k][1] = d[k][2] = d[k][3] = 0.f;
            const uint32_t wa = sm + OFF_S1 + lane * 64 + ((warp ^ (rr >> 1)) << 4);
            __nv_bfloat16* const outp = pin(out + (g & 1) * 1024 + (cta & 15) * 32 + warp * 8 + t * 2);
#pragma unroll
            for (int q = 0; q < 4; q++) {
                mbar_wait(bars + (B_WO + 4 + q) * 8, 0);
                if (q == 3 && tid == 0) TS(25);
#pragma unroll
                for (int k = 0; k < 4; k++) ldsm4t(a[k], wa + q * 8192 + k * 2048);
#pragma unroll
                for (int k = 0; k < 8; k++) {
                    const uint32_t u0 = x[k & 3][q][(k >> 2) * 2], u1 = x[k & 3][q][(k >> 2) * 2 + 1], u[4] = {u0, u0, u1, u1};
                    mma(d[k & 3], u, a[k & 3][(k >> 2) * 2], a[k & 3][(k >> 2) * 2 + 1]);
                }
            }
            if (lane < 8) out_add(outp, (d[0][0] + d[1][0]) + (d[2][0] + d[3][0]), (d[0][1] + d[1][1]) + (d[2][1] + d[3][1]));
            if (tid == 0) TS(15);
        }
    } else {
        const int st = tid - 128, w = warp - 4;
        const int g = lane >> 2, t = lane & 3, i = lane >> 3, rr = lane & 7;
        if (t == 0) {
#pragma unroll
            for (int k = 0; k < 4; k++) ll_store2(&g_e1[k >> 1][cta][w * 16 + g + (k & 1) * 8], 0.f, 0.f, 0u);
        }
        if (st < 64) {
            const int which = st >> 5, b = (st >> 4) & 1, c = st & 15;
            const uint4 v = __ldg((const uint4*)((which ? xA : xB) + b * 512 + j * 128) + c);
            sts128(sm + OFF_XB + (which * 2 + b) * VROW + c * 16, v);
        }
        bar_sync(0, NTHREADS);
        const uint32_t tag = lds32(sm + OFF_TAG);
        float c[4];
#pragma unroll 1
        for (int which = 0; which < 2; which++) {
            matvecT(c, sm + OFF_S0 + which * 2 * CH, sm + OFF_XB + which * 2 * VROW, 2, bars + (B_WQB + which * 2) * 8, w, lane);
            if (t == 0) {
                ll_store2(&g_e1[which][cta][w * 16 + g], c[0], c[1], tag);
                ll_store2(&g_e1[which][cta][w * 16 + g + 8], c[2], c[3], tag);
            }
        }
        __syncwarp();
        if (lane == 0) mbar_arrive(bars + B_FREE * 8);
        if (st == 0) TS(8);
        if (st < 128) {
            float q0, q1;
            sleep_ns(POLL_DELAY);
            ll_gather4(&g_e1[1][h * 4][st], tag, q0, q1);
            sts16(sm + OFF_QA + st * 2, f2bf(q0)); sts16(sm + OFF_QA + VROW + st * 2, f2bf(q1));
        }
        bar_sync(2, 256);
        if (st == 0) TS(9);
        {
            const int row = w * 16 + rr + 8 * (i & 1);
            const uint32_t a0 = sm + OFF_S2 + (row >> 6) * CH + (row & 63) * 128;
            const uint32_t va = sm + OFF_QA + g * VROW + t * 4;
            float d[4] = {0.f, 0.f, 0.f, 0.f};
            c[0] = c[1] = c[2] = c[3] = 0.f;
            mbar_wait(bars + (B_WUK + (w >> 2)) * 8, 0);
#pragma unroll
            for (int ks = 0; ks < 8; ks++) {
                const int chunk = 2 * ks + (i >> 1);
                uint32_t a[4];
                ldsm4(a, a0 + (chunk >> 3) * 8192 + (((chunk & 7) ^ rr) << 4));
                const uint32_t b0 = (g < 2) ? lds32(va + ks * 32) : 0u, b1 = (g < 2) ? lds32(va + ks * 32 + 16) : 0u;
                if (ks & 1) mma(d, a, b0, b1); else mma(c, a, b0, b1);
            }
            if (t == 0) {
                const uint32_t qs = sm + OFF_QS + (w * 16 + g) * 2;
                sts16(qs, f2bf(c[0] + d[0])); sts16(qs + VROW, f2bf(c[1] + d[1]));
                sts16(qs + 16, f2bf(c[2] + d[2])); sts16(qs + VROW + 16, f2bf(c[3] + d[3]));
            }
            bar_sync(2, 256);
            if (w == 0) {
                const int b = lane >> 4, cc = lane & 15;
                g_qabs[(b * 32 + h) * 64 + ((j * 16 + cc) ^ (h & 7))] = lds128(sm + OFF_QS + b * VROW + cc * 16);
                __syncwarp();
                if (lane == 0) {
                    cnt_rendezvous(&g_cnt[0], tag * 128u, 18);
                    TS(10);
                    mbar_expect(bars + B_GATH * 8, 2 * CH);
                    bulk1d_n(sm + OFF_S2, g_qabs + (cta >> 6) * 2048, 2 * CH, bars + B_GATH * 8);
                }
                __syncwarp();
            }
        }
        mbar_wait(bars + B_GATH * 8, 0);
        if (st == 0) TS(11);
        {
            const int mt = w & 1, kg = w >> 1;
            const uint32_t qa = sm + OFF_S2 + (mt * 16 + rr + 8 * (i & 1)) * 1024;
            const uint32_t ka = sm + OFF_S0 + kg * CH + (rr + 8 * (i >> 1)) * 128;
            float s0[4] = {0.f, 0.f, 0.f, 0.f}, s1[4] = {0.f, 0.f, 0.f, 0.f};
            mbar_wait(bars + (B_CKV + kg) * 8, 0);
#pragma unroll 2
            for (int gq = 0; gq < 8; gq++) {
#pragma unroll
                for (int k4 = 0; k4 < 4; k4++) {
                    uint32_t a[4], b[4];
                    ldsm4(a, qa + gq * 128 + (((2 * k4 + (i >> 1)) ^ rr) << 4));
                    ldsm4(b, ka + gq * 2048 + (((2 * k4 + (i & 1)) ^ rr) << 4));
                    mma(s0, a, b[0], b[1]);
                    mma(s1, a, b[2], b[3]);
                }
            }
            const uint32_t sa = sm + OFF_SC + ((mt * 16 + g) * 68 + kg * 16 + 2 * t) * 4;
            stsf2(sa, s0[0], s0[1]); stsf2(sa + 32, s1[0], s1[1]);
            stsf2(sa + 8 * 68 * 4, s0[2], s0[3]); stsf2(sa + 8 * 68 * 4 + 32, s1[2], s1[3]);
        }
        bar_sync(2, 256);
        {
            const int head = w * 4 + i;
            const uint32_t sa = sm + OFF_SC + (head * 68 + rr * 8) * 4;
            const uint4 u0 = lds128(sa), u1 = lds128(sa + 16);
            float s[8] = {__uint_as_float(u0.x), __uint_as_float(u0.y), __uint_as_float(u0.z), __uint_as_float(u0.w),
                          __uint_as_float(u1.x), __uint_as_float(u1.y), __uint_as_float(u1.z), __uint_as_float(u1.w)};
            float mx = s[0];
#pragma unroll
            for (int k = 1; k < 8; k++) mx = fmaxf(mx, s[k]);
#pragma unroll
            for (int o = 1; o < 8; o <<= 1) mx = fmaxf(mx, __shfl_xor_sync(0xffffffffu, mx, o));
            float sum = 0.f;
#pragma unroll
            for (int k = 0; k < 8; k++) { s[k] = ex2((s[k] - mx) * (SCALE * LOG2E)); sum += s[k]; }
#pragma unroll
            for (int o = 1; o < 8; o <<= 1) sum += __shfl_xor_sync(0xffffffffu, sum, o);
            const float inv = __fdividef(1.f, sum);
            uint4 p;
            p.x = pack2(s[0] * inv, s[1] * inv); p.y = pack2(s[2] * inv, s[3] * inv);
            p.z = pack2(s[4] * inv, s[5] * inv); p.w = pack2(s[6] * inv, s[7] * inv);
            sts128(sm + OFF_P + head * 128 + ((rr ^ (head & 7)) << 4), p);
            if (rr == 0) ((float*)g_lse)[head * 128 + cta] = mx * (SCALE * LOG2E) + lg2(sum);
        }
        bar_sync(2, 256);
        {
            float o[2][8][4];
#pragma unroll
            for (int mt = 0; mt < 2; mt++)
#pragma unroll
                for (int n = 0; n < 8; n++) { o[mt][n][0] = o[mt][n][1] = o[mt][n][2] = o[mt][n][3] = 0.f; }
            const uint32_t pa = sm + OFF_P + (rr + 8 * (i & 1)) * 128;
            const uint32_t va = sm + OFF_S0 + w * 2048 + (rr + 8 * (i & 1)) * 128;
#pragma unroll 1
            for (int kq = 0; kq < 4; kq++) {
                uint32_t a0[4], a1[4];
                ldsm4(a0, pa + (((2 * kq + (i >> 1)) ^ rr) << 4));
                ldsm4(a1, pa + 2048 + (((2 * kq + (i >> 1)) ^ rr) << 4));
#pragma unroll
                for (int n = 0; n < 8; n += 2) {
                    uint32_t b[4];
                    ldsm4t(b, va + kq * CH + (((n + (i >> 1)) ^ rr) << 4));
                    mma(o[0][n], a0, b[0], b[1]); mma(o[1][n], a1, b[0], b[1]);
                    mma(o[0][n + 1], a0, b[2], b[3]); mma(o[1][n + 1], a1, b[2], b[3]);
                }
            }
#pragma unroll
            for (int mt = 0; mt < 2; mt++)
#pragma unroll
                for (int hf = 0; hf < 2; hf++) {
                    const uint32_t dst = sm + OFF_S2 + (mt * 16 + hf * 8 + g) * 1024 + w * 128 + t * 16;
#pragma unroll
                    for (int nb = 0; nb < 2; nb++) {
                        uint4 v;
                        v.x = pack2(o[mt][nb * 4 + 0][hf * 2], o[mt][nb * 4 + 0][hf * 2 + 1]);
                        v.y = pack2(o[mt][nb * 4 + 1][hf * 2], o[mt][nb * 4 + 1][hf * 2 + 1]);
                        v.z = pack2(o[mt][nb * 4 + 2][hf * 2], o[mt][nb * 4 + 2][hf * 2 + 1]);
                        v.w = pack2(o[mt][nb * 4 + 3][hf * 2], o[mt][nb * 4 + 3][hf * 2 + 1]);
                        sts128(dst + nb * 64, v);
                    }
                }
            asm volatile("fence.proxy.async.shared::cta;" ::: "memory");
            __syncwarp();
            if (lane == 0) mbar_arrive(bars + B_FREE * 8);
            if (st < 82) *(st < 64 ? &g_e4[cta][st] : st < 80 ? &g_e5[cta][st - 64] : &g_l5[h][j * 2 + st - 80]) = make_uint4(EMPTY, EMPTY, EMPTY, EMPTY);
            else if (st < 84) ((uint4*)out)[cta * 2 + st - 82] = make_uint4(0u, 0u, 0u, 0u);
        }
        bar_sync(2, 256);
        if (st == 0) {
            TS(12);
#pragma unroll 1
            for (int k = 0; k < ST_SPLIT; k++) {
                asm volatile("cp.async.bulk.tensor.3d.global.shared::cta.bulk_group [%0, {%2,%3,%4}], [%1];"
                             ::"l"(&maps.ctxp), "r"(sm + OFF_S2 + k * (2 * CH / ST_SPLIT)), "r"(0), "r"(cta), "r"(k * (128 / ST_SPLIT)) : "memory");
                if (k + 1 < ST_SPLIT) __nanosleep(ST_GAP);
            }
            asm volatile("cp.async.bulk.commit_group;" ::: "memory");
            asm volatile("cp.async.bulk.wait_group 0;" ::: "memory");
            cnt_rendezvous(&g_cnt[32], tag * 128u, 20);
            TS(13);
            mbar_expect(bars + B_GATH * 8, 2 * CH + 512);
            bulk1d_n(sm + OFF_LSE, g_lse + h * 32, 512, bars + B_GATH * 8);
            bulk1d_n(sm + OFF_S2, g_ctxp + cta * 2048, 2 * CH, bars + B_GATH * 8);
        }
        __syncwarp();
        {
            mbar_wait(bars + B_GATH * 8, 1);
            if (st == 0) TS(22);
            uint4 v[8];
#pragma unroll
            for (int k = 0; k < 8; k++) v[k] = lds128(sm + OFF_S2 + (k * 256 + st) * 16);
            float ls[4];
#pragma unroll
            for (int k = 0; k < 4; k++) ls[k] = ldsf(sm + OFF_LSE + (k * 32 + lane) * 4);
            float m0 = fmaxf(ls[0], ls[1]), m1 = fmaxf(ls[2], ls[3]);
#pragma unroll
            for (int o = 16; o; o >>= 1) { m0 = fmaxf(m0, __shfl_xor_sync(0xffffffffu, m0, o)); m1 = fmaxf(m1, __shfl_xor_sync(0xffffffffu, m1, o)); }
            ls[0] = ex2(ls[0] - m0); ls[1] = ex2(ls[1] - m0); ls[2] = ex2(ls[2] - m1); ls[3] = ex2(ls[3] - m1);
            float z0 = ls[0] + ls[1], z1 = ls[2] + ls[3];
#pragma unroll
            for (int o = 16; o; o >>= 1) { z0 += __shfl_xor_sync(0xffffffffu, z0, o); z1 += __shfl_xor_sync(0xffffffffu, z1, o); }
            z0 = __fdividef(1.f, z0); z1 = __fdividef(1.f, z1);
            ls[0] *= z0; ls[1] *= z0; ls[2] *= z1; ls[3] *= z1;
            float a[2][8];
#pragma unroll
            for (int e = 0; e < 8; e++) a[0][e] = a[1][e] = 0.f;
            const int rg = st >> 4;
#pragma unroll
            for (int k = 0; k < 8; k++) {
                const float wt = __shfl_sync(0xffffffffu, ls[k >> 1], rg + 16 * (k & 1));
                const uint32_t u[4] = {v[k].x, v[k].y, v[k].z, v[k].w};
#pragma unroll
                for (int e = 0; e < 4; e++) {
                    a[k >> 2][2 * e] += wt * __uint_as_float(u[e] << 16);
                    a[k >> 2][2 * e + 1] += wt * __uint_as_float(u[e] & 0xffff0000u);
                }
            }
            const int b = lane >> 4, u16 = lane & 15;
            const uint32_t ra = sm + OFF_SC + (w * 256 + b * 128 + (u16 >> 3) * 64 + ((u16 >> 2) & 1) * 32 + (u16 & 3) * 2) * 4;
#pragma unroll
            for (int e = 0; e < 8; e += 2) {
                const float k0 = b ? a[1][e] : a[0][e], k1 = b ? a[1][e + 1] : a[0][e + 1];
                const float s0 = b ? a[0][e] : a[1][e], s1 = b ? a[0][e + 1] : a[1][e + 1];
                stsf2(ra + (e >> 1) * 32, k0 + __shfl_xor_sync(0xffffffffu, s0, 16), k1 + __shfl_xor_sync(0xffffffffu, s1, 16));
            }
            bar_sync(2, 256);
            if (st == 0) mbar_arrive(bars + B_S2 * 8);
            float s = 0.f;
#pragma unroll
            for (int k = 0; k < 8; k++) s += ldsf(sm + OFF_SC + (k * 256 + st) * 4);
            const float hi = bfround(s);
            const uint32_t ca = sm + OFF_CC + (st >> 7) * VROW + (st & 127) * 2;
            sts16(ca, f2bf(hi)); sts16(ca + 2 * VROW, f2bf(s - hi));
            bar_sync(2, 256);
        }
        matvecT(c, sm + OFF_S1, sm + OFF_CC, 4, bars + B_WUV * 8, w, lane);
#pragma unroll
        for (int k = 0; k < 4; k++) c[k] += __shfl_down_sync(0xffffffffu, c[k], 1);
        if (t == 0) {
            float* const e = (float*)g_e4[cta] + w * 16 + g;
            mail_put(e, c[0]); mail_put(e + 128, c[1]); mail_put(e + 8, c[2]); mail_put(e + 136, c[3]);
        }
        __syncwarp();
        if (lane == 0) mbar_arrive(bars + B_FREE * 8);
        if (st == 0) TS(23);
        {
            const uint4* const pv = &g_e4[(cta & ~15) + (w >> 1) * 4][(w & 1) * 32 + lane];
            uint4 x[4];
            uint32_t it = 0;
            sleep_ns(POLL_DELAY2);
            while (true) {
#pragma unroll
                for (int k = 0; k < 4; k++) { x[k].x = x[k].y = x[k].z = x[k].w = 0u; mail_get(x[k], pv + k * 64); }
                if (!__any_sync(0xffffffffu, mail_missing(x[0]) | mail_missing(x[1]) | mail_missing(x[2]) | mail_missing(x[3]))) break;
                if (++it > SPIN_MAX) __trap();
                __nanosleep(BACKOFF);
            }
#define SUM4(e) ((__uint_as_float(x[0].e) + __uint_as_float(x[1].e)) + (__uint_as_float(x[2].e) + __uint_as_float(x[3].e)))
            sts64(sm + OFF_CA + w * VROW + lane * 8, pack2(SUM4(x), SUM4(y)), pack2(SUM4(z), SUM4(w)));
#undef SUM4
        }
        if (st == 0) TS(14);
        bar_arrive(4, 256 + 128);
        {
            const uint32_t a0 = sm + OFF_S0 + w * 1024 + (rr + 8 * (i >> 1)) * 64 + (((i & 1) ^ (rr >> 1)) << 4);
            const uint4* const pv = pin(&g_e5[(cta & ~15) + (w >> 1) * 4 + (g & 3)][(w & 1) * 8 + (g >> 2) * 4 + t]);
            const uint4* const pl = pin(g_l5[(h & ~3) + (w >> 1)]);
            const uint32_t wa = sm + OFF_SC + ((w * 2 + (t >> 1)) * 80 + (t & 1) * 40 + g) * 4;
            __nv_bfloat16* const outp = pin(out + (lane >> 4) * 1024 + 512 + (cta & 15) * 32 + (lane & 15) * 2);
            uint32_t a[4][2][4];
            uint4 x, xl;
            x.x = xl.x = EMPTY; x.y = x.z = x.w = xl.y = xl.z = xl.w = 0u;
#pragma unroll
            for (int q = 0; q < 4; q++) {
                mbar_wait(bars + (B_WO + q) * 8, 0);
                if (q == POLL_Q) { mail_get(x, pv); mail_get(xl, pl); }
                ldsm4t(a[q][0], a0 + q * 8192);
                ldsm4t(a[q][1], (a0 ^ 32) + q * 8192);
            }
            if (st == 0) TS(26);
            uint32_t it = 0;
            while (true) {
                const bool n = mail_missing(x), nl = mail_missing(xl);
                if (!__any_sync(0xffffffffu, n | nl)) break;
                if (POLL_GAP) __nanosleep(POLL_GAP);
                mail_get(x, pv, n); mail_get(xl, pl, nl);
                if (++it > SPIN_MAX) __trap();
            }
            if (st == 0) TS(16);
            float d[2][2][4];
#pragma unroll
            for (int k = 0; k < 4; k++) {
                float (&dk)[4] = d[k >> 1][k & 1];
                dk[0] = dk[1] = dk[2] = dk[3] = 0.f;
                mma(dk, a[k >> 1][k & 1], x.x, x.y);
            }
#pragma unroll
            for (int k = 0; k < 4; k++) mma(d[k >> 1][k & 1], a[2 + (k >> 1)][k & 1], x.z, x.w);
            float w0, w1;
            merge_weights((t & 1) ? xl.z : xl.x, (t & 1) ? xl.w : xl.y, w0, w1);
#pragma unroll
            for (int k = 0; k < 4; k++) {
                const float s0 = (t & 2) ? d[1][k >> 1][(k & 1) * 2] : d[0][k >> 1][(k & 1) * 2];
                const float s1 = (t & 2) ? d[1][k >> 1][(k & 1) * 2 + 1] : d[0][k >> 1][(k & 1) * 2 + 1];
                sts32(wa + k * 32, __float_as_uint(w0 * s0 + w1 * s1));
            }
            if (st == 0) TS(17);
            if (w == 0) {
                bar_sync(5, 256);
                const uint32_t ra = sm + OFF_SC + ((lane >> 4) * 40 + (lane & 15) * 2) * 4;
                float2 r[16];
#pragma unroll
                for (int k = 0; k < 16; k++) r[k] = ldsf2(ra + k * 320);
#pragma unroll
                for (int o = 1; o < 16; o <<= 1)
#pragma unroll
                    for (int k = 0; k < 16; k += 2 * o) { r[k].x += r[k + o].x; r[k].y += r[k + o].y; }
                out_add(outp, r[0].x, r[0].y);
            } else {
                bar_arrive(5, 256);
            }
        }
    }
}

typedef CUresult (*EncodeFn)(CUtensorMap*, CUtensorMapDataType, cuuint32_t, void*, const cuuint64_t*, const cuuint64_t*,
                             const cuuint32_t*, const cuuint32_t*, CUtensorMapInterleave, CUtensorMapSwizzle,
                             CUtensorMapL2promotion, CUtensorMapFloatOOBfill);

void make_map(EncodeFn enc, CUtensorMap* m, void* p, unsigned rows, unsigned cols, unsigned br, unsigned bg) {
    cuuint64_t gd[3] = {64, rows, cols / 64};
    cuuint64_t gs[2] = {(cuuint64_t)cols * 2, 128};
    cuuint32_t bx[3] = {64, br, bg};
    cuuint32_t es[3] = {1, 1, 1};
    enc(m, CU_TENSOR_MAP_DATA_TYPE_BFLOAT16, 3, p, gd, gs, bx, es, CU_TENSOR_MAP_INTERLEAVE_NONE,
        CU_TENSOR_MAP_SWIZZLE_128B, CU_TENSOR_MAP_L2_PROMOTION_L2_128B, CU_TENSOR_MAP_FLOAT_OOB_FILL_NONE);
}

}

extern "C" void kernel_launch(void* const* d_in, const int* in_sizes, int n_in, void* d_out, int out_size) {
    static EncodeFn enc = nullptr;
    if (!enc) {
        void* fn = nullptr;
        cudaDriverEntryPointQueryResult qr;
        cudaGetDriverEntryPoint("cuTensorMapEncodeTiled", &fn, cudaEnableDefault, &qr);
        enc = (EncodeFn)fn;
        cudaFuncSetAttribute(fused_decode_kernel, cudaFuncAttributeMaxDynamicSharedMemorySize, SMEM_BYTES);
    }
    Maps maps;
    make_map(enc, &maps.wqB, d_in[9], 512, 4096, 64, 2);
    make_map(enc, &maps.wqA, d_in[2], 512, 4096, 64, 2);
    make_map(enc, &maps.wuk, d_in[3], 512, 4096, 64, 2);
    make_map(enc, &maps.wuv, d_in[4], 512, 4096, 64, 2);
    for (int k = 0; k < 2; k++) {
        cuuint64_t gd[3] = {512, 128, 32};
        cuuint64_t gs[2] = {1024, 131072};
        cuuint32_t bx[3] = {32, 32, 4};
        cuuint32_t es[3] = {1, 1, 1};
        enc(&maps.woB + k, CU_TENSOR_MAP_DATA_TYPE_BFLOAT16, 3, d_in[k ? 5 : 10], gd, gs, bx, es, CU_TENSOR_MAP_INTERLEAVE_NONE,
            CU_TENSOR_MAP_SWIZZLE_64B, (CUtensorMapL2promotion)WOPROMO, CU_TENSOR_MAP_FLOAT_OOB_FILL_NONE);
    }
    make_map(enc, &maps.ckv, d_in[1], 8192, 512, 16, 8);
    {
        void* p = nullptr;
        cudaGetSymbolAddress(&p, g_ctxp);
        cuuint64_t gd[3] = {128, 128, 128};
        cuuint64_t gs[2] = {256, 32768};
        cuuint32_t bx[3] = {128, 1, 128 / ST_SPLIT};
        cuuint32_t es[3] = {1, 1, 1};
        enc(&maps.ctxp, CU_TENSOR_MAP_DATA_TYPE_BFLOAT16, 3, p, gd, gs, bx, es, CU_TENSOR_MAP_INTERLEAVE_NONE,
            CU_TENSOR_MAP_SWIZZLE_NONE, CU_TENSOR_MAP_L2_PROMOTION_NONE, CU_TENSOR_MAP_FLOAT_OOB_FILL_NONE);
    }
    fused_decode_kernel<<<NCTA, NTHREADS, SMEM_BYTES>>>((const char*)d_in[9], maps, (const char*)d_in[7], (const char*)d_in[8],
                                                         (const __nv_bfloat16*)d_in[0], (const __nv_bfloat16*)d_in[6],
                                                         (__nv_bfloat16*)d_out, 0u);
}
```

```cpp
#include <cuda_runtime.h>
#include <cuda.h>
#include <cuda_bf16.h>
#include <stdint.h>

#define RING 7
#define WIN 4
#define WHI 5
#define THETA 64
#define END_V 40
#define GATE_W 64
#define PREWIN 2
#define TAILWIN 3
#define POLL_Q 0
#define POLL_GAP 0
#define WOPROMO CU_TENSOR_MAP_L2_PROMOTION_L2_256B
#define POLL_DELAY 2500
#define POLL_DELAY2 4000
#define ST_SPLIT 8
#define ST_GAP 500
#define BACKOFF 200
#define BACKOFF2 100

namespace {

constexpr int NCTA = 128;
constexpr int NTHREADS = 448;
constexpr uint32_t CH = 16384;
constexpr int NTILE = 32;

constexpr uint32_t OFF_RING = 0;
constexpr uint32_t OFF_S0 = RING * CH;
constexpr uint32_t OFF_S1 = OFF_S0 + 2 * CH;
constexpr uint32_t OFF_S2 = OFF_S1 + 2 * CH;
constexpr uint32_t OFF_P = OFF_S2 + 2 * CH;
constexpr uint32_t OFF_SC = OFF_P + 4096;
constexpr uint32_t VROW = 272;
constexpr uint32_t OFF_XB = OFF_SC + 8704;
constexpr uint32_t OFF_XA = OFF_XB + 2 * VROW;
constexpr uint32_t OFF_QA = OFF_XA + 2 * VROW;
constexpr uint32_t OFF_QS = OFF_QA + 2 * VROW;
constexpr uint32_t OFF_CC = OFF_QS + 2 * VROW;
constexpr uint32_t OFF_CA = OFF_P;
constexpr uint32_t OFF_QB = OFF_CC + 4 * VROW;
constexpr uint32_t OFF_LSE = OFF_QB + 256;
constexpr uint32_t OFF_ML = OFF_LSE + 512;
constexpr uint32_t OFF_TAG = OFF_ML + 32;
constexpr uint32_t OFF_NOW = OFF_TAG + 4;
constexpr uint32_t OFF_WIN = OFF_TAG + 8;
constexpr uint32_t OFF_TWIN = OFF_TAG + 12;
constexpr uint32_t OFF_BAR = OFF_TAG + 16;
constexpr int B_EMPTY = RING;
constexpr int B_WQB = 2 * RING;
constexpr int B_WQA = B_WQB + 2;
constexpr int B_WUK = B_WQA + 2;
constexpr int B_WUV = B_WUK + 2;
constexpr int B_CKV = B_WUV + 2;
constexpr int B_WO = B_CKV + 4;
constexpr int B_FREE = B_WO + 8;
constexpr int B_GATH = B_FREE + 1;
constexpr int B_S2 = B_GATH + 1;
constexpr int NBAR = B_S2 + 1;
constexpr uint32_t TS_OFF = OFF_BAR + NBAR * 8;
constexpr uint32_t SMEM_USED = TS_OFF;
constexpr uint32_t SMEM_BYTES = SMEM_USED + 1024;
static_assert(SMEM_BYTES <= 232448, "smem");
static_assert(RING >= WHI && WHI >= WIN && WIN >= 3 && WIN <= 6, "windows");

constexpr float LOG2E = 1.4426950408889634f;
constexpr float SCALE = 0.08838834764831845f;
#define SPIN_LOG 22
constexpr uint32_t SPIN_MAX = 1u << SPIN_LOG;

struct Maps { CUtensorMap wqB, wqA, wuk, wuv, woB, woA, ckv, ctxp; };

__device__ unsigned g_epoch;
__device__ __align__(256) unsigned g_cnt[96];
__device__ __align__(256) ulonglong2 g_e1[2][NCTA][128];
__device__ __align__(256) uint4 g_qabs[2 * 32 * 64];
__device__ __align__(256) uint4 g_ctxp[NCTA * 128 * 16];
__device__ __align__(256) float4 g_lse[32 * 32];
__device__ __align__(256) uint4 g_e4[NCTA][64];
__device__ __align__(256) uint4 g_e5[NCTA][16];
__device__ __align__(256) uint4 g_l5[32][8];
constexpr uint32_t EMPTY = 0xffffffffu;

#define TS(k) do {} while (0)

__device__ __forceinline__ void mbar_init(uint32_t b, int c) { asm volatile("mbarrier.init.shared::cta.b64 [%0], %1;" ::"r"(b), "r"(c) : "memory"); }
__device__ __forceinline__ void mbar_expect(uint32_t b, uint32_t bytes) { asm volatile("mbarrier.arrive.expect_tx.shared::cta.b64 _, [%0], %1;" ::"r"(b), "r"(bytes) : "memory"); }
__device__ __forceinline__ void mbar_arrive(uint32_t b) { asm volatile("mbarrier.arrive.shared::cta.b64 _, [%0];" ::"r"(b) : "memory"); }
__device__ __forceinline__ void mbar_wait(uint32_t b, uint32_t ph) {
    asm volatile("{\n.reg .pred p;\n.reg .u32 n;\nmov.u32 n, 0;\n"
                 "W:\nmbarrier.try_wait.parity.shared::cta.b64 p, [%0], %1;\n@p bra D;\n"
                 "add.u32 n, n, 1;\nsetp.le.u32 p, n, %2;\n@p bra W;\ntrap;\nD:\n}" ::"r"(b), "r"(ph), "n"(SPIN_MAX) : "memory");
}
__device__ __forceinline__ uint32_t mbar_test(uint32_t b, uint32_t ph) {
    uint32_t ok;
    asm volatile("{\n.reg .pred p;\nmbarrier.test_wait.parity.shared::cta.b64 p, [%1], %2;\nselp.u32 %0, 1, 0, p;\n}" : "=r"(ok) : "r"(b), "r"(ph) : "memory");
    return ok;
}
__device__ __forceinline__ void bulk1d(uint32_t dst, const void* src, uint32_t bar, uint64_t pol) {
    asm volatile("cp.async.bulk.shared::cluster.global.mbarrier::complete_tx::bytes.L2::cache_hint [%0], [%1], %2, [%3], %4;"
                 ::"r"(dst), "l"(src), "n"(CH), "r"(bar), "l"(pol) : "memory");
}
__device__ __forceinline__ void bulk1d_n(uint32_t dst, const void* src, uint32_t bytes, uint32_t bar) {
    asm volatile("cp.async.bulk.shared::cluster.global.mbarrier::complete_tx::bytes [%0], [%1], %2, [%3];"
                 ::"r"(dst), "l"(src), "r"(bytes), "r"(bar) : "memory");
}
__device__ __forceinline__ void tma3d(uint32_t dst, const CUtensorMap* map, int c1, int c2, uint32_t bar, uint64_t pol, int c0 = 0) {
    asm volatile("cp.async.bulk.tensor.3d.shared::cluster.global.mbarrier::complete_tx::bytes.L2::cache_hint [%0], [%1, {%3,%4,%5}], [%2], %6;"
                 ::"r"(dst), "l"(map), "r"(bar), "r"(c0), "r"(c1), "r"(c2), "l"(pol) : "memory");
}
__device__ __forceinline__ void bar_sync(int id, int n) { asm volatile("barrier.cta.sync %0, %1;" ::"r"(id), "r"(n) : "memory"); }
__device__ __forceinline__ void bar_arrive(int id, int n) { asm volatile("barrier.cta.arrive %0, %1;" ::"r"(id), "r"(n) : "memory"); }
__device__ __forceinline__ void ldsm4(uint32_t (&r)[4], uint32_t a) {
    asm volatile("ldmatrix.sync.aligned.m8n8.x4.shared.b16 {%0,%1,%2,%3}, [%4];" : "=r"(r[0]), "=r"(r[1]), "=r"(r[2]), "=r"(r[3]) : "r"(a) : "memory");
}
__device__ __forceinline__ void ldsm4t(uint32_t (&r)[4], uint32_t a) {
    asm volatile("ldmatrix.sync.aligned.m8n8.x4.trans.shared.b16 {%0,%1,%2,%3}, [%4];" : "=r"(r[0]), "=r"(r[1]), "=r"(r[2]), "=r"(r[3]) : "r"(a) : "memory");
}
__device__ __forceinline__ void mma(float (&c)[4], const uint32_t (&a)[4], uint32_t b0, uint32_t b1) {
    asm volatile("mma.sync.aligned.m16n8k16.row.col.f32.bf16.bf16.f32 {%0,%1,%2,%3}, {%4,%5,%6,%7}, {%8,%9}, {%0,%1,%2,%3};"
                 : "+f"(c[0]), "+f"(c[1]), "+f"(c[2]), "+f"(c[3]) : "r"(a[0]), "r"(a[1]), "r"(a[2]), "r"(a[3]), "r"(b0), "r"(b1));
}
__device__ __forceinline__ uint32_t lds32(uint32_t a) { uint32_t v; asm volatile("ld.shared.b32 %0, [%1];" : "=r"(v) : "r"(a) : "memory"); return v; }
__device__ __forceinline__ uint32_t ldsv(uint32_t a) { uint32_t v; asm volatile("ld.volatile.shared.b32 %0, [%1];" : "=r"(v) : "r"(a) : "memory"); return v; }
__device__ __forceinline__ void stsv(uint32_t a, uint32_t v) { asm volatile("st.volatile.shared.b32 [%0], %1;" ::"r"(a), "r"(v) : "memory"); }
__device__ __forceinline__ float ldsf(uint32_t a) { float v; asm volatile("ld.shared.f32 %0, [%1];" : "=f"(v) : "r"(a) : "memory"); return v; }
__device__ __forceinline__ uint4 lds128(uint32_t a) { uint4 v; asm volatile("ld.shared.v4.b32 {%0,%1,%2,%3}, [%4];" : "=r"(v.x), "=r"(v.y), "=r"(v.z), "=r"(v.w) : "r"(a) : "memory"); return v; }
__device__ __forceinline__ void sts16(uint32_t a, uint16_t v) { asm volatile("st.shared.b16 [%0], %1;" ::"r"(a), "h"(v) : "memory"); }
__device__ __forceinline__ void sts32(uint32_t a, uint32_t v) { asm volatile("st.shared.b32 [%0], %1;" ::"r"(a), "r"(v) : "memory"); }
__device__ __forceinline__ void stsf2(uint32_t a, float x, float y) { asm volatile("st.shared.v2.f32 [%0], {%1,%2};" ::"r"(a), "f"(x), "f"(y) : "memory"); }
__device__ __forceinline__ void sts128(uint32_t a, uint4 v) { asm volatile("st.shared.v4.b32 [%0], {%1,%2,%3,%4};" ::"r"(a), "r"(v.x), "r"(v.y), "r"(v.z), "r"(v.w) : "memory"); }
__device__ __forceinline__ uint16_t f2bf(float x) { return __bfloat16_as_ushort(__float2bfloat16_rn(x)); }
__device__ __forceinline__ float bfround(float x) { return __bfloat162float(__float2bfloat16_rn(x)); }
__device__ __forceinline__ uint32_t pack2(float lo, float hi) { uint32_t r; asm("cvt.rn.bf16x2.f32 %0, %1, %2;" : "=r"(r) : "f"(hi), "f"(lo)); return r; }
__device__ __forceinline__ float ex2(float x) { float r; asm("ex2.approx.ftz.f32 %0, %1;" : "=f"(r) : "f"(x)); return r; }
__device__ __forceinline__ float lg2(float x) { float r; asm("lg2.approx.ftz.f32 %0, %1;" : "=f"(r) : "f"(x)); return r; }

__device__ __forceinline__ float rcp(float x) { float r; asm("rcp.approx.ftz.f32 %0, %1;" : "=f"(r) : "f"(x)); return r; }
__device__ __forceinline__ void merge_weights(uint32_t l0, uint32_t l1, float& w0, float& w1) {
    const float a = __uint_as_float(l0), b = __uint_as_float(l1), mx = fmaxf(a, b), e0 = ex2(a - mx), e1 = ex2(b - mx), r = rcp(e0 + e1);
    w0 = e0 * r; w1 = e1 * r;
}

__device__ __forceinline__ void sleep_ns(uint32_t ns) {
    uint32_t t0, t;
    asm volatile("mov.u32 %0, %clock;" : "=r"(t0));
    do { __nanosleep(200); asm volatile("mov.u32 %0, %clock;" : "=r"(t)); } while (t - t0 < 2 * ns);
}

__device__ __forceinline__ void ll_store2(ulonglong2* p, float a, float b, uint32_t tag) {
    unsigned long long x = ((unsigned long long)tag << 32) | __float_as_uint(a);
    unsigned long long y = ((unsigned long long)tag << 32) | __float_as_uint(b);
    asm volatile("st.relaxed.gpu.global.v2.b64 [%0], {%1,%2};" ::"l"(p), "l"(x), "l"(y) : "memory");
}
__device__ __forceinline__ void ll_ld2(const void* p, unsigned long long& x, unsigned long long& y) {
    asm volatile("ld.relaxed.gpu.global.v2.b64 {%0,%1}, [%2];" : "=l"(x), "=l"(y) : "l"(p) : "memory");
}
__device__ __forceinline__ void ll_gather4(const ulonglong2* p, uint32_t tag, float& r0, float& r1) {
    unsigned long long x[4], y[4]; uint32_t it = 0;
    while (true) {
        bool ok = true;
#pragma unroll
        for (int k = 0; k < 4; k++) ll_ld2(p + k * 128, x[k], y[k]);
#pragma unroll
        for (int k = 0; k < 4; k++) ok = ok && (uint32_t)(x[k] >> 32) == tag && (uint32_t)(y[k] >> 32) == tag;
        if (ok) break;
        if (++it > SPIN_MAX) __trap();
        __nanosleep(BACKOFF);
    }
    r0 = (__uint_as_float((uint32_t)x[0]) + __uint_as_float((uint32_t)x[1])) + (__uint_as_float((uint32_t)x[2]) + __uint_as_float((uint32_t)x[3]));
    r1 = (__uint_as_float((uint32_t)y[0]) + __uint_as_float((uint32_t)y[1])) + (__uint_as_float((uint32_t)y[2]) + __uint_as_float((uint32_t)y[3]));
}
__device__ __forceinline__ void cnt_rendezvous(unsigned* c, uint32_t target, int tsk) {
    TS(tsk);
    asm volatile("red.release.gpu.global.add.u32 [%0], 1;" ::"l"(c) : "memory");
    if (tsk == 18) TS(tsk + 1);
    uint32_t v, it = 0;
    while (true) {
        asm volatile("ld.acquire.gpu.global.u32 %0, [%1];" : "=r"(v) : "l"(c) : "memory");
        if ((int)(v - target) >= 0) break;
        if (++it > SPIN_MAX) __trap();
        __nanosleep(BACKOFF);
    }
    asm volatile("fence.proxy.async.global;" ::: "memory");
}

__device__ __forceinline__ void matvec_loadA(uint32_t (&a)[8][4], uint32_t tile, uint32_t bar, int w, int lane) {
    const int i = lane >> 3, rr = lane & 7, chunk = 2 * w + (i & 1);
    const uint32_t a0 = tile + (chunk >> 3) * 8192 + (rr + 8 * (i >> 1)) * 128 + (((chunk & 7) ^ rr) << 4);
#pragma unroll
    for (int hh = 0; hh < 2; hh++) {
        mbar_wait(bar + hh * 8, 0);
#pragma unroll
        for (int k = 0; k < 4; k++) ldsm4t(a[hh * 4 + k], a0 + hh * CH + k * 2048);
    }
}
__device__ __forceinline__ void matvec_mma(float (&c)[4], const uint32_t (&a)[8][4], uint32_t vec, int nvec, int lane) {
    const uint32_t va = vec + (lane & (nvec - 1)) * VROW + (lane >> 3) * 16;
    float d[4][4];
#pragma unroll
    for (int q = 0; q < 4; q++) {
        uint32_t b[4];
        ldsm4(b, va + q * 64);
        d[q][0] = d[q][1] = d[q][2] = d[q][3] = 0.f;
        mma(d[q], a[2 * q], b[0], b[1]);
        mma(d[q], a[2 * q + 1], b[2], b[3]);
    }
#pragma unroll
    for (int k = 0; k < 4; k++) c[k] = (d[0][k] + d[1][k]) + (d[2][k] + d[3][k]);
}
__device__ __forceinline__ void matvecT(float (&c)[4], uint32_t tile, uint32_t vec, int nvec, uint32_t bar, int w, int lane) {
    uint32_t a[8][4];
    matvec_loadA(a, tile, bar, w, lane);
    matvec_mma(c, a, vec, nvec, lane);
}
template <class T> __device__ __forceinline__ T* pin(T* p) { asm volatile("" : "+l"(p)); return p; }
__device__ __forceinline__ void mail_put(void* p, uint32_t v) { asm volatile("st.relaxed.gpu.global.b32 [%0], %1;" ::"l"(p), "r"(v) : "memory"); }
__device__ __forceinline__ void mail_put(void* p, float v) { mail_put(p, __float_as_uint(v)); }
__device__ __forceinline__ void out_add(__nv_bfloat16* p, float x, float y) {
    asm volatile("red.relaxed.gpu.global.add.noftz.bf16x2 [%0], %1;" ::"l"(p), "r"(pack2(x, y)) : "memory");
}
__device__ __forceinline__ bool mail_missing(const uint4& v) { return v.x == EMPTY || v.y == EMPTY || v.z == EMPTY || v.w == EMPTY; }
__device__ __forceinline__ void mail_get(uint4& v, const uint4* p, bool need = true) {
    asm volatile("{\n.reg .pred q;\nsetp.ne.u32 q, %5, 0;\n@q ld.relaxed.gpu.global.v4.b32 {%0,%1,%2,%3}, [%4];\n}"
                 : "+r"(v.x), "+r"(v.y), "+r"(v.z), "+r"(v.w) : "l"(p), "r"((uint32_t)need) : "memory");
}
__device__ __forceinline__ void sts64(uint32_t a, uint32_t x, uint32_t y) { asm volatile("st.shared.v2.b32 [%0], {%1,%2};" ::"r"(a), "r"(x), "r"(y) : "memory"); }
__device__ __forceinline__ float2 ldsf2(uint32_t a) { float2 v; asm volatile("ld.shared.v2.f32 {%0,%1}, [%2];" : "=f"(v.x), "=f"(v.y) : "r"(a) : "memory"); return v; }

__global__ void __launch_bounds__(NTHREADS, 1)
fused_decode_kernel(const char* __restrict__ wqraw, const __grid_constant__ Maps maps, const char* __restrict__ Kc, const char* __restrict__ Vc,
                    const __nv_bfloat16* __restrict__ xA, const __nv_bfloat16* __restrict__ xB,
                    __nv_bfloat16* __restrict__ out, const uint32_t zero) {
    if (threadIdx.x - 32u < 64u) {
        const uint32_t r = threadIdx.x - 32u;
        const uint32_t off = ((blockIdx.x & 3) << 20) + ((blockIdx.x >> 2) << 8) + ((r >> 1) << 13) + ((r & 1) << 7);
        asm volatile("prefetch.global.L2 [%0];" ::"l"(wqraw + off) : "memory");
    }
    extern __shared__ char smem_raw[];
    const uint32_t sm = ((uint32_t)__cvta_generic_to_shared(smem_raw) + 1023u) & ~1023u;
    const uint32_t bars = sm + OFF_BAR;
    const int cta = blockIdx.x, h = cta >> 2, j = cta & 3;
    uint64_t pol = 0;
    if (threadIdx.x == 0) {
        TS(0);
        asm volatile("createpolicy.fractional.L2::evict_first.b64 %0, 1.0;" : "=l"(pol));
#pragma unroll
        for (int i = 0; i < WIN; i++) mbar_init(bars + (B_WQB + i) * 8, 1);
        asm volatile("fence.mbarrier_init.release.cluster;" ::: "memory");
#pragma unroll
        for (int i = 0; i < WIN; i++) {
            mbar_expect(bars + (B_WQB + i) * 8, CH);
            tma3d(sm + OFF_S0 + i * CH, &maps.wqB + (i >> 1), j * 128 + (i & 1) * 64, h * 2, bars + (B_WQB + i) * 8, pol);
        }
    }
    const int tid = threadIdx.x < 64 ? threadIdx.x + 384 : threadIdx.x - 64, warp = tid >> 5, lane = tid & 31;

    if (warp == 12) {
        const size_t kvoff = ((size_t)(((j >> 1) * 32 + h) * 4096 + (j & 1) * 2048)) * 256;
        const char* kp = Kc + kvoff;
        const char* vp = Vc + kvoff;
        __syncwarp();
        bar_arrive(0, NTHREADS);
        bar_sync(3, 64);
        if (lane == 0) {
            uint32_t pb[WHI];
#pragma unroll
            for (int i = 0; i < WHI; i++) pb[i] = i < WHI - WIN ? (bars + B_WO * 8) | 1u : bars + (B_WQB + i - (WHI - WIN)) * 8;
            auto pace = [&](uint32_t bar, uint32_t par, uint32_t wina) {
                uint32_t it = 0;
                while (true) {
                    const uint32_t win = ldsv(wina);
                    uint32_t busy = 0;
#pragma unroll
                    for (int i = 0; i < WHI; i++) busy += mbar_test(pb[i] & ~1u, pb[i] & 1u) ^ 1u;
                    if (busy < win) break;
                    if (++it > SPIN_MAX) __trap();
                }
#pragma unroll
                for (int i = 0; i + 1 < WHI; i++) pb[i] = pb[i + 1];
                pb[WHI - 1] = bar | par;
            };
            auto side = [&](const CUtensorMap* m, uint32_t dst, int bidx, int c1, int c2, uint32_t wina) {
                const uint32_t bar = bars + bidx * 8;
                pace(bar, 0, wina);
                mbar_expect(bar, CH);
                tma3d(dst, m, c1, c2, bar, pol);
            };
#pragma unroll 1
            for (int i = WIN; i < 6; i++)
                side(&maps.wqB + (i >> 1), sm + OFF_S0 + i * CH, B_WQB + i, j * 128 + (i & 1) * 64, h * 2, sm + OFF_WIN);
            TS(1);
            uint32_t slot = 0, use = 0;
            int nuv = 0;
#pragma unroll 1
            for (int n = 0; n < 2 * NTILE; n++) {
                if (n == RING) {
                    mbar_wait(bars + B_FREE * 8, 0);
#pragma unroll 1
                    for (int q = 0; q < 4; q++) side(&maps.ckv, sm + OFF_S0 + q * CH, B_CKV + q, cta * 64 + q * 16, 0, sm + OFF_WIN);
                }
                if (nuv < 2 && n > RING && (n >= 2 * NTILE - 8 || mbar_test(bars + B_FREE * 8, 1))) {
                    mbar_wait(bars + B_FREE * 8, 1);
                    side(&maps.wuv, sm + OFF_S1 + nuv * CH, B_WUV + nuv, j * 128 + nuv * 64, h * 2, sm + OFF_WIN);
                    nuv++;
                }
                const uint32_t fb = bars + slot * 8;
                pace(fb, use & 1, sm + OFF_WIN);
                mbar_wait(fb + B_EMPTY * 8, (use & 1) ^ 1);
                mbar_expect(fb, CH);
                bulk1d(sm + OFF_RING + slot * CH, ((n & 1) ? vp : kp) + (size_t)(n >> 1) * CH, fb, pol);
                asm volatile("red.relaxed.gpu.global.add.u32 [%0], 1;" ::"l"(&g_cnt[64]) : "memory");
                stsv(sm + OFF_NOW, n + 1);
                if (++slot == RING) { slot = 0; use++; }
            }
            TS(2);
            mbar_wait(bars + B_FREE * 8, 0);
#pragma unroll 1
            for (int i = 0; i < 4; i++) {
                const uint32_t bar = bars + (B_WO + 2 * i) * 8;
                pace(bar + 8, 0, sm + OFF_TWIN);
                TS(32 + i);
#pragma unroll
                for (int k = 0; k < 2; k++) {
                    mbar_expect(bar + k * 8, CH / 2);
                    tma3d(sm + OFF_S0 + i * CH + k * (CH / 2), &maps.woB + (i >> 1), (i & 1) * 64 + k * 32, h & ~3, bar + k * 8, pol, (cta & 15) * 32);
                }
            }
            TS(3);
        }
    } else if (warp == 13) {
        if (lane == 0) {
#pragma unroll
            for (int i = 0; i < NBAR; i++)
                if (i < B_WQB || i >= B_WQB + WIN)
                    mbar_init(bars + i * 8, i == B_FREE ? 8 : (i >= B_EMPTY && i < B_EMPTY + RING) ? 4 : 1);
            asm volatile("fence.mbarrier_init.release.cluster;" ::: "memory");
#pragma unroll
            for (int i = 2; i < 8; i++) asm volatile("prefetch.tensormap [%0];" ::"l"(&maps.wqB + i) : "memory");
            stsv(sm + OFF_NOW, 0); stsv(sm + OFF_WIN, WIN); stsv(sm + OFF_TWIN, PREWIN);
        }
        __syncwarp();
        bar_arrive(3, 64);
        bar_sync(0, NTHREADS);
        if (lane == 0) {
            const uint32_t base = (lds32(sm + OFF_TAG) - 1u) * (NCTA * 2 * NTILE);
            mbar_wait(bars + (B_WUK + 1) * 8, 0);
            uint32_t it = 0;
            while (true) {
                const uint32_t n = ldsv(sm + OFF_NOW);
                uint32_t v;
                asm volatile("ld.relaxed.gpu.global.u32 %0, [%1];" : "=r"(v) : "l"(&g_cnt[64]) : "memory");
                v -= base;
                if (v >= NCTA * 2 * NTILE - GATE_W) break;
                const int diff = (int)(n * NCTA) - (int)v;
                stsv(sm + OFF_WIN, diff < -THETA ? WHI : WIN - (diff > THETA) - (v >= NCTA * END_V));
                if (++it > SPIN_MAX) __trap();
                __nanosleep(BACKOFF2);
            }
            stsv(sm + OFF_WIN, WHI); stsv(sm + OFF_TWIN, TAILWIN);
            TS(24);
        }
    } else if (warp < 4) {
        const int g = lane >> 2, t = lane & 3, i = lane >> 3, rr = lane & 7;
        if (tid == 0) {
            const unsigned e = atomicAdd(&g_epoch, 1u);
            sts32(sm + OFF_TAG, (e >> 7) + 1u);
        }
        bar_sync(0, NTHREADS);
        const uint32_t tag = lds32(sm + OFF_TAG);
        {
            mbar_wait(bars + 8, 0);
            float q0, q1;
            ll_gather4(&g_e1[0][h * 4][tid], tag, q0, q1);
            sts16(sm + OFF_QB + tid * 2, f2bf((j >> 1) ? q1 : q0));
        }
        bar_sync(1, 128);
        if (tid == 0) TS(4);
        uint32_t qf[8][2];
#pragma unroll
        for (int c = 0; c < 8; c++) {
            const uint32_t a = sm + OFF_QB + (((c + g) & 7) * 8 + 2 * t) * 2;
            qf[c][0] = lds32(a); qf[c][1] = lds32(a + 128);
        }
        float acc[8][4];
#pragma unroll
        for (int c = 0; c < 8; c++) { acc[c][0] = acc[c][1] = acc[c][2] = acc[c][3] = 0.f; }
        float m = -INFINITY, l = 0.f;
        const bool diag = (t == (g >> 1));
        const uint32_t krow = sm + OFF_RING + (warp * 16 + rr + 8 * (i & 1)) * 256 + (i >> 1) * 128;
        const uint32_t vrow = sm + OFF_RING + (warp * 16 + rr + 8 * (i >> 1)) * 256 + (i & 1) * 128;
        uint32_t slot = 0, ph = 0;
        uint32_t* const e5own = pin((uint32_t*)g_e5[cta] + tid);
        uint32_t a[8][4], b0, b1;
#pragma unroll 1
        for (int tile = 0;; tile++) {
            mbar_wait(bars + slot * 8, ph);
#pragma unroll
            for (int c = 0; c < 8; c++) ldsm4(a[c], krow + slot * CH + (((c + rr) & 7) << 4));
            __syncwarp();
            if (lane == 0) mbar_arrive(bars + (B_EMPTY + slot) * 8 + ((a[0][0] | a[1][0] | a[2][0] | a[3][0] | a[4][0] | a[5][0] | a[6][0] | a[7][0]) & zero));
            if (++slot == RING) { slot = 0; ph ^= 1; }
            float s0[4] = {0.f, 0.f, 0.f, 0.f}, s1[4] = {0.f, 0.f, 0.f, 0.f};
#pragma unroll
            for (int c = 0; c < 8; c += 2) { mma(s0, a[c], qf[c][0], qf[c][1]); mma(s1, a[c + 1], qf[c + 1][0], qf[c + 1][1]); }
            float slo = (g & 1) ? s0[1] + s1[1] : s0[0] + s1[0];
            float shi = (g & 1) ? s0[3] + s1[3] : s0[2] + s1[2];
            slo = diag ? bfround(bfround(slo) * SCALE) : -INFINITY;
            shi = diag ? bfround(bfround(shi) * SCALE) : -INFINITY;
            int key = __float_as_int(fmaxf(slo, shi));
            key ^= (key >> 31) & 0x7fffffff;
            key = __reduce_max_sync(0xffffffffu, key);
            key ^= (key >> 31) & 0x7fffffff;
            const float mn = fmaxf(m, __int_as_float(key));
            const float alpha = ex2((m - mn) * LOG2E);
            m = mn;
            const float plo = ex2((slo - mn) * LOG2E), phi = ex2((shi - mn) * LOG2E);
            l = l * alpha + (plo + phi);
            b0 = (g & 1) ? pack2(0.f, plo) : pack2(plo, 0.f);
            b1 = (g & 1) ? pack2(0.f, phi) : pack2(phi, 0.f);
#pragma unroll
            for (int c = 0; c < 8; c++) { acc[c][0] *= alpha; acc[c][1] *= alpha; acc[c][2] *= alpha; acc[c][3] *= alpha; }
            if (tile == NTILE - 1) break;
            mbar_wait(bars + slot * 8, ph);
#pragma unroll
            for (int c = 0; c < 8; c++) ldsm4t(a[c], vrow + slot * CH + (((c + rr) & 7) << 4));
            __syncwarp();
            if (lane == 0) mbar_arrive(bars + (B_EMPTY + slot) * 8 + ((a[0][0] | a[1][0] | a[2][0] | a[3][0] | a[4][0] | a[5][0] | a[6][0] | a[7][0]) & zero));
            if (++slot == RING) { slot = 0; ph ^= 1; }
#pragma unroll
            for (int c = 0; c < 8; c++) mma(acc[c], a[c], b0, b1);
        }
#pragma unroll
        for (int o = 16; o; o >>= 1) l += __shfl_xor_sync(0xffffffffu, l, o);
        if (lane == 0) stsf2(sm + OFF_ML + warp * 8, m, l);
        mbar_wait(bars + B_S2 * 8, 0);
        bar_sync(1, 128);
        {
            const uint4 ml0 = lds128(sm + OFF_ML), ml1 = lds128(sm + OFF_ML + 16);
            const float m0 = __uint_as_float(ml0.x), m1 = __uint_as_float(ml0.z), m2 = __uint_as_float(ml1.x), m3 = __uint_as_float(ml1.z);
            const float M = fmaxf(fmaxf(m0, m1), fmaxf(m2, m3));
            const float L = (ex2((m0 - M) * LOG2E) * __uint_as_float(ml0.y) + ex2((m1 - M) * LOG2E) * __uint_as_float(ml0.w))
                          + (ex2((m2 - M) * LOG2E) * __uint_as_float(ml1.y) + ex2((m3 - M) * LOG2E) * __uint_as_float(ml1.w));
            const float f = ex2((m - M) * LOG2E) * rcp(L);
            if (tid == 0) mail_put((float*)g_l5[h] + j, M * LOG2E + lg2(L));
            const uint32_t wa = sm + OFF_S2 + warp * 640 + (t * 16 + (t >> 1) * 8 + g) * 4;
            const uint32_t ra = sm + OFF_S2 + ((tid >> 4 & 1) * 40 + (tid & 2) * 40 + (tid >> 5) * 16 + (tid & 1) * 8 + (tid >> 2 & 3) * 2) * 4;
            mbar_wait(bars + slot * 8, ph);
#pragma unroll
            for (int c = 0; c < 8; c++) ldsm4t(a[c], vrow + slot * CH + (((c + rr) & 7) << 4));
#pragma unroll
            for (int c = 0; c < 8; c++) mma(acc[c], a[c], b0, b1);
            if (tid == 0) TS(5);
            float v[2][8];
#pragma unroll
            for (int c = 0; c < 8; c++) { v[0][c] = acc[c][0] + acc[(c + 7) & 7][1]; v[1][c] = acc[c][2] + acc[(c + 7) & 7][3]; }
#pragma unroll
            for (int c = 0; c < 4; c++) { v[0][c] += __shfl_xor_sync(0xffffffffu, v[0][c + 4], 2); v[1][c] += __shfl_xor_sync(0xffffffffu, v[1][c + 4], 2); }
            const int src = (lane & ~3) | ((lane + 3) & 3);
#pragma unroll
            for (int c = 0; c < 2; c++) { v[0][c] += __shfl_sync(0xffffffffu, v[0][c + 2], src); v[1][c] += __shfl_sync(0xffffffffu, v[1][c + 2], src); }
#pragma unroll
            for (int c = 0; c < 4; c++) sts32(wa + (c >> 1) * 320 + (c & 1) * 32, __float_as_uint(v[c >> 1][c & 1] * f));
            if (warp < 2) {
                bar_sync(1, 128);
                const float2 r0 = ldsf2(ra), r1 = ldsf2(ra + 640), r2 = ldsf2(ra + 1280), r3 = ldsf2(ra + 1920);
                mail_put(e5own, pack2((r0.x + r1.x) + (r2.x + r3.x), (r0.y + r1.y) + (r2.y + r3.y)));
            } else {
                bar_arrive(1, 128);
            }
        }
        if (tid == 0) TS(6);
        {
            uint32_t x[4][4][4];
            float d[4][4];
            bar_sync(4, 256 + 128);
#pragma unroll
            for (int k = 0; k < 16; k++) ldsm4(x[k >> 2][k & 3], sm + OFF_CA + ((k >> 2) * 2 + (lane & 1)) * VROW + (k & 3) * 64 + (i & 1) * 32 + (i >> 1) * 16);
#pragma unroll
            for (int k = 0; k < 4; k++) d[k][0] = d[k][1] = d[k][2] = d[k][3] = 0.f;
            const uint32_t wa = sm + OFF_S1 + lane * 64 + ((warp ^ (rr >> 1)) << 4);
            __nv_bfloat16* const outp = pin(out + (g & 1) * 1024 + (cta & 15) * 32 + warp * 8 + t * 2);
#pragma unroll
            for (int q = 0; q < 4; q++) {
                mbar_wait(bars + (B_WO + 4 + q) * 8, 0);
                if (q == 3 && tid == 0) TS(25);
#pragma unroll
                for (int k = 0; k < 4; k++) ldsm4t(a[k], wa + q * 8192 + k * 2048);
#pragma unroll
                for (int k = 0; k < 8; k++) mma(d[k & 3], x[k >> 1][q], a[k >> 1][(k & 1) * 2], a[k >> 1][(k & 1) * 2 + 1]);
            }
            if (lane < 8) out_add(outp, (d[0][0] + d[1][2]) + (d[2][0] + d[3][2]), (d[0][1] + d[1][3]) + (d[2][1] + d[3][3]));
            if (tid == 0) TS(15);
        }
    } else {
        const int st = tid - 128, w = warp - 4;
        const int g = lane >> 2, t = lane & 3, i = lane >> 3, rr = lane & 7;
        if (t == 0) {
#pragma unroll
            for (int k = 0; k < 4; k++) ll_store2(&g_e1[k >> 1][cta][w * 16 + g + (k & 1) * 8], 0.f, 0.f, 0u);
        }
        if (st < 64) {
            const int which = st >> 5, b = (st >> 4) & 1, c = st & 15;
            const uint4 v = __ldg((const uint4*)((which ? xA : xB) + b * 512 + j * 128) + c);
            sts128(sm + OFF_XB + (which * 2 + b) * VROW + c * 16, v);
        }
        bar_sync(0, NTHREADS);
        const uint32_t tag = lds32(sm + OFF_TAG);
        float c[4];
#pragma unroll 1
        for (int which = 0; which < 2; which++) {
            matvecT(c, sm + OFF_S0 + which * 2 * CH, sm + OFF_XB + which * 2 * VROW, 2, bars + (B_WQB + which * 2) * 8, w, lane);
            if (t == 0) {
                ll_store2(&g_e1[which][cta][w * 16 + g], c[0], c[1], tag);
                ll_store2(&g_e1[which][cta][w * 16 + g + 8], c[2], c[3], tag);
            }
        }
        __syncwarp();
        if (lane == 0) mbar_arrive(bars + B_FREE * 8);
        if (st == 0) TS(8);
        if (st < 128) {
            float q0, q1;
            sleep_ns(POLL_DELAY);
            ll_gather4(&g_e1[1][h * 4][st], tag, q0, q1);
            sts16(sm + OFF_QA + st * 2, f2bf(q0)); sts16(sm + OFF_QA + VROW + st * 2, f2bf(q1));
        }
        bar_sync(2, 256);
        if (st == 0) TS(9);
        {
            const int row = w * 16 + rr + 8 * (i & 1);
            const uint32_t a0 = sm + OFF_S2 + (row >> 6) * CH + (row & 63) * 128;
            const uint32_t va = sm + OFF_QA + g * VROW + t * 4;
            float d[4] = {0.f, 0.f, 0.f, 0.f};
            c[0] = c[1] = c[2] = c[3] = 0.f;
            mbar_wait(bars + (B_WUK + (w >> 2)) * 8, 0);
#pragma unroll
            for (int ks = 0; ks < 8; ks++) {
                const int chunk = 2 * ks + (i >> 1);
                uint32_t a[4];
                ldsm4(a, a0 + (chunk >> 3) * 8192 + (((chunk & 7) ^ rr) << 4));
                const uint32_t b0 = (g < 2) ? lds32(va + ks * 32) : 0u, b1 = (g < 2) ? lds32(va + ks * 32 + 16) : 0u;
                if (ks & 1) mma(d, a, b0, b1); else mma(c, a, b0, b1);
            }
            if (t == 0) {
                const uint32_t qs = sm + OFF_QS + (w * 16 + g) * 2;
                sts16(qs, f2bf(c[0] + d[0])); sts16(qs + VROW, f2bf(c[1] + d[1]));
                sts16(qs + 16, f2bf(c[2] + d[2])); sts16(qs + VROW + 16, f2bf(c[3] + d[3]));
            }
            bar_sync(2, 256);
            if (w == 0) {
                const int b = lane >> 4, cc = lane & 15;
                g_qabs[(b * 32 + h) * 64 + ((j * 16 + cc) ^ (h & 7))] = lds128(sm + OFF_QS + b * VROW + cc * 16);
                __syncwarp();
                if (lane == 0) {
                    cnt_rendezvous(&g_cnt[0], tag * 128u, 18);
                    TS(10);
                    mbar_expect(bars + B_GATH * 8, 2 * CH);
                    bulk1d_n(sm + OFF_S2, g_qabs + (cta >> 6) * 2048, 2 * CH, bars + B_GATH * 8);
                }
                __syncwarp();
            }
        }
        mbar_wait(bars + B_GATH * 8, 0);
        if (st == 0) TS(11);
        {
            const int mt = w & 1, kg = w >> 1;
            const uint32_t qa = sm + OFF_S2 + (mt * 16 + rr + 8 * (i & 1)) * 1024;
            const uint32_t ka = sm + OFF_S0 + kg * CH + (rr + 8 * (i >> 1)) * 128;
            float s0[4] = {0.f, 0.f, 0.f, 0.f}, s1[4] = {0.f, 0.f, 0.f, 0.f};
            mbar_wait(bars + (B_CKV + kg) * 8, 0);
#pragma unroll 2
            for (int gq = 0; gq < 8; gq++) {
#pragma unroll
                for (int k4 = 0; k4 < 4; k4++) {
                    uint32_t a[4], b[4];
                    ldsm4(a, qa + gq * 128 + (((2 * k4 + (i >> 1)) ^ rr) << 4));
                    ldsm4(b, ka + gq * 2048 + (((2 * k4 + (i & 1)) ^ rr) << 4));
                    mma(s0, a, b[0], b[1]);
                    mma(s1, a, b[2], b[3]);
                }
            }
            const uint32_t sa = sm + OFF_SC + ((mt * 16 + g) * 68 + kg * 16 + 2 * t) * 4;
            stsf2(sa, s0[0], s0[1]); stsf2(sa + 32, s1[0], s1[1]);
            stsf2(sa + 8 * 68 * 4, s0[2], s0[3]); stsf2(sa + 8 * 68 * 4 + 32, s1[2], s1[3]);
        }
        bar_sync(2, 256);
        {
            const int head = w * 4 + i;
            const uint32_t sa = sm + OFF_SC + (head * 68 + rr * 8) * 4;
            const uint4 u0 = lds128(sa), u1 = lds128(sa + 16);
            float s[8] = {__uint_as_float(u0.x), __uint_as_float(u0.y), __uint_as_float(u0.z), __uint_as_float(u0.w),
                          __uint_as_float(u1.x), __uint_as_float(u1.y), __uint_as_float(u1.z), __uint_as_float(u1.w)};
            float mx = s[0];
#pragma unroll
            for (int k = 1; k < 8; k++) mx = fmaxf(mx, s[k]);
#pragma unroll
            for (int o = 1; o < 8; o <<= 1) mx = fmaxf(mx, __shfl_xor_sync(0xffffffffu, mx, o));
            float sum = 0.f;
#pragma unroll
            for (int k = 0; k < 8; k++) { s[k] = ex2((s[k] - mx) * (SCALE * LOG2E)); sum += s[k]; }
#pragma unroll
            for (int o = 1; o < 8; o <<= 1) sum += __shfl_xor_sync(0xffffffffu, sum, o);
            const float inv = __fdividef(1.f, sum);
            uint4 p;
            p.x = pack2(s[0] * inv, s[1] * inv); p.y = pack2(s[2] * inv, s[3] * inv);
            p.z = pack2(s[4] * inv, s[5] * inv); p.w = pack2(s[6] * inv, s[7] * inv);
            sts128(sm + OFF_P + head * 128 + ((rr ^ (head & 7)) << 4), p);
            if (rr == 0) ((float*)g_lse)[head * 128 + cta] = mx * (SCALE * LOG2E) + lg2(sum);
        }
        bar_sync(2, 256);
        {
            float o[2][8][4];
#pragma unroll
            for (int mt = 0; mt < 2; mt++)
#pragma unroll
                for (int n = 0; n < 8; n++) { o[mt][n][0] = o[mt][n][1] = o[mt][n][2] = o[mt][n][3] = 0.f; }
            const uint32_t pa = sm + OFF_P + (rr + 8 * (i & 1)) * 128;
            const uint32_t va = sm + OFF_S0 + w * 2048 + (rr + 8 * (i & 1)) * 128;
#pragma unroll 1
            for (int kq = 0; kq < 4; kq++) {
                uint32_t a0[4], a1[4];
                ldsm4(a0, pa + (((2 * kq + (i >> 1)) ^ rr) << 4));
                ldsm4(a1, pa + 2048 + (((2 * kq + (i >> 1)) ^ rr) << 4));
#pragma unroll
                for (int n = 0; n < 8; n += 2) {
                    uint32_t b[4];
                    ldsm4t(b, va + kq * CH + (((n + (i >> 1)) ^ rr) << 4));
                    mma(o[0][n], a0, b[0], b[1]); mma(o[1][n], a1, b[0], b[1]);
                    mma(o[0][n + 1], a0, b[2], b[3]); mma(o[1][n + 1], a1, b[2], b[3]);
                }
            }
#pragma unroll
            for (int mt = 0; mt < 2; mt++)
#pragma unroll
                for (int hf = 0; hf < 2; hf++) {
                    const uint32_t dst = sm + OFF_S2 + (mt * 16 + hf * 8 + g) * 1024 + w * 128 + t * 16;
#pragma unroll
                    for (int nb = 0; nb < 2; nb++) {
                        uint4 v;
                        v.x = pack2(o[mt][nb * 4 + 0][hf * 2], o[mt][nb * 4 + 0][hf * 2 + 1]);
                        v.y = pack2(o[mt][nb * 4 + 1][hf * 2], o[mt][nb * 4 + 1][hf * 2 + 1]);
                        v.z = pack2(o[mt][nb * 4 + 2][hf * 2], o[mt][nb * 4 + 2][hf * 2 + 1]);
                        v.w = pack2(o[mt][nb * 4 + 3][hf * 2], o[mt][nb * 4 + 3][hf * 2 + 1]);
                        sts128(dst + nb * 64, v);
                    }
                }
            asm volatile("fence.proxy.async.shared::cta;" ::: "memory");
            __syncwarp();
            if (lane == 0) mbar_arrive(bars + B_FREE * 8);
            if (st < 82) *(st < 64 ? &g_e4[cta][st] : st < 80 ? &g_e5[cta][st - 64] : &g_l5[h][j * 2 + st - 80]) = make_uint4(EMPTY, EMPTY, EMPTY, EMPTY);
            else if (st < 84) ((uint4*)out)[cta * 2 + st - 82] = make_uint4(0u, 0u, 0u, 0u);
        }
        bar_sync(2, 256);
        if (st == 0) {
            TS(12);
#pragma unroll 1
            for (int k = 0; k < ST_SPLIT; k++) {
                asm volatile("cp.async.bulk.tensor.3d.global.shared::cta.bulk_group [%0, {%2,%3,%4}], [%1];"
                             ::"l"(&maps.ctxp), "r"(sm + OFF_S2 + k * (2 * CH / ST_SPLIT)), "r"(0), "r"(cta), "r"(k * (128 / ST_SPLIT)) : "memory");
                if (k + 1 < ST_SPLIT) __nanosleep(ST_GAP);
            }
            asm volatile("cp.async.bulk.commit_group;" ::: "memory");
            asm volatile("cp.async.bulk.wait_group 0;" ::: "memory");
            cnt_rendezvous(&g_cnt[32], tag * 128u, 20);
            TS(13);
            mbar_expect(bars + B_GATH * 8, 2 * CH + 512);
            bulk1d_n(sm + OFF_LSE, g_lse + h * 32, 512, bars + B_GATH * 8);
            bulk1d_n(sm + OFF_S2, g_ctxp + cta * 2048, 2 * CH, bars + B_GATH * 8);
        }
        __syncwarp();
        {
            mbar_wait(bars + B_GATH * 8, 1);
            if (st == 0) TS(22);
            uint4 v[8];
#pragma unroll
            for (int k = 0; k < 8; k++) v[k] = lds128(sm + OFF_S2 + (k * 256 + st) * 16);
            float ls[4];
#pragma unroll
            for (int k = 0; k < 4; k++) ls[k] = ldsf(sm + OFF_LSE + (k * 32 + lane) * 4);
            float m0 = fmaxf(ls[0], ls[1]), m1 = fmaxf(ls[2], ls[3]);
#pragma unroll
            for (int o = 16; o; o >>= 1) { m0 = fmaxf(m0, __shfl_xor_sync(0xffffffffu, m0, o)); m1 = fmaxf(m1, __shfl_xor_sync(0xffffffffu, m1, o)); }
            ls[0] = ex2(ls[0] - m0); ls[1] = ex2(ls[1] - m0); ls[2] = ex2(ls[2] - m1); ls[3] = ex2(ls[3] - m1);
            float z0 = ls[0] + ls[1], z1 = ls[2] + ls[3];
#pragma unroll
            for (int o = 16; o; o >>= 1) { z0 += __shfl_xor_sync(0xffffffffu, z0, o); z1 += __shfl_xor_sync(0xffffffffu, z1, o); }
            z0 = __fdividef(1.f, z0); z1 = __fdividef(1.f, z1);
            ls[0] *= z0; ls[1] *= z0; ls[2] *= z1; ls[3] *= z1;
            float a[2][8];
#pragma unroll
            for (int e = 0; e < 8; e++) a[0][e] = a[1][e] = 0.f;
            const int rg = st >> 4;
#pragma unroll
            for (int k = 0; k < 8; k++) {
                const float wt = __shfl_sync(0xffffffffu, ls[k >> 1], rg + 16 * (k & 1));
                const uint32_t u[4] = {v[k].x, v[k].y, v[k].z, v[k].w};
#pragma unroll
                for (int e = 0; e < 4; e++) {
                    a[k >> 2][2 * e] += wt * __uint_as_float(u[e] << 16);
                    a[k >> 2][2 * e + 1] += wt * __uint_as_float(u[e] & 0xffff0000u);
                }
            }
            const int b = lane >> 4, u16 = lane & 15;
            const uint32_t ra = sm + OFF_SC + (w * 256 + b * 128 + (u16 >> 3) * 64 + ((u16 >> 2) & 1) * 32 + (u16 & 3) * 2) * 4;
#pragma unroll
            for (int e = 0; e < 8; e += 2) {
                const float k0 = b ? a[1][e] : a[0][e], k1 = b ? a[1][e + 1] : a[0][e + 1];
                const float s0 = b ? a[0][e] : a[1][e], s1 = b ? a[0][e + 1] : a[1][e + 1];
                stsf2(ra + (e >> 1) * 32, k0 + __shfl_xor_sync(0xffffffffu, s0, 16), k1 + __shfl_xor_sync(0xffffffffu, s1, 16));
            }
            bar_sync(2, 256);
            if (st == 0) mbar_arrive(bars + B_S2 * 8);
            float s = 0.f;
#pragma unroll
            for (int k = 0; k < 8; k++) s += ldsf(sm + OFF_SC + (k * 256 + st) * 4);
            const float hi = bfround(s);
            const uint32_t ca = sm + OFF_CC + (st >> 7) * VROW + (st & 127) * 2;
            sts16(ca, f2bf(hi)); sts16(ca + 2 * VROW, f2bf(s - hi));
            bar_sync(2, 256);
        }
        matvecT(c, sm + OFF_S1, sm + OFF_CC, 4, bars + B_WUV * 8, w, lane);
#pragma unroll
        for (int k = 0; k < 4; k++) c[k] += __shfl_down_sync(0xffffffffu, c[k], 1);
        if (t == 0) {
            float* const e = (float*)g_e4[cta] + w * 16 + g;
            mail_put(e, c[0]); mail_put(e + 128, c[1]); mail_put(e + 8, c[2]); mail_put(e + 136, c[3]);
        }
        __syncwarp();
        if (lane == 0) mbar_arrive(bars + B_FREE * 8);
        if (st == 0) TS(23);
        {
            const uint4* const pv = &g_e4[(cta & ~15) + (w >> 1) * 4][(w & 1) * 32 + lane];
            uint4 x[4];
            uint32_t it = 0;
            sleep_ns(POLL_DELAY2);
            while (true) {
#pragma unroll
                for (int k = 0; k < 4; k++) { x[k].x = x[k].y = x[k].z = x[k].w = 0u; mail_get(x[k], pv + k * 64); }
                if (!__any_sync(0xffffffffu, mail_missing(x[0]) | mail_missing(x[1]) | mail_missing(x[2]) | mail_missing(x[3]))) break;
                if (++it > SPIN_MAX) __trap();
                __nanosleep(BACKOFF);
            }
#define SUM4(e) ((__uint_as_float(x[0].e) + __uint_as_float(x[1].e)) + (__uint_as_float(x[2].e) + __uint_as_float(x[3].e)))
            sts64(sm + OFF_CA + w * VROW + lane * 8, pack2(SUM4(x), SUM4(y)), pack2(SUM4(z), SUM4(w)));
#undef SUM4
        }
        if (st == 0) TS(14);
        bar_arrive(4, 256 + 128);
        {
            const uint32_t a0 = sm + OFF_S0 + w * 1024 + (rr + 8 * (i >> 1)) * 64 + (((i & 1) ^ (rr >> 1)) << 4);
            const uint4* const pv = pin(&g_e5[(cta & ~15) + (w >> 1) * 4 + (g & 3)][(w & 1) * 8 + (g >> 2) * 4 + t]);
            const uint4* const pl = pin(g_l5[(h & ~3) + (w >> 1)]);
            const uint32_t wa = sm + OFF_SC + ((w * 2 + (t >> 1)) * 80 + (t & 1) * 40 + g) * 4;
            __nv_bfloat16* const outp = pin(out + (lane >> 4) * 1024 + 512 + (cta & 15) * 32 + (lane & 15) * 2);
            uint32_t a[4][2][4];
            uint4 x, xl;
            x.x = xl.x = EMPTY; x.y = x.z = x.w = xl.y = xl.z = xl.w = 0u;
#pragma unroll
            for (int q = 0; q < 4; q++) {
                mbar_wait(bars + (B_WO + q) * 8, 0);
                if (q == POLL_Q) { mail_get(x, pv); mail_get(xl, pl); }
                ldsm4t(a[q][0], a0 + q * 8192);
                ldsm4t(a[q][1], (a0 ^ 32) + q * 8192);
            }
            if (st == 0) TS(26);
            uint32_t it = 0;
            while (true) {
                const bool n = mail_missing(x), nl = mail_missing(xl);
                if (!__any_sync(0xffffffffu, n | nl)) break;
                if (POLL_GAP) __nanosleep(POLL_GAP);
                mail_get(x, pv, n); mail_get(xl, pl, nl);
                if (++it > SPIN_MAX) __trap();
            }
            if (st == 0) TS(16);
            float d[2][2][4];
#pragma unroll
            for (int k = 0; k < 4; k++) {
                float (&dk)[4] = d[k >> 1][k & 1];
                dk[0] = dk[1] = dk[2] = dk[3] = 0.f;
                mma(dk, a[k >> 1][k & 1], x.x, x.y);
            }
#pragma unroll
            for (int k = 0; k < 4; k++) mma(d[k >> 1][k & 1], a[2 + (k >> 1)][k & 1], x.z, x.w);
            float w0, w1;
            merge_weights((t & 1) ? xl.z : xl.x, (t & 1) ? xl.w : xl.y, w0, w1);
#pragma unroll
            for (int k = 0; k < 4; k++) {
                const float s0 = (t & 2) ? d[1][k >> 1][(k & 1) * 2] : d[0][k >> 1][(k & 1) * 2];
                const float s1 = (t & 2) ? d[1][k >> 1][(k & 1) * 2 + 1] : d[0][k >> 1][(k & 1) * 2 + 1];
                sts32(wa + k * 32, __float_as_uint(w0 * s0 + w1 * s1));
            }
            if (st == 0) TS(17);
            if (w == 0) {
                bar_sync(5, 256);
                const uint32_t ra = sm + OFF_SC + ((lane >> 4) * 40 + (lane & 15) * 2) * 4;
                float2 r[16];
#pragma unroll
                for (int k = 0; k < 16; k++) r[k] = ldsf2(ra + k * 320);
#pragma unroll
                for (int o = 1; o < 16; o <<= 1)
#pragma unroll
                    for (int k = 0; k < 16; k += 2 * o) { r[k].x += r[k + o].x; r[k].y += r[k + o].y; }
                out_add(outp, r[0].x, r[0].y);
            } else {
                bar_arrive(5, 256);
            }
        }
    }
}

typedef CUresult (*EncodeFn)(CUtensorMap*, CUtensorMapDataType, cuuint32_t, void*, const cuuint64_t*, const cuuint64_t*,
                             const cuuint32_t*, const cuuint32_t*, CUtensorMapInterleave, CUtensorMapSwizzle,
                             CUtensorMapL2promotion, CUtensorMapFloatOOBfill);

void make_map(EncodeFn enc, CUtensorMap* m, void* p, unsigned rows, unsigned cols, unsigned br, unsigned bg) {
    cuuint64_t gd[3] = {64, rows, cols / 64};
    cuuint64_t gs[2] = {(cuuint64_t)cols * 2, 128};
    cuuint32_t bx[3] = {64, br, bg};
    cuuint32_t es[3] = {1, 1, 1};
    enc(m, CU_TENSOR_MAP_DATA_TYPE_BFLOAT16, 3, p, gd, gs, bx, es, CU_TENSOR_MAP_INTERLEAVE_NONE,
        CU_TENSOR_MAP_SWIZZLE_128B, CU_TENSOR_MAP_L2_PROMOTION_L2_128B, CU_TENSOR_MAP_FLOAT_OOB_FILL_NONE);
}

}

extern "C" void kernel_launch(void* const* d_in, const int* in_sizes, int n_in, void* d_out, int out_size) {
    static EncodeFn enc = nullptr;
    if (!enc) {
        void* fn = nullptr;
        cudaDriverEntryPointQueryResult qr;
        cudaGetDriverEntryPoint("cuTensorMapEncodeTiled", &fn, cudaEnableDefault, &qr);
        enc = (EncodeFn)fn;
        cudaFuncSetAttribute(fused_decode_kernel, cudaFuncAttributeMaxDynamicSharedMemorySize, SMEM_BYTES);
    }
    Maps maps;
    make_map(enc, &maps.wqB, d_in[9], 512, 4096, 64, 2);
    make_map(enc, &maps.wqA, d_in[2], 512, 4096, 64, 2);
    make_map(enc, &maps.wuk, d_in[3], 512, 4096, 64, 2);
    make_map(enc, &maps.wuv, d_in[4], 512, 4096, 64, 2);
    for (int k = 0; k < 2; k++) {
        cuuint64_t gd[3] = {512, 128, 32};
        cuuint64_t gs[2] = {1024, 131072};
        cuuint32_t bx[3] = {32, 32, 4};
        cuuint32_t es[3] = {1, 1, 1};
        enc(&maps.woB + k, CU_TENSOR_MAP_DATA_TYPE_BFLOAT16, 3, d_in[k ? 5 : 10], gd, gs, bx, es, CU_TENSOR_MAP_INTERLEAVE_NONE,
            CU_TENSOR_MAP_SWIZZLE_64B, (CUtensorMapL2promotion)WOPROMO, CU_TENSOR_MAP_FLOAT_OOB_FILL_NONE);
    }
    make_map(enc, &maps.ckv, d_in[1], 8192, 512, 16, 8);
    {
        void* p = nullptr;
        cudaGetSymbolAddress(&p, g_ctxp);
        cuuint64_t gd[3] = {128, 128, 128};
        cuuint64_t gs[2] = {256, 32768};
        cuuint32_t bx[3] = {128, 1, 128 / ST_SPLIT};
        cuuint32_t es[3] = {1, 1, 1};
        enc(&maps.ctxp, CU_TENSOR_MAP_DATA_TYPE_BFLOAT16, 3, p, gd, gs, bx, es, CU_TENSOR_MAP_INTERLEAVE_NONE,
            CU_TENSOR_MAP_SWIZZLE_NONE, CU_TENSOR_MAP_L2_PROMOTION_NONE, CU_TENSOR_MAP_FLOAT_OOB_FILL_NONE);
    }
    fused_decode_kernel<<<NCTA, NTHREADS, SMEM_BYTES>>>((const char*)d_in[9], maps, (const char*)d_in[7], (const char*)d_in[8],
                                                         (const __nv_bfloat16*)d_in[0], (const __nv_bfloat16*)d_in[6],
                                                         (__nv_bfloat16*)d_out, 0u);
}
```

```cpp
#include <cuda_runtime.h>
#include <cuda.h>
#include <cuda_bf16.h>
#include <stdint.h>

#define RING 7
#define WIN 4
#define WHI 5
#define THETA 64
#define END_V 40
#define GATE_W 64
#define PREWIN 2
#define TAILWIN 3
#define ONEBAR 0
#define HINT_AT 1
#define TRIG_AT 1
#define POLL_GAP 0
#define WOPROMO CU_TENSOR_MAP_L2_PROMOTION_L2_256B
#define POLL_DELAY 2500
#define POLL_DELAY2 4000
#define ST_SPLIT 8
#define ST_GAP 500
#define BACKOFF 200
#define BACKOFF2 100

namespace {

constexpr int NCTA = 128;
constexpr int NTHREADS = 448;
constexpr uint32_t CH = 16384;
constexpr int NTILE = 32;

constexpr uint32_t OFF_RING = 0;
constexpr uint32_t OFF_S0 = RING * CH;
constexpr uint32_t OFF_S1 = OFF_S0 + 2 * CH;
constexpr uint32_t OFF_S2 = OFF_S1 + 2 * CH;
constexpr uint32_t OFF_P = OFF_S2 + 2 * CH;
constexpr uint32_t OFF_SC = OFF_P + 4096;
constexpr uint32_t VROW = 272;
constexpr uint32_t OFF_XB = OFF_SC + 8704;
constexpr uint32_t OFF_XA = OFF_XB + 2 * VROW;
constexpr uint32_t OFF_QA = OFF_XA + 2 * VROW;
constexpr uint32_t OFF_QS = OFF_QA + 2 * VROW;
constexpr uint32_t OFF_CC = OFF_QS + 2 * VROW;
constexpr uint32_t OFF_CA = OFF_P;
constexpr uint32_t OFF_QB = OFF_CC + 4 * VROW;
constexpr uint32_t OFF_LSE = OFF_QB + 256;
constexpr uint32_t OFF_ML = OFF_LSE + 512;
constexpr uint32_t OFF_TAG = OFF_ML + 32;
constexpr uint32_t OFF_NOW = OFF_TAG + 4;
constexpr uint32_t OFF_WIN = OFF_TAG + 8;
constexpr uint32_t OFF_TWIN = OFF_TAG + 12;
constexpr uint32_t OFF_BAR = OFF_TAG + 16;
constexpr int B_EMPTY = RING;
constexpr int B_WQB = 2 * RING;
constexpr int B_WQA = B_WQB + 2;
constexpr int B_WUK = B_WQA + 2;
constexpr int B_WUV = B_WUK + 2;
constexpr int B_CKV = B_WUV + 2;
constexpr int B_WO = B_CKV + 4;
constexpr int B_FREE = B_WO + 8;
constexpr int B_GATH = B_FREE + 1;
constexpr int B_S2 = B_GATH + 1;
constexpr int NBAR = B_S2 + 1;
constexpr uint32_t TS_OFF = OFF_BAR + NBAR * 8;
constexpr uint32_t SMEM_USED = TS_OFF;
constexpr uint32_t SMEM_BYTES = SMEM_USED + 1024;
static_assert(SMEM_BYTES <= 232448, "smem");
static_assert(RING >= WHI && WHI >= WIN && WIN >= 3 && WIN <= 6, "windows");

constexpr float LOG2E = 1.4426950408889634f;
constexpr float SCALE = 0.08838834764831845f;
#define SPIN_LOG 22
constexpr uint32_t SPIN_MAX = 1u << SPIN_LOG;

struct Maps { CUtensorMap wqB, wqA, wuk, wuv, woB, woA, ckv, ctxp; };

__device__ unsigned g_epoch;
__device__ __align__(256) unsigned g_cnt[96];
__device__ __align__(256) ulonglong2 g_e1[2][NCTA][128];
__device__ __align__(256) uint4 g_qabs[2 * 32 * 64];
__device__ __align__(256) uint4 g_ctxp[NCTA * 128 * 16];
__device__ __align__(256) float4 g_lse[32 * 32];
__device__ __align__(256) uint4 g_e4[NCTA][64];
__device__ __align__(256) uint4 g_e5[NCTA][16];
__device__ __align__(256) uint4 g_l5[32][8];
constexpr uint32_t EMPTY = 0xffffffffu;

#define TS(k) do {} while (0)

__device__ __forceinline__ void mbar_init(uint32_t b, int c) { asm volatile("mbarrier.init.shared::cta.b64 [%0], %1;" ::"r"(b), "r"(c) : "memory"); }
__device__ __forceinline__ void mbar_expect(uint32_t b, uint32_t bytes) { asm volatile("mbarrier.arrive.expect_tx.shared::cta.b64 _, [%0], %1;" ::"r"(b), "r"(bytes) : "memory"); }
__device__ __forceinline__ void mbar_arrive(uint32_t b) { asm volatile("mbarrier.arrive.shared::cta.b64 _, [%0];" ::"r"(b) : "memory"); }
__device__ __forceinline__ void mbar_wait(uint32_t b, uint32_t ph) {
    asm volatile("{\n.reg .pred p;\n.reg .u32 n;\nmov.u32 n, 0;\n"
                 "W:\nmbarrier.try_wait.parity.shared::cta.b64 p, [%0], %1;\n@p bra D;\n"
                 "add.u32 n, n, 1;\nsetp.le.u32 p, n, %2;\n@p bra W;\ntrap;\nD:\n}" ::"r"(b), "r"(ph), "n"(SPIN_MAX) : "memory");
}
__device__ __forceinline__ uint32_t mbar_test(uint32_t b, uint32_t ph) {
    uint32_t ok;
    asm volatile("{\n.reg .pred p;\nmbarrier.test_wait.parity.shared::cta.b64 p, [%1], %2;\nselp.u32 %0, 1, 0, p;\n}" : "=r"(ok) : "r"(b), "r"(ph) : "memory");
    return ok;
}
__device__ __forceinline__ void bulk1d(uint32_t dst, const void* src, uint32_t bar, uint64_t pol) {
    asm volatile("cp.async.bulk.shared::cluster.global.mbarrier::complete_tx::bytes.L2::cache_hint [%0], [%1], %2, [%3], %4;"
                 ::"r"(dst), "l"(src), "n"(CH), "r"(bar), "l"(pol) : "memory");
}
__device__ __forceinline__ void bulk1d_n(uint32_t dst, const void* src, uint32_t bytes, uint32_t bar) {
    asm volatile("cp.async.bulk.shared::cluster.global.mbarrier::complete_tx::bytes [%0], [%1], %2, [%3];"
                 ::"r"(dst), "l"(src), "r"(bytes), "r"(bar) : "memory");
}
__device__ __forceinline__ void tma3d(uint32_t dst, const CUtensorMap* map, int c1, int c2, uint32_t bar, uint64_t pol, int c0 = 0) {
    asm volatile("cp.async.bulk.tensor.3d.shared::cluster.global.mbarrier::complete_tx::bytes.L2::cache_hint [%0], [%1, {%3,%4,%5}], [%2], %6;"
                 ::"r"(dst), "l"(map), "r"(bar), "r"(c0), "r"(c1), "r"(c2), "l"(pol) : "memory");
}
__device__ __forceinline__ void bar_sync(int id, int n) { asm volatile("barrier.cta.sync %0, %1;" ::"r"(id), "r"(n) : "memory"); }
__device__ __forceinline__ void bar_arrive(int id, int n) { asm volatile("barrier.cta.arrive %0, %1;" ::"r"(id), "r"(n) : "memory"); }
__device__ __forceinline__ void ldsm4(uint32_t (&r)[4], uint32_t a) {
    asm volatile("ldmatrix.sync.aligned.m8n8.x4.shared.b16 {%0,%1,%2,%3}, [%4];" : "=r"(r[0]), "=r"(r[1]), "=r"(r[2]), "=r"(r[3]) : "r"(a) : "memory");
}
__device__ __forceinline__ void ldsm4t(uint32_t (&r)[4], uint32_t a) {
    asm volatile("ldmatrix.sync.aligned.m8n8.x4.trans.shared.b16 {%0,%1,%2,%3}, [%4];" : "=r"(r[0]), "=r"(r[1]), "=r"(r[2]), "=r"(r[3]) : "r"(a) : "memory");
}
__device__ __forceinline__ void mma(float (&c)[4], const uint32_t (&a)[4], uint32_t b0, uint32_t b1) {
    asm volatile("mma.sync.aligned.m16n8k16.row.col.f32.bf16.bf16.f32 {%0,%1,%2,%3}, {%4,%5,%6,%7}, {%8,%9}, {%0,%1,%2,%3};"
                 : "+f"(c[0]), "+f"(c[1]), "+f"(c[2]), "+f"(c[3]) : "r"(a[0]), "r"(a[1]), "r"(a[2]), "r"(a[3]), "r"(b0), "r"(b1));
}
__device__ __forceinline__ uint32_t lds32(uint32_t a) { uint32_t v; asm volatile("ld.shared.b32 %0, [%1];" : "=r"(v) : "r"(a) : "memory"); return v; }
__device__ __forceinline__ uint32_t ldsv(uint32_t a) { uint32_t v; asm volatile("ld.volatile.shared.b32 %0, [%1];" : "=r"(v) : "r"(a) : "memory"); return v; }
__device__ __forceinline__ void stsv(uint32_t a, uint32_t v) { asm volatile("st.volatile.shared.b32 [%0], %1;" ::"r"(a), "r"(v) : "memory"); }
__device__ __forceinline__ float ldsf(uint32_t a) { float v; asm volatile("ld.shared.f32 %0, [%1];" : "=f"(v) : "r"(a) : "memory"); return v; }
__device__ __forceinline__ uint4 lds128(uint32_t a) { uint4 v; asm volatile("ld.shared.v4.b32 {%0,%1,%2,%3}, [%4];" : "=r"(v.x), "=r"(v.y), "=r"(v.z), "=r"(v.w) : "r"(a) : "memory"); return v; }
__device__ __forceinline__ void sts16(uint32_t a, uint16_t v) { asm volatile("st.shared.b16 [%0], %1;" ::"r"(a), "h"(v) : "memory"); }
__device__ __forceinline__ void sts32(uint32_t a, uint32_t v) { asm volatile("st.shared.b32 [%0], %1;" ::"r"(a), "r"(v) : "memory"); }
__device__ __forceinline__ void stsf2(uint32_t a, float x, float y) { asm volatile("st.shared.v2.f32 [%0], {%1,%2};" ::"r"(a), "f"(x), "f"(y) : "memory"); }
__device__ __forceinline__ void sts128(uint32_t a, uint4 v) { asm volatile("st.shared.v4.b32 [%0], {%1,%2,%3,%4};" ::"r"(a), "r"(v.x), "r"(v.y), "r"(v.z), "r"(v.w) : "memory"); }
__device__ __forceinline__ uint16_t f2bf(float x) { return __bfloat16_as_ushort(__float2bfloat16_rn(x)); }
__device__ __forceinline__ float bfround(float x) { return __bfloat162float(__float2bfloat16_rn(x)); }
__device__ __forceinline__ uint32_t pack2(float lo, float hi) { uint32_t r; asm("cvt.rn.bf16x2.f32 %0, %1, %2;" : "=r"(r) : "f"(hi), "f"(lo)); return r; }
__device__ __forceinline__ float ex2(float x) { float r; asm("ex2.approx.ftz.f32 %0, %1;" : "=f"(r) : "f"(x)); return r; }
__device__ __forceinline__ float lg2(float x) { float r; asm("lg2.approx.ftz.f32 %0, %1;" : "=f"(r) : "f"(x)); return r; }

__device__ __forceinline__ float rcp(float x) { float r; asm("rcp.approx.ftz.f32 %0, %1;" : "=f"(r) : "f"(x)); return r; }
__device__ __forceinline__ void merge_weights(uint32_t l0, uint32_t l1, float& w0, float& w1) {
    const float a = __uint_as_float(l0), b = __uint_as_float(l1), mx = fmaxf(a, b), e0 = ex2(a - mx), e1 = ex2(b - mx), r = rcp(e0 + e1);
    w0 = e0 * r; w1 = e1 * r;
}

__device__ __forceinline__ void sleep_ns(uint32_t ns) {
    uint32_t t0, t;
    asm volatile("mov.u32 %0, %clock;" : "=r"(t0));
    do { __nanosleep(200); asm volatile("mov.u32 %0, %clock;" : "=r"(t)); } while (t - t0 < 2 * ns);
}

__device__ __forceinline__ void ll_store2(ulonglong2* p, float a, float b, uint32_t tag) {
    unsigned long long x = ((unsigned long long)tag << 32) | __float_as_uint(a);
    unsigned long long y = ((unsigned long long)tag << 32) | __float_as_uint(b);
    asm volatile("st.relaxed.gpu.global.v2.b64 [%0], {%1,%2};" ::"l"(p), "l"(x), "l"(y) : "memory");
}
__device__ __forceinline__ void ll_ld2(const void* p, unsigned long long& x, unsigned long long& y) {
    asm volatile("ld.relaxed.gpu.global.v2.b64 {%0,%1}, [%2];" : "=l"(x), "=l"(y) : "l"(p) : "memory");
}
__device__ __forceinline__ void ll_gather4(const ulonglong2* p, uint32_t tag, float& r0, float& r1) {
    unsigned long long x[4], y[4]; uint32_t it = 0;
    while (true) {
        bool ok = true;
#pragma unroll
        for (int k = 0; k < 4; k++) ll_ld2(p + k * 128, x[k], y[k]);
#pragma unroll
        for (int k = 0; k < 4; k++) ok = ok && (uint32_t)(x[k] >> 32) == tag && (uint32_t)(y[k] >> 32) == tag;
        if (ok) break;
        if (++it > SPIN_MAX) __trap();
        __nanosleep(BACKOFF);
    }
    r0 = (__uint_as_float((uint32_t)x[0]) + __uint_as_float((uint32_t)x[1])) + (__uint_as_float((uint32_t)x[2]) + __uint_as_float((uint32_t)x[3]));
    r1 = (__uint_as_float((uint32_t)y[0]) + __uint_as_float((uint32_t)y[1])) + (__uint_as_float((uint32_t)y[2]) + __uint_as_float((uint32_t)y[3]));
}
__device__ __forceinline__ void cnt_rendezvous(unsigned* c, uint32_t target, int tsk) {
    TS(tsk);
    asm volatile("red.release.gpu.global.add.u32 [%0], 1;" ::"l"(c) : "memory");
    if (tsk == 18) TS(tsk + 1);
    uint32_t v, it = 0;
    while (true) {
        asm volatile("ld.acquire.gpu.global.u32 %0, [%1];" : "=r"(v) : "l"(c) : "memory");
        if ((int)(v - target) >= 0) break;
        if (++it > SPIN_MAX) __trap();
        __nanosleep(BACKOFF);
    }
    asm volatile("fence.proxy.async.global;" ::: "memory");
}

__device__ __forceinline__ void matvec_loadA(uint32_t (&a)[8][4], uint32_t tile, uint32_t bar, int w, int lane) {
    const int i = lane >> 3, rr = lane & 7, chunk = 2 * w + (i & 1);
    const uint32_t a0 = tile + (chunk >> 3) * 8192 + (rr + 8 * (i >> 1)) * 128 + (((chunk & 7) ^ rr) << 4);
#pragma unroll
    for (int hh = 0; hh < 2; hh++) {
        mbar_wait(bar + hh * 8, 0);
#pragma unroll
        for (int k = 0; k < 4; k++) ldsm4t(a[hh * 4 + k], a0 + hh * CH + k * 2048);
    }
}
__device__ __forceinline__ void matvec_mma(float (&c)[4], const uint32_t (&a)[8][4], uint32_t vec, int nvec, int lane) {
    const uint32_t va = vec + (lane & (nvec - 1)) * VROW + (lane >> 3) * 16;
    float d[4][4];
#pragma unroll
    for (int q = 0; q < 4; q++) {
        uint32_t b[4];
        ldsm4(b, va + q * 64);
        d[q][0] = d[q][1] = d[q][2] = d[q][3] = 0.f;
        mma(d[q], a[2 * q], b[0], b[1]);
        mma(d[q], a[2 * q + 1], b[2], b[3]);
    }
#pragma unroll
    for (int k = 0; k < 4; k++) c[k] = (d[0][k] + d[1][k]) + (d[2][k] + d[3][k]);
}
__device__ __forceinline__ void matvecT(float (&c)[4], uint32_t tile, uint32_t vec, int nvec, uint32_t bar, int w, int lane) {
    uint32_t a[8][4];
    matvec_loadA(a, tile, bar, w, lane);
    matvec_mma(c, a, vec, nvec, lane);
}
template <class T> __device__ __forceinline__ T* pin(T* p) { asm volatile("" : "+l"(p)); return p; }
__device__ __forceinline__ void mail_put(void* p, uint32_t v) { asm volatile("st.relaxed.gpu.global.b32 [%0], %1;" ::"l"(p), "r"(v) : "memory"); }
__device__ __forceinline__ void mail_put(void* p, float v) { mail_put(p, __float_as_uint(v)); }
__device__ __forceinline__ void out_add(__nv_bfloat16* p, float x, float y) {
    asm volatile("red.relaxed.gpu.global.add.noftz.bf16x2 [%0], %1;" ::"l"(p), "r"(pack2(x, y)) : "memory");
}
__device__ __forceinline__ bool mail_missing(const uint4& v) { return v.x == EMPTY || v.y == EMPTY || v.z == EMPTY || v.w == EMPTY; }
__device__ __forceinline__ void mail_get(uint4& v, const uint4* p, bool need = true) {
    asm volatile("{\n.reg .pred q;\nsetp.ne.u32 q, %5, 0;\n@q ld.relaxed.gpu.global.v4.b32 {%0,%1,%2,%3}, [%4];\n}"
                 : "+r"(v.x), "+r"(v.y), "+r"(v.z), "+r"(v.w) : "l"(p), "r"((uint32_t)need) : "memory");
}
__device__ __forceinline__ void sts64(uint32_t a, uint32_t x, uint32_t y) { asm volatile("st.shared.v2.b32 [%0], {%1,%2};" ::"r"(a), "r"(x), "r"(y) : "memory"); }
__device__ __forceinline__ float2 ldsf2(uint32_t a) { float2 v; asm volatile("ld.shared.v2.f32 {%0,%1}, [%2];" : "=f"(v.x), "=f"(v.y) : "r"(a) : "memory"); return v; }

__global__ void __launch_bounds__(NTHREADS, 1)
fused_decode_kernel(const char* __restrict__ wqraw, const __grid_constant__ Maps maps, const char* __restrict__ Kc, const char* __restrict__ Vc,
                    const __nv_bfloat16* __restrict__ xA, const __nv_bfloat16* __restrict__ xB,
                    __nv_bfloat16* __restrict__ out, const uint32_t zero) {
    if (threadIdx.x - 32u < 64u) {
        const uint32_t r = threadIdx.x - 32u;
        const uint32_t off = ((blockIdx.x & 3) << 20) + ((blockIdx.x >> 2) << 8) + ((r >> 1) << 13) + ((r & 1) << 7);
        asm volatile("prefetch.global.L2 [%0];" ::"l"(wqraw + off) : "memory");
    }
    extern __shared__ char smem_raw[];
    const uint32_t sm = ((uint32_t)__cvta_generic_to_shared(smem_raw) + 1023u) & ~1023u;
    const uint32_t bars = sm + OFF_BAR;
    const int cta = blockIdx.x, h = cta >> 2, j = cta & 3;
    uint64_t pol = 0;
    if (threadIdx.x == 0) {
        TS(0);
        asm volatile("createpolicy.fractional.L2::evict_first.b64 %0, 1.0;" : "=l"(pol));
#pragma unroll
        for (int i = 0; i < WIN; i++) mbar_init(bars + (B_WQB + i) * 8, 1);
        asm volatile("fence.mbarrier_init.release.cluster;" ::: "memory");
#pragma unroll
        for (int i = 0; i < WIN; i++) {
            mbar_expect(bars + (B_WQB + i) * 8, CH);
            tma3d(sm + OFF_S0 + i * CH, &maps.wqB + (i >> 1), j * 128 + (i & 1) * 64, h * 2, bars + (B_WQB + i) * 8, pol);
        }
    }
    const int tid = threadIdx.x < 64 ? threadIdx.x + 384 : threadIdx.x - 64, warp = tid >> 5, lane = tid & 31;

    if (warp == 12) {
        const size_t kvoff = ((size_t)(((j >> 1) * 32 + h) * 4096 + (j & 1) * 2048)) * 256;
        const char* kp = Kc + kvoff;
        const char* vp = Vc + kvoff;
        __syncwarp();
        bar_arrive(0, NTHREADS);
        bar_sync(3, 64);
        if (lane == 0) {
            uint32_t pb[WHI];
#pragma unroll
            for (int i = 0; i < WHI; i++) pb[i] = i < WHI - WIN ? (bars + B_WO * 8) | 1u : bars + (B_WQB + i - (WHI - WIN)) * 8;
            auto pace = [&](uint32_t bar, uint32_t par, uint32_t wina) {
                uint32_t it = 0;
                while (true) {
                    const uint32_t win = ldsv(wina);
                    uint32_t busy = 0;
#pragma unroll
                    for (int i = 0; i < WHI; i++) busy += mbar_test(pb[i] & ~1u, pb[i] & 1u) ^ 1u;
                    if (busy < win) break;
                    if (++it > SPIN_MAX) __trap();
                }
#pragma unroll
                for (int i = 0; i + 1 < WHI; i++) pb[i] = pb[i + 1];
                pb[WHI - 1] = bar | par;
            };
            auto side = [&](const CUtensorMap* m, uint32_t dst, int bidx, int c1, int c2, uint32_t wina) {
                const uint32_t bar = bars + bidx * 8;
                pace(bar, 0, wina);
                mbar_expect(bar, CH);
                tma3d(dst, m, c1, c2, bar, pol);
            };
#pragma unroll 1
            for (int i = WIN; i < 6; i++)
                side(&maps.wqB + (i >> 1), sm + OFF_S0 + i * CH, B_WQB + i, j * 128 + (i & 1) * 64, h * 2, sm + OFF_WIN);
            TS(1);
            uint32_t slot = 0, use = 0;
            int nuv = 0;
#pragma unroll 1
            for (int n = 0; n < 2 * NTILE; n++) {
                if (n == RING) {
                    mbar_wait(bars + B_FREE * 8, 0);
#pragma unroll 1
                    for (int q = 0; q < 4; q++) side(&maps.ckv, sm + OFF_S0 + q * CH, B_CKV + q, cta * 64 + q * 16, 0, sm + OFF_WIN);
                }
                if (nuv < 2 && n > RING && (n >= 2 * NTILE - 8 || mbar_test(bars + B_FREE * 8, 1))) {
                    mbar_wait(bars + B_FREE * 8, 1);
                    side(&maps.wuv, sm + OFF_S1 + nuv * CH, B_WUV + nuv, j * 128 + nuv * 64, h * 2, sm + OFF_WIN);
                    nuv++;
                }
                const uint32_t fb = bars + slot * 8;
                pace(fb, use & 1, sm + OFF_WIN);
                mbar_wait(fb + B_EMPTY * 8, (use & 1) ^ 1);
                mbar_expect(fb, CH);
                bulk1d(sm + OFF_RING + slot * CH, ((n & 1) ? vp : kp) + (size_t)(n >> 1) * CH, fb, pol);
                asm volatile("red.relaxed.gpu.global.add.u32 [%0], 1;" ::"l"(&g_cnt[64]) : "memory");
                stsv(sm + OFF_NOW, n + 1);
                if (++slot == RING) { slot = 0; use++; }
            }
            TS(2);
            mbar_wait(bars + B_FREE * 8, 0);
#pragma unroll 1
            for (int i = 0; i < 4; i++) {
                const uint32_t bar = bars + (B_WO + 2 * i) * 8;
                pace(bar + 8, 0, sm + OFF_TWIN);
                TS(32 + i);
#pragma unroll
                for (int k = 0; k < 2; k++) {
                    const uint32_t bk = (ONEBAR && i >= 2) ? bar + 8 : bar + k * 8;
                    if (ONEBAR && i >= 2) { if (!k) mbar_expect(bk, CH); } else mbar_expect(bk, CH / 2);
                    tma3d(sm + OFF_S0 + i * CH + k * (CH / 2), &maps.woB + (i >> 1), (i & 1) * 64 + k * 32, h & ~3, bk, pol, (cta & 15) * 32);
                }
            }
            TS(3);
        }
    } else if (warp == 13) {
        if (lane == 0) {
#pragma unroll
            for (int i = 0; i < NBAR; i++)
                if (i < B_WQB || i >= B_WQB + WIN)
                    mbar_init(bars + i * 8, i == B_FREE ? 8 : (i >= B_EMPTY && i < B_EMPTY + RING) ? 4 : 1);
            asm volatile("fence.mbarrier_init.release.cluster;" ::: "memory");
#pragma unroll
            for (int i = 2; i < 8; i++) asm volatile("prefetch.tensormap [%0];" ::"l"(&maps.wqB + i) : "memory");
            stsv(sm + OFF_NOW, 0); stsv(sm + OFF_WIN, WIN); stsv(sm + OFF_TWIN, PREWIN);
        }
        __syncwarp();
        bar_arrive(3, 64);
        bar_sync(0, NTHREADS);
        if (lane == 0) {
            const uint32_t base = (lds32(sm + OFF_TAG) - 1u) * (NCTA * 2 * NTILE);
            mbar_wait(bars + (B_WUK + 1) * 8, 0);
            uint32_t it = 0;
            while (true) {
                const uint32_t n = ldsv(sm + OFF_NOW);
                uint32_t v;
                asm volatile("ld.relaxed.gpu.global.u32 %0, [%1];" : "=r"(v) : "l"(&g_cnt[64]) : "memory");
                v -= base;
                if (v >= NCTA * 2 * NTILE - GATE_W) break;
                const int diff = (int)(n * NCTA) - (int)v;
                stsv(sm + OFF_WIN, diff < -THETA ? WHI : WIN - (diff > THETA) - (v >= NCTA * END_V));
                if (++it > SPIN_MAX) __trap();
                __nanosleep(BACKOFF2);
            }
            stsv(sm + OFF_WIN, WHI); stsv(sm + OFF_TWIN, TAILWIN);
            TS(24);
        }
    } else if (warp < 4) {
        const int g = lane >> 2, t = lane & 3, i = lane >> 3, rr = lane & 7;
        if (tid == 0) {
            const unsigned e = atomicAdd(&g_epoch, 1u);
            sts32(sm + OFF_TAG, (e >> 7) + 1u);
        }
        bar_sync(0, NTHREADS);
        const uint32_t tag = lds32(sm + OFF_TAG);
        {
            mbar_wait(bars + 8, 0);
            float q0, q1;
            ll_gather4(&g_e1[0][h * 4][tid], tag, q0, q1);
            sts16(sm + OFF_QB + tid * 2, f2bf((j >> 1) ? q1 : q0));
        }
        bar_sync(1, 128);
        if (tid == 0) TS(4);
        uint32_t qf[8][2];
#pragma unroll
        for (int c = 0; c < 8; c++) {
            const uint32_t a = sm + OFF_QB + (((c + g) & 7) * 8 + 2 * t) * 2;
            qf[c][0] = lds32(a); qf[c][1] = lds32(a + 128);
        }
        float acc[8][4];
#pragma unroll
        for (int c = 0; c < 8; c++) { acc[c][0] = acc[c][1] = acc[c][2] = acc[c][3] = 0.f; }
        float m = -INFINITY, l = 0.f;
        const bool diag = (t == (g >> 1));
        const uint32_t krow = sm + OFF_RING + (warp * 16 + rr + 8 * (i & 1)) * 256 + (i >> 1) * 128;
        const uint32_t vrow = sm + OFF_RING + (warp * 16 + rr + 8 * (i >> 1)) * 256 + (i & 1) * 128;
        uint32_t slot = 0, ph = 0;
        uint32_t* const e5own = pin((uint32_t*)g_e5[cta] + tid);
        uint32_t a[8][4], b0, b1;
#pragma unroll 1
        for (int tile = 0;; tile++) {
            mbar_wait(bars + slot * 8, ph);
#pragma unroll
            for (int c = 0; c < 8; c++) ldsm4(a[c], krow + slot * CH + (((c + rr) & 7) << 4));
            __syncwarp();
            if (lane == 0) mbar_arrive(bars + (B_EMPTY + slot) * 8 + ((a[0][0] | a[1][0] | a[2][0] | a[3][0] | a[4][0] | a[5][0] | a[6][0] | a[7][0]) & zero));
            if (++slot == RING) { slot = 0; ph ^= 1; }
            float s0[4] = {0.f, 0.f, 0.f, 0.f}, s1[4] = {0.f, 0.f, 0.f, 0.f};
#pragma unroll
            for (int c = 0; c < 8; c += 2) { mma(s0, a[c], qf[c][0], qf[c][1]); mma(s1, a[c + 1], qf[c + 1][0], qf[c + 1][1]); }
            float slo = (g & 1) ? s0[1] + s1[1] : s0[0] + s1[0];
            float shi = (g & 1) ? s0[3] + s1[3] : s0[2] + s1[2];
            slo = diag ? bfround(bfround(slo) * SCALE) : -INFINITY;
            shi = diag ? bfround(bfround(shi) * SCALE) : -INFINITY;
            int key = __float_as_int(fmaxf(slo, shi));
            key ^= (key >> 31) & 0x7fffffff;
            key = __reduce_max_sync(0xffffffffu, key);
            key ^= (key >> 31) & 0x7fffffff;
            const float mn = fmaxf(m, __int_as_float(key));
            const float alpha = ex2((m - mn) * LOG2E);
            m = mn;
            const float plo = ex2((slo - mn) * LOG2E), phi = ex2((shi - mn) * LOG2E);
            l = l * alpha + (plo + phi);
            b0 = (g & 1) ? pack2(0.f, plo) : pack2(plo, 0.f);
            b1 = (g & 1) ? pack2(0.f, phi) : pack2(phi, 0.f);
#pragma unroll
            for (int c = 0; c < 8; c++) { acc[c][0] *= alpha; acc[c][1] *= alpha; acc[c][2] *= alpha; acc[c][3] *= alpha; }
            if (tile == NTILE - 1) break;
            mbar_wait(bars + slot * 8, ph);
#pragma unroll
            for (int c = 0; c < 8; c++) ldsm4t(a[c], vrow + slot * CH + (((c + rr) & 7) << 4));
            __syncwarp();
            if (lane == 0) mbar_arrive(bars + (B_EMPTY + slot) * 8 + ((a[0][0] | a[1][0] | a[2][0] | a[3][0] | a[4][0] | a[5][0] | a[6][0] | a[7][0]) & zero));
            if (++slot == RING) { slot = 0; ph ^= 1; }
#pragma unroll
            for (int c = 0; c < 8; c++) mma(acc[c], a[c], b0, b1);
        }
#pragma unroll
        for (int o = 16; o; o >>= 1) l += __shfl_xor_sync(0xffffffffu, l, o);
        if (lane == 0) stsf2(sm + OFF_ML + warp * 8, m, l);
        mbar_wait(bars + B_S2 * 8, 0);
        bar_sync(1, 128);
        {
            const uint4 ml0 = lds128(sm + OFF_ML), ml1 = lds128(sm + OFF_ML + 16);
            const float m0 = __uint_as_float(ml0.x), m1 = __uint_as_float(ml0.z), m2 = __uint_as_float(ml1.x), m3 = __uint_as_float(ml1.z);
            const float M = fmaxf(fmaxf(m0, m1), fmaxf(m2, m3));
            const float L = (ex2((m0 - M) * LOG2E) * __uint_as_float(ml0.y) + ex2((m1 - M) * LOG2E) * __uint_as_float(ml0.w))
                          + (ex2((m2 - M) * LOG2E) * __uint_as_float(ml1.y) + ex2((m3 - M) * LOG2E) * __uint_as_float(ml1.w));
            const float f = ex2((m - M) * LOG2E) * rcp(L);
            const float lse = M * LOG2E + lg2(L);
            float* const l5own = pin((float*)g_l5[h] + j);
            if (HINT_AT == 0 && tid == 96) mail_put(l5own, lse);
            if (TRIG_AT == 0) bar_sync(4, 256 + 128);
            const uint32_t wa = sm + OFF_S2 + warp * 640 + (t * 16 + (t >> 1) * 8 + g) * 4;
            const uint32_t ra = sm + OFF_S2 + ((tid >> 4 & 1) * 40 + (tid & 2) * 40 + (tid >> 5) * 16 + (tid & 1) * 8 + (tid >> 2 & 3) * 2) * 4;
            mbar_wait(bars + slot * 8, ph);
#pragma unroll
            for (int c = 0; c < 8; c++) ldsm4t(a[c], vrow + slot * CH + (((c + rr) & 7) << 4));
            if (HINT_AT == 1 && tid == 96) mail_put(l5own, lse);
#pragma unroll
            for (int c = 0; c < 8; c++) mma(acc[c], a[c], b0, b1);
            if (tid == 0) TS(5);
            float v[2][8];
#pragma unroll
            for (int c = 0; c < 8; c++) { v[0][c] = acc[c][0] + acc[(c + 7) & 7][1]; v[1][c] = acc[c][2] + acc[(c + 7) & 7][3]; }
#pragma unroll
            for (int c = 0; c < 4; c++) { v[0][c] += __shfl_xor_sync(0xffffffffu, v[0][c + 4], 2); v[1][c] += __shfl_xor_sync(0xffffffffu, v[1][c + 4], 2); }
            const int src = (lane & ~3) | ((lane + 3) & 3);
#pragma unroll
            for (int c = 0; c < 2; c++) { v[0][c] += __shfl_sync(0xffffffffu, v[0][c + 2], src); v[1][c] += __shfl_sync(0xffffffffu, v[1][c + 2], src); }
#pragma unroll
            for (int c = 0; c < 4; c++) sts32(wa + (c >> 1) * 320 + (c & 1) * 32, __float_as_uint(v[c >> 1][c & 1] * f));
            if (warp < 2) {
                bar_sync(1, 128);
                const float2 r0 = ldsf2(ra), r1 = ldsf2(ra + 640), r2 = ldsf2(ra + 1280), r3 = ldsf2(ra + 1920);
                mail_put(e5own, pack2((r0.x + r1.x) + (r2.x + r3.x), (r0.y + r1.y) + (r2.y + r3.y)));
            } else {
                bar_arrive(1, 128);
                if (HINT_AT == 2 && tid == 96) mail_put(l5own, lse);
            }
        }
        if (tid == 0) TS(6);
        {
            uint32_t x[4][4][4];
            float d[4][4];
            if (TRIG_AT == 1) bar_sync(4, 256 + 128);
#pragma unroll
            for (int k = 0; k < 16; k++) ldsm4(x[k >> 2][k & 3], sm + OFF_CA + ((k >> 2) * 2 + (lane & 1)) * VROW + (k & 3) * 64 + (i & 1) * 32 + (i >> 1) * 16);
#pragma unroll
            for (int k = 0; k < 4; k++) d[k][0] = d[k][1] = d[k][2] = d[k][3] = 0.f;
            const uint32_t wa = sm + OFF_S1 + lane * 64 + ((warp ^ (rr >> 1)) << 4);
            __nv_bfloat16* const outp = pin(out + (g & 1) * 1024 + (cta & 15) * 32 + warp * 8 + t * 2);
#pragma unroll
            for (int q = 0; q < 4; q += 2) {
#pragma unroll
                for (int k = 0; k < 8; k++) {
                    if (k == 0 || (k == 4 && !ONEBAR)) mbar_wait(bars + (B_WO + 4 + q + (ONEBAR ? 1 : k >> 2)) * 8, 0);
                    ldsm4t(a[k], wa + q * 8192 + k * 2048);
                }
#pragma unroll
                for (int k = 0; k < 16; k++) mma(d[k & 3], x[(k >> 1) & 3][q + (k >> 3)], a[k >> 1][(k & 1) * 2], a[k >> 1][(k & 1) * 2 + 1]);
            }
            if (lane < 8) out_add(outp, (d[0][0] + d[1][2]) + (d[2][0] + d[3][2]), (d[0][1] + d[1][3]) + (d[2][1] + d[3][3]));
            if (tid == 0) TS(15);
        }
    } else {
        const int st = tid - 128, w = warp - 4;
        const int g = lane >> 2, t = lane & 3, i = lane >> 3, rr = lane & 7;
        if (t == 0) {
#pragma unroll
            for (int k = 0; k < 4; k++) ll_store2(&g_e1[k >> 1][cta][w * 16 + g + (k & 1) * 8], 0.f, 0.f, 0u);
        }
        if (st < 64) {
            const int which = st >> 5, b = (st >> 4) & 1, c = st & 15;
            const uint4 v = __ldg((const uint4*)((which ? xA : xB) + b * 512 + j * 128) + c);
            sts128(sm + OFF_XB + (which * 2 + b) * VROW + c * 16, v);
        }
        bar_sync(0, NTHREADS);
        const uint32_t tag = lds32(sm + OFF_TAG);
        float c[4];
#pragma unroll 1
        for (int which = 0; which < 2; which++) {
            matvecT(c, sm + OFF_S0 + which * 2 * CH, sm + OFF_XB + which * 2 * VROW, 2, bars + (B_WQB + which * 2) * 8, w, lane);
            if (t == 0) {
                ll_store2(&g_e1[which][cta][w * 16 + g], c[0], c[1], tag);
                ll_store2(&g_e1[which][cta][w * 16 + g + 8], c[2], c[3], tag);
            }
        }
        __syncwarp();
        if (lane == 0) mbar_arrive(bars + B_FREE * 8);
        if (st == 0) TS(8);
        if (st < 128) {
            float q0, q1;
            sleep_ns(POLL_DELAY);
            ll_gather4(&g_e1[1][h * 4][st], tag, q0, q1);
            sts16(sm + OFF_QA + st * 2, f2bf(q0)); sts16(sm + OFF_QA + VROW + st * 2, f2bf(q1));
        }
        bar_sync(2, 256);
        if (st == 0) TS(9);
        {
            const int row = w * 16 + rr + 8 * (i & 1);
            const uint32_t a0 = sm + OFF_S2 + (row >> 6) * CH + (row & 63) * 128;
            const uint32_t va = sm + OFF_QA + g * VROW + t * 4;
            float d[4] = {0.f, 0.f, 0.f, 0.f};
            c[0] = c[1] = c[2] = c[3] = 0.f;
            mbar_wait(bars + (B_WUK + (w >> 2)) * 8, 0);
#pragma unroll
            for (int ks = 0; ks < 8; ks++) {
                const int chunk = 2 * ks + (i >> 1);
                uint32_t a[4];
                ldsm4(a, a0 + (chunk >> 3) * 8192 + (((chunk & 7) ^ rr) << 4));
                const uint32_t b0 = (g < 2) ? lds32(va + ks * 32) : 0u, b1 = (g < 2) ? lds32(va + ks * 32 + 16) : 0u;
                if (ks & 1) mma(d, a, b0, b1); else mma(c, a, b0, b1);
            }
            if (t == 0) {
                const uint32_t qs = sm + OFF_QS + (w * 16 + g) * 2;
                sts16(qs, f2bf(c[0] + d[0])); sts16(qs + VROW, f2bf(c[1] + d[1]));
                sts16(qs + 16, f2bf(c[2] + d[2])); sts16(qs + VROW + 16, f2bf(c[3] + d[3]));
            }
            bar_sync(2, 256);
            if (w == 0) {
                const int b = lane >> 4, cc = lane & 15;
                g_qabs[(b * 32 + h) * 64 + ((j * 16 + cc) ^ (h & 7))] = lds128(sm + OFF_QS + b * VROW + cc * 16);
                __syncwarp();
                if (lane == 0) {
                    cnt_rendezvous(&g_cnt[0], tag * 128u, 18);
                    TS(10);
                    mbar_expect(bars + B_GATH * 8, 2 * CH);
                    bulk1d_n(sm + OFF_S2, g_qabs + (cta >> 6) * 2048, 2 * CH, bars + B_GATH * 8);
                }
                __syncwarp();
            }
        }
        mbar_wait(bars + B_GATH * 8, 0);
        if (st == 0) TS(11);
        {
            const int mt = w & 1, kg = w >> 1;
            const uint32_t qa = sm + OFF_S2 + (mt * 16 + rr + 8 * (i & 1)) * 1024;
            const uint32_t ka = sm + OFF_S0 + kg * CH + (rr + 8 * (i >> 1)) * 128;
            float s0[4] = {0.f, 0.f, 0.f, 0.f}, s1[4] = {0.f, 0.f, 0.f, 0.f};
            mbar_wait(bars + (B_CKV + kg) * 8, 0);
#pragma unroll 2
            for (int gq = 0; gq < 8; gq++) {
#pragma unroll
                for (int k4 = 0; k4 < 4; k4++) {
                    uint32_t a[4], b[4];
                    ldsm4(a, qa + gq * 128 + (((2 * k4 + (i >> 1)) ^ rr) << 4));
                    ldsm4(b, ka + gq * 2048 + (((2 * k4 + (i & 1)) ^ rr) << 4));
                    mma(s0, a, b[0], b[1]);
                    mma(s1, a, b[2], b[3]);
                }
            }
            const uint32_t sa = sm + OFF_SC + ((mt * 16 + g) * 68 + kg * 16 + 2 * t) * 4;
            stsf2(sa, s0[0], s0[1]); stsf2(sa + 32, s1[0], s1[1]);
            stsf2(sa + 8 * 68 * 4, s0[2], s0[3]); stsf2(sa + 8 * 68 * 4 + 32, s1[2], s1[3]);
        }
        bar_sync(2, 256);
        {
            const int head = w * 4 + i;
            const uint32_t sa = sm + OFF_SC + (head * 68 + rr * 8) * 4;
            const uint4 u0 = lds128(sa), u1 = lds128(sa + 16);
            float s[8] = {__uint_as_float(u0.x), __uint_as_float(u0.y), __uint_as_float(u0.z), __uint_as_float(u0.w),
                          __uint_as_float(u1.x), __uint_as_float(u1.y), __uint_as_float(u1.z), __uint_as_float(u1.w)};
            float mx = s[0];
#pragma unroll
            for (int k = 1; k < 8; k++) mx = fmaxf(mx, s[k]);
#pragma unroll
            for (int o = 1; o < 8; o <<= 1) mx = fmaxf(mx, __shfl_xor_sync(0xffffffffu, mx, o));
            float sum = 0.f;
#pragma unroll
            for (int k = 0; k < 8; k++) { s[k] = ex2((s[k] - mx) * (SCALE * LOG2E)); sum += s[k]; }
#pragma unroll
            for (int o = 1; o < 8; o <<= 1) sum += __shfl_xor_sync(0xffffffffu, sum, o);
            const float inv = __fdividef(1.f, sum);
            uint4 p;
            p.x = pack2(s[0] * inv, s[1] * inv); p.y = pack2(s[2] * inv, s[3] * inv);
            p.z = pack2(s[4] * inv, s[5] * inv); p.w = pack2(s[6] * inv, s[7] * inv);
            sts128(sm + OFF_P + head * 128 + ((rr ^ (head & 7)) << 4), p);
            if (rr == 0) ((float*)g_lse)[head * 128 + cta] = mx * (SCALE * LOG2E) + lg2(sum);
        }
        bar_sync(2, 256);
        {
            float o[2][8][4];
#pragma unroll
            for (int mt = 0; mt < 2; mt++)
#pragma unroll
                for (int n = 0; n < 8; n++) { o[mt][n][0] = o[mt][n][1] = o[mt][n][2] = o[mt][n][3] = 0.f; }
            const uint32_t pa = sm + OFF_P + (rr + 8 * (i & 1)) * 128;
            const uint32_t va = sm + OFF_S0 + w * 2048 + (rr + 8 * (i & 1)) * 128;
#pragma unroll 1
            for (int kq = 0; kq < 4; kq++) {
                uint32_t a0[4], a1[4];
                ldsm4(a0, pa + (((2 * kq + (i >> 1)) ^ rr) << 4));
                ldsm4(a1, pa + 2048 + (((2 * kq + (i >> 1)) ^ rr) << 4));
#pragma unroll
                for (int n = 0; n < 8; n += 2) {
                    uint32_t b[4];
                    ldsm4t(b, va + kq * CH + (((n + (i >> 1)) ^ rr) << 4));
                    mma(o[0][n], a0, b[0], b[1]); mma(o[1][n], a1, b[0], b[1]);
                    mma(o[0][n + 1], a0, b[2], b[3]); mma(o[1][n + 1], a1, b[2], b[3]);
                }
            }
#pragma unroll
            for (int mt = 0; mt < 2; mt++)
#pragma unroll
                for (int hf = 0; hf < 2; hf++) {
                    const uint32_t dst = sm + OFF_S2 + (mt * 16 + hf * 8 + g) * 1024 + w * 128 + t * 16;
#pragma unroll
                    for (int nb = 0; nb < 2; nb++) {
                        uint4 v;
                        v.x = pack2(o[mt][nb * 4 + 0][hf * 2], o[mt][nb * 4 + 0][hf * 2 + 1]);
                        v.y = pack2(o[mt][nb * 4 + 1][hf * 2], o[mt][nb * 4 + 1][hf * 2 + 1]);
                        v.z = pack2(o[mt][nb * 4 + 2][hf * 2], o[mt][nb * 4 + 2][hf * 2 + 1]);
                        v.w = pack2(o[mt][nb * 4 + 3][hf * 2], o[mt][nb * 4 + 3][hf * 2 + 1]);
                        sts128(dst + nb * 64, v);
                    }
                }
            asm volatile("fence.proxy.async.shared::cta;" ::: "memory");
            __syncwarp();
            if (lane == 0) mbar_arrive(bars + B_FREE * 8);
            if (st < 82) *(st < 64 ? &g_e4[cta][st] : st < 80 ? &g_e5[cta][st - 64] : &g_l5[h][j * 2 + st - 80]) = make_uint4(EMPTY, EMPTY, EMPTY, EMPTY);
            else if (st < 84) ((uint4*)out)[cta * 2 + st - 82] = make_uint4(0u, 0u, 0u, 0u);
        }
        bar_sync(2, 256);
        if (st == 0) {
            TS(12);
#pragma unroll 1
            for (int k = 0; k < ST_SPLIT; k++) {
                asm volatile("cp.async.bulk.tensor.3d.global.shared::cta.bulk_group [%0, {%2,%3,%4}], [%1];"
                             ::"l"(&maps.ctxp), "r"(sm + OFF_S2 + k * (2 * CH / ST_SPLIT)), "r"(0), "r"(cta), "r"(k * (128 / ST_SPLIT)) : "memory");
                if (k + 1 < ST_SPLIT) __nanosleep(ST_GAP);
            }
            asm volatile("cp.async.bulk.commit_group;" ::: "memory");
            asm volatile("cp.async.bulk.wait_group 0;" ::: "memory");
            cnt_rendezvous(&g_cnt[32], tag * 128u, 20);
            TS(13);
            mbar_expect(bars + B_GATH * 8, 2 * CH + 512);
            bulk1d_n(sm + OFF_LSE, g_lse + h * 32, 512, bars + B_GATH * 8);
            bulk1d_n(sm + OFF_S2, g_ctxp + cta * 2048, 2 * CH, bars + B_GATH * 8);
        }
        __syncwarp();
        {
            mbar_wait(bars + B_GATH * 8, 1);
            if (st == 0) TS(22);
            uint4 v[8];
#pragma unroll
            for (int k = 0; k < 8; k++) v[k] = lds128(sm + OFF_S2 + (k * 256 + st) * 16);
            float ls[4];
#pragma unroll
            for (int k = 0; k < 4; k++) ls[k] = ldsf(sm + OFF_LSE + (k * 32 + lane) * 4);
            float m0 = fmaxf(ls[0], ls[1]), m1 = fmaxf(ls[2], ls[3]);
#pragma unroll
            for (int o = 16; o; o >>= 1) { m0 = fmaxf(m0, __shfl_xor_sync(0xffffffffu, m0, o)); m1 = fmaxf(m1, __shfl_xor_sync(0xffffffffu, m1, o)); }
            ls[0] = ex2(ls[0] - m0); ls[1] = ex2(ls[1] - m0); ls[2] = ex2(ls[2] - m1); ls[3] = ex2(ls[3] - m1);
            float z0 = ls[0] + ls[1], z1 = ls[2] + ls[3];
#pragma unroll
            for (int o = 16; o; o >>= 1) { z0 += __shfl_xor_sync(0xffffffffu, z0, o); z1 += __shfl_xor_sync(0xffffffffu, z1, o); }
            z0 = __fdividef(1.f, z0); z1 = __fdividef(1.f, z1);
            ls[0] *= z0; ls[1] *= z0; ls[2] *= z1; ls[3] *= z1;
            float a[2][8];
#pragma unroll
            for (int e = 0; e < 8; e++) a[0][e] = a[1][e] = 0.f;
            const int rg = st >> 4;
#pragma unroll
            for (int k = 0; k < 8; k++) {
                const float wt = __shfl_sync(0xffffffffu, ls[k >> 1], rg + 16 * (k & 1));
                const uint32_t u[4] = {v[k].x, v[k].y, v[k].z, v[k].w};
#pragma unroll
                for (int e = 0; e < 4; e++) {
                    a[k >> 2][2 * e] += wt * __uint_as_float(u[e] << 16);
                    a[k >> 2][2 * e + 1] += wt * __uint_as_float(u[e] & 0xffff0000u);
                }
            }
            const int b = lane >> 4, u16 = lane & 15;
            const uint32_t ra = sm + OFF_SC + (w * 256 + b * 128 + (u16 >> 3) * 64 + ((u16 >> 2) & 1) * 32 + (u16 & 3) * 2) * 4;
#pragma unroll
            for (int e = 0; e < 8; e += 2) {
                const float k0 = b ? a[1][e] : a[0][e], k1 = b ? a[1][e + 1] : a[0][e + 1];
                const float s0 = b ? a[0][e] : a[1][e], s1 = b ? a[0][e + 1] : a[1][e + 1];
                stsf2(ra + (e >> 1) * 32, k0 + __shfl_xor_sync(0xffffffffu, s0, 16), k1 + __shfl_xor_sync(0xffffffffu, s1, 16));
            }
            bar_sync(2, 256);
            if (st == 0) mbar_arrive(bars + B_S2 * 8);
            float s = 0.f;
#pragma unroll
            for (int k = 0; k < 8; k++) s += ldsf(sm + OFF_SC + (k * 256 + st) * 4);
            const float hi = bfround(s);
            const uint32_t ca = sm + OFF_CC + (st >> 7) * VROW + (st & 127) * 2;
            sts16(ca, f2bf(hi)); sts16(ca + 2 * VROW, f2bf(s - hi));
            bar_sync(2, 256);
        }
        matvecT(c, sm + OFF_S1, sm + OFF_CC, 4, bars + B_WUV * 8, w, lane);
#pragma unroll
        for (int k = 0; k < 4; k++) c[k] += __shfl_down_sync(0xffffffffu, c[k], 1);
        if (t == 0) {
            float* const e = (float*)g_e4[cta] + w * 16 + g;
            mail_put(e, c[0]); mail_put(e + 128, c[1]); mail_put(e + 8, c[2]); mail_put(e + 136, c[3]);
        }
        __syncwarp();
        if (lane == 0) mbar_arrive(bars + B_FREE * 8);
        if (st == 0) TS(23);
        {
            const uint4* const pv = &g_e4[(cta & ~15) + (w >> 1) * 4][(w & 1) * 32 + lane];
            uint4 x[4];
            uint32_t it = 0;
            sleep_ns(POLL_DELAY2);
            while (true) {
#pragma unroll
                for (int k = 0; k < 4; k++) { x[k].x = x[k].y = x[k].z = x[k].w = 0u; mail_get(x[k], pv + k * 64); }
                if (!__any_sync(0xffffffffu, mail_missing(x[0]) | mail_missing(x[1]) | mail_missing(x[2]) | mail_missing(x[3]))) break;
                if (++it > SPIN_MAX) __trap();
                __nanosleep(BACKOFF);
            }
#define SUM4(e) ((__uint_as_float(x[0].e) + __uint_as_float(x[1].e)) + (__uint_as_float(x[2].e) + __uint_as_float(x[3].e)))
            sts64(sm + OFF_CA + w * VROW + lane * 8, pack2(SUM4(x), SUM4(y)), pack2(SUM4(z), SUM4(w)));
#undef SUM4
        }
        if (st == 0) TS(14);
        bar_sync(4, 256 + 128);
        {
            const uint32_t a0 = sm + OFF_S0 + w * 1024 + (rr + 8 * (i >> 1)) * 64 + (((i & 1) ^ (rr >> 1)) << 4);
            const uint4* const pv = pin(&g_e5[(cta & ~15) + (w >> 1) * 4 + (g & 3)][(w & 1) * 8 + (g >> 2) * 4 + t]);
            const uint32_t* const pl = pin((const uint32_t*)g_l5[(h & ~3) + (w >> 1)] + t);
            const uint32_t wa = sm + OFF_SC + ((w * 2 + (t >> 1)) * 80 + (t & 1) * 40 + g) * 4;
            __nv_bfloat16* const outp = pin(out + (lane >> 4) * 1024 + 512 + (cta & 15) * 32 + (lane & 15) * 2);
            uint32_t a[4][2][4], xl = 0u, it = 0;
            uint4 x = make_uint4(0u, 0u, 0u, 0u);
            while (true) {
                if (lane < 4) asm volatile("atom.relaxed.gpu.global.or.b32 %0, [%1], 0;" : "=r"(xl) : "l"(pl) : "memory");
                if (!__any_sync(0xffffffffu, xl == EMPTY)) break;
                if (POLL_GAP) __nanosleep(POLL_GAP);
                if (++it > SPIN_MAX) __trap();
            }
            if (st == 0) TS(25);
            mail_get(x, pv);
            float w0, w1;
            merge_weights(__shfl_sync(0xffffffffu, xl, (t & 1) * 2), __shfl_sync(0xffffffffu, xl, (t & 1) * 2 + 1), w0, w1);
#pragma unroll
            for (int q = 0; q < 4; q++) {
                mbar_wait(bars + (B_WO + q) * 8, 0);
                ldsm4t(a[q][0], a0 + q * 8192);
                ldsm4t(a[q][1], (a0 ^ 32) + q * 8192);
            }
            if (st == 0) TS(26);
            while (true) {
                const bool n = mail_missing(x);
                if (!__any_sync(0xffffffffu, n)) break;
                mail_get(x, pv, n);
                if (++it > SPIN_MAX) __trap();
            }
            if (st == 0) TS(16);
            float d[2][2][4];
#pragma unroll
            for (int k = 0; k < 4; k++) {
                float (&dk)[4] = d[k >> 1][k & 1];
                dk[0] = dk[1] = dk[2] = dk[3] = 0.f;
                mma(dk, a[k >> 1][k & 1], x.x, x.y);
            }
#pragma unroll
            for (int k = 0; k < 4; k++) mma(d[k >> 1][k & 1], a[2 + (k >> 1)][k & 1], x.z, x.w);
#pragma unroll
            for (int k = 0; k < 4; k++) {
                const float s0 = (t & 2) ? d[1][k >> 1][(k & 1) * 2] : d[0][k >> 1][(k & 1) * 2];
                const float s1 = (t & 2) ? d[1][k >> 1][(k & 1) * 2 + 1] : d[0][k >> 1][(k & 1) * 2 + 1];
                sts32(wa + k * 32, __float_as_uint(w0 * s0 + w1 * s1));
            }
            if (st == 0) TS(17);
            if (w == 0) {
                bar_sync(5, 256);
                const uint32_t ra = sm + OFF_SC + ((lane >> 4) * 40 + (lane & 15) * 2) * 4;
                float2 r[16];
#pragma unroll
                for (int k = 0; k < 16; k++) r[k] = ldsf2(ra + k * 320);
#pragma unroll
                for (int o = 1; o < 16; o <<= 1)
#pragma unroll
                    for (int k = 0; k < 16; k += 2 * o) { r[k].x += r[k + o].x; r[k].y += r[k + o].y; }
                out_add(outp, r[0].x, r[0].y);
            } else {
                bar_arrive(5, 256);
            }
        }
    }
}

typedef CUresult (*EncodeFn)(CUtensorMap*, CUtensorMapDataType, cuuint32_t, void*, const cuuint64_t*, const cuuint64_t*,
                             const cuuint32_t*, const cuuint32_t*, CUtensorMapInterleave, CUtensorMapSwizzle,
                             CUtensorMapL2promotion, CUtensorMapFloatOOBfill);

void make_map(EncodeFn enc, CUtensorMap* m, void* p, unsigned rows, unsigned cols, unsigned br, unsigned bg) {
    cuuint64_t gd[3] = {64, rows, cols / 64};
    cuuint64_t gs[2] = {(cuuint64_t)cols * 2, 128};
    cuuint32_t bx[3] = {64, br, bg};
    cuuint32_t es[3] = {1, 1, 1};
    enc(m, CU_TENSOR_MAP_DATA_TYPE_BFLOAT16, 3, p, gd, gs, bx, es, CU_TENSOR_MAP_INTERLEAVE_NONE,
        CU_TENSOR_MAP_SWIZZLE_128B, CU_TENSOR_MAP_L2_PROMOTION_L2_128B, CU_TENSOR_MAP_FLOAT_OOB_FILL_NONE);
}

}

extern "C" void kernel_launch(void* const* d_in, const int* in_sizes, int n_in, void* d_out, int out_size) {
    static EncodeFn enc = nullptr;
    if (!enc) {
        void* fn = nullptr;
        cudaDriverEntryPointQueryResult qr;
        cudaGetDriverEntryPoint("cuTensorMapEncodeTiled", &fn, cudaEnableDefault, &qr);
        enc = (EncodeFn)fn;
        cudaFuncSetAttribute(fused_decode_kernel, cudaFuncAttributeMaxDynamicSharedMemorySize, SMEM_BYTES);
    }
    Maps maps;
    make_map(enc, &maps.wqB, d_in[9], 512, 4096, 64, 2);
    make_map(enc, &maps.wqA, d_in[2], 512, 4096, 64, 2);
    make_map(enc, &maps.wuk, d_in[3], 512, 4096, 64, 2);
    make_map(enc, &maps.wuv, d_in[4], 512, 4096, 64, 2);
    for (int k = 0; k < 2; k++) {
        cuuint64_t gd[3] = {512, 128, 32};
        cuuint64_t gs[2] = {1024, 131072};
        cuuint32_t bx[3] = {32, 32, 4};
        cuuint32_t es[3] = {1, 1, 1};
        enc(&maps.woB + k, CU_TENSOR_MAP_DATA_TYPE_BFLOAT16, 3, d_in[k ? 5 : 10], gd, gs, bx, es, CU_TENSOR_MAP_INTERLEAVE_NONE,
            CU_TENSOR_MAP_SWIZZLE_64B, (CUtensorMapL2promotion)WOPROMO, CU_TENSOR_MAP_FLOAT_OOB_FILL_NONE);
    }
    make_map(enc, &maps.ckv, d_in[1], 8192, 512, 16, 8);
    {
        void* p = nullptr;
        cudaGetSymbolAddress(&p, g_ctxp);
        cuuint64_t gd[3] = {128, 128, 128};
        cuuint64_t gs[2] = {256, 32768};
        cuuint32_t bx[3] = {128, 1, 128 / ST_SPLIT};
        cuuint32_t es[3] = {1, 1, 1};
        enc(&maps.ctxp, CU_TENSOR_MAP_DATA_TYPE_BFLOAT16, 3, p, gd, gs, bx, es, CU_TENSOR_MAP_INTERLEAVE_NONE,
            CU_TENSOR_MAP_SWIZZLE_NONE, CU_TENSOR_MAP_L2_PROMOTION_NONE, CU_TENSOR_MAP_FLOAT_OOB_FILL_NONE);
    }
    fused_decode_kernel<<<NCTA, NTHREADS, SMEM_BYTES>>>((const char*)d_in[9], maps, (const char*)d_in[7], (const char*)d_in[8],
                                                         (const __nv_bfloat16*)d_in[0], (const __nv_bfloat16*)d_in[6],
                                                         (__nv_bfloat16*)d_out, 0u);
}
```

```cpp
#include <cuda_runtime.h>
#include <cuda.h>
#include <cuda_bf16.h>
#include <stdint.h>

#define RING 7
#define WIN 4
#define WHI 5
#define THETA 64
#define END_V 40
#define GATE_W 64
#define PREWIN 2
#define TAILWIN 3
#define ONEBAR 0
#define G_SPLIT 8
#define G_GAP 500
#define TX 0
#define POLL_GAP 0
#define WOPROMO CU_TENSOR_MAP_L2_PROMOTION_L2_256B
#define POLL_DELAY 2500
#define POLL_DELAY2 4000
#define ST_SPLIT 8
#define ST_GAP 500
#define BACKOFF 200
#define BACKOFF2 100

namespace {

constexpr int NCTA = 128;
constexpr int NTHREADS = 448;
constexpr uint32_t CH = 16384;
constexpr int NTILE = 32;
constexpr int RUN = 4;

constexpr uint32_t OFF_RING = 0;
constexpr uint32_t OFF_S0 = RING * CH;
constexpr uint32_t OFF_S1 = OFF_S0 + 2 * CH;
constexpr uint32_t OFF_S2 = OFF_S1 + 2 * CH;
constexpr uint32_t OFF_P = OFF_S2 + 2 * CH;
constexpr uint32_t OFF_SC = OFF_P + 4096;
constexpr uint32_t VROW = 272;
constexpr uint32_t OFF_XB = OFF_SC + 8704;
constexpr uint32_t OFF_XA = OFF_XB + 2 * VROW;
constexpr uint32_t OFF_QA = OFF_XA + 2 * VROW;
constexpr uint32_t OFF_QS = OFF_QA + 2 * VROW;
constexpr uint32_t OFF_CC = OFF_QS + 2 * VROW;
constexpr uint32_t OFF_CA = OFF_P;
constexpr uint32_t OFF_QB = OFF_CC + 4 * VROW;
constexpr uint32_t OFF_LSE = OFF_QB + 256;
constexpr uint32_t OFF_ML = OFF_LSE + 512;
constexpr uint32_t OFF_TAG = OFF_ML + 32;
constexpr uint32_t OFF_NOW = OFF_TAG + 4;
constexpr uint32_t OFF_WIN = OFF_TAG + 8;
constexpr uint32_t OFF_TWIN = OFF_TAG + 12;
constexpr uint32_t OFF_BAR = OFF_TAG + 16;
constexpr int B_EMPTY = RING;
constexpr int B_WQB = 2 * RING;
constexpr int B_WQA = B_WQB + 2;
constexpr int B_WUK = B_WQA + 2;
constexpr int B_WUV = B_WUK + 2;
constexpr int B_CKV = B_WUV + 2;
constexpr int B_WO = B_CKV + 4;
constexpr int B_FREE = B_WO + 8;
constexpr int B_GATH = B_FREE + 1;
constexpr int B_S2 = B_GATH + 1;
constexpr int NBAR = B_S2 + 1;
constexpr uint32_t TS_OFF = OFF_BAR + NBAR * 8;
constexpr uint32_t SMEM_USED = TS_OFF;
constexpr uint32_t SMEM_BYTES = SMEM_USED + 1024;
static_assert(SMEM_BYTES <= 232448, "smem");
static_assert(RING >= RUN && RING >= WHI && WHI >= WIN && WIN >= 3 && WIN <= 6, "windows");

constexpr float LOG2E = 1.4426950408889634f;
constexpr float SCALE = 0.08838834764831845f;
#define SPIN_LOG 22
constexpr uint32_t SPIN_MAX = 1u << SPIN_LOG;

struct Maps { CUtensorMap wqB, wqA, wuk, wuv, woB, woA, ckv, ctxp; };

__device__ unsigned g_epoch;
__device__ __align__(256) unsigned g_cnt[96];
__device__ __align__(256) ulonglong2 g_e1[2][NCTA][128];
__device__ __align__(256) uint4 g_qabs[2 * 32 * 64];
__device__ __align__(256) uint4 g_ctxp[NCTA * 128 * 16];
__device__ __align__(256) float4 g_lse[32 * 32];
__device__ __align__(256) uint4 g_e4[NCTA][64];
__device__ __align__(256) uint4 g_e5[NCTA][16];
__device__ __align__(256) uint4 g_l5[32][8];
constexpr uint32_t EMPTY = 0xffffffffu;

#define TS(k) do {} while (0)

__device__ __forceinline__ void mbar_init(uint32_t b, int c) { asm volatile("mbarrier.init.shared::cta.b64 [%0], %1;" ::"r"(b), "r"(c) : "memory"); }
__device__ __forceinline__ void mbar_expect(uint32_t b, uint32_t bytes) { asm volatile("mbarrier.arrive.expect_tx.shared::cta.b64 _, [%0], %1;" ::"r"(b), "r"(bytes) : "memory"); }
__device__ __forceinline__ void mbar_arrive(uint32_t b) { asm volatile("mbarrier.arrive.shared::cta.b64 _, [%0];" ::"r"(b) : "memory"); }
__device__ __forceinline__ void mbar_wait(uint32_t b, uint32_t ph) {
    asm volatile("{\n.reg .pred p;\n.reg .u32 n;\nmov.u32 n, 0;\n"
                 "W:\nmbarrier.try_wait.parity.shared::cta.b64 p, [%0], %1;\n@p bra D;\n"
                 "add.u32 n, n, 1;\nsetp.le.u32 p, n, %2;\n@p bra W;\ntrap;\nD:\n}" ::"r"(b), "r"(ph), "n"(SPIN_MAX) : "memory");
}
__device__ __forceinline__ uint32_t mbar_test(uint32_t b, uint32_t ph) {
    uint32_t ok;
    asm volatile("{\n.reg .pred p;\nmbarrier.test_wait.parity.shared::cta.b64 p, [%1], %2;\nselp.u32 %0, 1, 0, p;\n}" : "=r"(ok) : "r"(b), "r"(ph) : "memory");
    return ok;
}
__device__ __forceinline__ void bulk1d(uint32_t dst, const void* src, uint32_t bar, uint64_t pol) {
    asm volatile("cp.async.bulk.shared::cluster.global.mbarrier::complete_tx::bytes.L2::cache_hint [%0], [%1], %2, [%3], %4;"
                 ::"r"(dst), "l"(src), "n"(CH), "r"(bar), "l"(pol) : "memory");
}
__device__ __forceinline__ void bulk1d_n(uint32_t dst, const void* src, uint32_t bytes, uint32_t bar) {
    asm volatile("cp.async.bulk.shared::cluster.global.mbarrier::complete_tx::bytes [%0], [%1], %2, [%3];"
                 ::"r"(dst), "l"(src), "r"(bytes), "r"(bar) : "memory");
}
__device__ __forceinline__ void tma3d(uint32_t dst, const CUtensorMap* map, int c1, int c2, uint32_t bar, uint64_t pol, int c0 = 0) {
    asm volatile("cp.async.bulk.tensor.3d.shared::cluster.global.mbarrier::complete_tx::bytes.L2::cache_hint [%0], [%1, {%3,%4,%5}], [%2], %6;"
                 ::"r"(dst), "l"(map), "r"(bar), "r"(c0), "r"(c1), "r"(c2), "l"(pol) : "memory");
}
__device__ __forceinline__ void bar_sync(int id, int n) { asm volatile("barrier.cta.sync %0, %1;" ::"r"(id), "r"(n) : "memory"); }
__device__ __forceinline__ void bar_arrive(int id, int n) { asm volatile("barrier.cta.arrive %0, %1;" ::"r"(id), "r"(n) : "memory"); }
__device__ __forceinline__ void ldsm4(uint32_t (&r)[4], uint32_t a) {
    asm volatile("ldmatrix.sync.aligned.m8n8.x4.shared.b16 {%0,%1,%2,%3}, [%4];" : "=r"(r[0]), "=r"(r[1]), "=r"(r[2]), "=r"(r[3]) : "r"(a) : "memory");
}
__device__ __forceinline__ void ldsm4t(uint32_t (&r)[4], uint32_t a) {
    asm volatile("ldmatrix.sync.aligned.m8n8.x4.trans.shared.b16 {%0,%1,%2,%3}, [%4];" : "=r"(r[0]), "=r"(r[1]), "=r"(r[2]), "=r"(r[3]) : "r"(a) : "memory");
}
__device__ __forceinline__ void mma(float (&c)[4], const uint32_t (&a)[4], uint32_t b0, uint32_t b1) {
    asm volatile("mma.sync.aligned.m16n8k16.row.col.f32.bf16.bf16.f32 {%0,%1,%2,%3}, {%4,%5,%6,%7}, {%8,%9}, {%0,%1,%2,%3};"
                 : "+f"(c[0]), "+f"(c[1]), "+f"(c[2]), "+f"(c[3]) : "r"(a[0]), "r"(a[1]), "r"(a[2]), "r"(a[3]), "r"(b0), "r"(b1));
}
__device__ __forceinline__ uint32_t lds32(uint32_t a) { uint32_t v; asm volatile("ld.shared.b32 %0, [%1];" : "=r"(v) : "r"(a) : "memory"); return v; }
__device__ __forceinline__ uint32_t ldsv(uint32_t a) { uint32_t v; asm volatile("ld.volatile.shared.b32 %0, [%1];" : "=r"(v) : "r"(a) : "memory"); return v; }
__device__ __forceinline__ void stsv(uint32_t a, uint32_t v) { asm volatile("st.volatile.shared.b32 [%0], %1;" ::"r"(a), "r"(v) : "memory"); }
__device__ __forceinline__ float ldsf(uint32_t a) { float v; asm volatile("ld.shared.f32 %0, [%1];" : "=f"(v) : "r"(a) : "memory"); return v; }
__device__ __forceinline__ uint4 lds128(uint32_t a) { uint4 v; asm volatile("ld.shared.v4.b32 {%0,%1,%2,%3}, [%4];" : "=r"(v.x), "=r"(v.y), "=r"(v.z), "=r"(v.w) : "r"(a) : "memory"); return v; }
__device__ __forceinline__ void sts16(uint32_t a, uint16_t v) { asm volatile("st.shared.b16 [%0], %1;" ::"r"(a), "h"(v) : "memory"); }
__device__ __forceinline__ void sts32(uint32_t a, uint32_t v) { asm volatile("st.shared.b32 [%0], %1;" ::"r"(a), "r"(v) : "memory"); }
__device__ __forceinline__ void stsf2(uint32_t a, float x, float y) { asm volatile("st.shared.v2.f32 [%0], {%1,%2};" ::"r"(a), "f"(x), "f"(y) : "memory"); }
__device__ __forceinline__ void sts128(uint32_t a, uint4 v) { asm volatile("st.shared.v4.b32 [%0], {%1,%2,%3,%4};" ::"r"(a), "r"(v.x), "r"(v.y), "r"(v.z), "r"(v.w) : "memory"); }
__device__ __forceinline__ uint16_t f2bf(float x) { return __bfloat16_as_ushort(__float2bfloat16_rn(x)); }
__device__ __forceinline__ float bfround(float x) { return __bfloat162float(__float2bfloat16_rn(x)); }
__device__ __forceinline__ uint32_t pack2(float lo, float hi) { uint32_t r; asm("cvt.rn.bf16x2.f32 %0, %1, %2;" : "=r"(r) : "f"(hi), "f"(lo)); return r; }
__device__ __forceinline__ float ex2(float x) { float r; asm("ex2.approx.ftz.f32 %0, %1;" : "=f"(r) : "f"(x)); return r; }
__device__ __forceinline__ float lg2(float x) { float r; asm("lg2.approx.ftz.f32 %0, %1;" : "=f"(r) : "f"(x)); return r; }

__device__ __forceinline__ float rcp(float x) { float r; asm("rcp.approx.ftz.f32 %0, %1;" : "=f"(r) : "f"(x)); return r; }
__device__ __forceinline__ void merge_weights(uint32_t l0, uint32_t l1, float& w0, float& w1) {
    const float a = __uint_as_float(l0), b = __uint_as_float(l1), mx = fmaxf(a, b), e0 = ex2(a - mx), e1 = ex2(b - mx), r = rcp(e0 + e1);
    w0 = e0 * r; w1 = e1 * r;
}

__device__ __forceinline__ void sleep_ns(uint32_t ns) {
    uint32_t t0, t;
    asm volatile("mov.u32 %0, %clock;" : "=r"(t0));
    do { __nanosleep(200); asm volatile("mov.u32 %0, %clock;" : "=r"(t)); } while (t - t0 < 2 * ns);
}

__device__ __forceinline__ void ll_store2(ulonglong2* p, float a, float b, uint32_t tag) {
    unsigned long long x = ((unsigned long long)tag << 32) | __float_as_uint(a);
    unsigned long long y = ((unsigned long long)tag << 32) | __float_as_uint(b);
    asm volatile("st.relaxed.gpu.global.v2.b64 [%0], {%1,%2};" ::"l"(p), "l"(x), "l"(y) : "memory");
}
__device__ __forceinline__ void ll_ld2(const void* p, unsigned long long& x, unsigned long long& y) {
    asm volatile("ld.relaxed.gpu.global.v2.b64 {%0,%1}, [%2];" : "=l"(x), "=l"(y) : "l"(p) : "memory");
}
__device__ __forceinline__ void ll_gather4(const ulonglong2* p, uint32_t tag, float& r0, float& r1) {
    unsigned long long x[4], y[4]; uint32_t it = 0;
    while (true) {
        bool ok = true;
#pragma unroll
        for (int k = 0; k < 4; k++) ll_ld2(p + k * 128, x[k], y[k]);
#pragma unroll
        for (int k = 0; k < 4; k++) ok = ok && (uint32_t)(x[k] >> 32) == tag && (uint32_t)(y[k] >> 32) == tag;
        if (ok) break;
        if (++it > SPIN_MAX) __trap();
        __nanosleep(BACKOFF);
    }
    r0 = (__uint_as_float((uint32_t)x[0]) + __uint_as_float((uint32_t)x[1])) + (__uint_as_float((uint32_t)x[2]) + __uint_as_float((uint32_t)x[3]));
    r1 = (__uint_as_float((uint32_t)y[0]) + __uint_as_float((uint32_t)y[1])) + (__uint_as_float((uint32_t)y[2]) + __uint_as_float((uint32_t)y[3]));
}
__device__ __forceinline__ void cnt_rendezvous(unsigned* c, uint32_t target, int tsk) {
    TS(tsk);
    asm volatile("red.release.gpu.global.add.u32 [%0], 1;" ::"l"(c) : "memory");
    if (tsk == 18) TS(tsk + 1);
    uint32_t v, it = 0;
    while (true) {
        asm volatile("ld.acquire.gpu.global.u32 %0, [%1];" : "=r"(v) : "l"(c) : "memory");
        if ((int)(v - target) >= 0) break;
        if (++it > SPIN_MAX) __trap();
        __nanosleep(BACKOFF);
    }
    asm volatile("fence.proxy.async.global;" ::: "memory");
}

__device__ __forceinline__ void matvec_loadA(uint32_t (&a)[8][4], uint32_t tile, uint32_t bar, int w, int lane) {
    const int i = lane >> 3, rr = lane & 7, chunk = 2 * w + (i & 1);
    const uint32_t a0 = tile + (chunk >> 3) * 8192 + (rr + 8 * (i >> 1)) * 128 + (((chunk & 7) ^ rr) << 4);
#pragma unroll
    for (int hh = 0; hh < 2; hh++) {
        mbar_wait(bar + hh * 8, 0);
#pragma unroll
        for (int k = 0; k < 4; k++) ldsm4t(a[hh * 4 + k], a0 + hh * CH + k * 2048);
    }
}
__device__ __forceinline__ void matvec_mma(float (&c)[4], const uint32_t (&a)[8][4], uint32_t vec, int nvec, int lane) {
    const uint32_t va = vec + (lane & (nvec - 1)) * VROW + (lane >> 3) * 16;
    float d[4][4];
#pragma unroll
    for (int q = 0; q < 4; q++) {
        uint32_t b[4];
        ldsm4(b, va + q * 64);
        d[q][0] = d[q][1] = d[q][2] = d[q][3] = 0.f;
        mma(d[q], a[2 * q], b[0], b[1]);
        mma(d[q], a[2 * q + 1], b[2], b[3]);
    }
#pragma unroll
    for (int k = 0; k < 4; k++) c[k] = (d[0][k] + d[1][k]) + (d[2][k] + d[3][k]);
}
__device__ __forceinline__ void matvecT(float (&c)[4], uint32_t tile, uint32_t vec, int nvec, uint32_t bar, int w, int lane) {
    uint32_t a[8][4];
    matvec_loadA(a, tile, bar, w, lane);
    matvec_mma(c, a, vec, nvec, lane);
}
template <class T> __device__ __forceinline__ T* pin(T* p) { asm volatile("" : "+l"(p)); return p; }
__device__ __forceinline__ void mail_put(void* p, uint32_t v) { asm volatile("st.relaxed.gpu.global.b32 [%0], %1;" ::"l"(p), "r"(v) : "memory"); }
__device__ __forceinline__ void mail_put(void* p, float v) { mail_put(p, __float_as_uint(v)); }
__device__ __forceinline__ void out_add(__nv_bfloat16* p, float x, float y) {
    asm volatile("red.relaxed.gpu.global.add.noftz.bf16x2 [%0], %1;" ::"l"(p), "r"(pack2(x, y)) : "memory");
}
__device__ __forceinline__ bool mail_missing(const uint4& v) { return v.x == EMPTY || v.y == EMPTY || v.z == EMPTY || v.w == EMPTY; }
__device__ __forceinline__ void mail_get(uint4& v, const uint4* p, bool need = true) {
    asm volatile("{\n.reg .pred q;\nsetp.ne.u32 q, %5, 0;\n@q ld.relaxed.gpu.global.v4.b32 {%0,%1,%2,%3}, [%4];\n}"
                 : "+r"(v.x), "+r"(v.y), "+r"(v.z), "+r"(v.w) : "l"(p), "r"((uint32_t)need) : "memory");
}
__device__ __forceinline__ void sts64(uint32_t a, uint32_t x, uint32_t y) { asm volatile("st.shared.v2.b32 [%0], {%1,%2};" ::"r"(a), "r"(x), "r"(y) : "memory"); }
__device__ __forceinline__ float2 ldsf2(uint32_t a) { float2 v; asm volatile("ld.shared.v2.f32 {%0,%1}, [%2];" : "=f"(v.x), "=f"(v.y) : "r"(a) : "memory"); return v; }

__global__ void __launch_bounds__(NTHREADS, 1)
fused_decode_kernel(const char* __restrict__ wqraw, const __grid_constant__ Maps maps, const char* __restrict__ Kc, const char* __restrict__ Vc,
                    const __nv_bfloat16* __restrict__ xA, const __nv_bfloat16* __restrict__ xB,
                    __nv_bfloat16* __restrict__ out, const uint32_t zero) {
    asm volatile("{\n.reg .pred p;\nsetp.eq.u32 p, %1, 32;\n@p cp.async.bulk.prefetch.L2.global [%0], 32768;\n}"
                 ::"l"(wqraw + (size_t)blockIdx.x * 32768u), "r"(threadIdx.x) : "memory");
    extern __shared__ char smem_raw[];
    const uint32_t sm = ((uint32_t)__cvta_generic_to_shared(smem_raw) + 1023u) & ~1023u;
    const uint32_t bars = sm + OFF_BAR;
    const int cta = blockIdx.x, h = cta >> 2, j = cta & 3;
    uint64_t pol = 0;
    if (threadIdx.x == 0) {
        TS(0);
        asm volatile("createpolicy.fractional.L2::evict_first.b64 %0, 1.0;" : "=l"(pol));
#pragma unroll
        for (int i = 0; i < WIN; i++) mbar_init(bars + (B_WQB + i) * 8, 1);
        asm volatile("fence.mbarrier_init.release.cluster;" ::: "memory");
#pragma unroll
        for (int i = 0; i < WIN; i++) {
            mbar_expect(bars + (B_WQB + i) * 8, CH);
            tma3d(sm + OFF_S0 + i * CH, &maps.wqB + (i >> 1), j * 128 + (i & 1) * 64, h * 2, bars + (B_WQB + i) * 8, pol);
        }
    }
    const int tid = threadIdx.x < 64 ? threadIdx.x + 384 : threadIdx.x - 64, warp = tid >> 5, lane = tid & 31;

    if (warp == 12) {
        const size_t kvoff = ((size_t)(((j >> 1) * 32 + h) * 4096 + (j & 1) * 2048)) * 256;
        const char* kp = Kc + kvoff;
        const char* vp = Vc + kvoff;
        __syncwarp();
        bar_arrive(0, NTHREADS);
        bar_sync(3, 64);
        if (lane == 0) {
            uint32_t pb[WHI];
#pragma unroll
            for (int i = 0; i < WHI; i++) pb[i] = i < WHI - WIN ? (bars + B_WO * 8) | 1u : bars + (B_WQB + i - (WHI - WIN)) * 8;
            auto pace = [&](uint32_t bar, uint32_t par, uint32_t wina) {
                uint32_t it = 0;
                while (true) {
                    const uint32_t win = ldsv(wina);
                    uint32_t busy = 0;
#pragma unroll
                    for (int i = 0; i < WHI; i++) busy += mbar_test(pb[i] & ~1u, pb[i] & 1u) ^ 1u;
                    if (busy < win) break;
                    if (++it > SPIN_MAX) __trap();
                }
#pragma unroll
                for (int i = 0; i + 1 < WHI; i++) pb[i] = pb[i + 1];
                pb[WHI - 1] = bar | par;
            };
            auto side = [&](const CUtensorMap* m, uint32_t dst, int bidx, int c1, int c2, uint32_t wina) {
                const uint32_t bar = bars + bidx * 8;
                pace(bar, 0, wina);
                mbar_expect(bar, CH);
                tma3d(dst, m, c1, c2, bar, pol);
            };
#pragma unroll 1
            for (int i = WIN; i < 6; i++)
                side(&maps.wqB + (i >> 1), sm + OFF_S0 + i * CH, B_WQB + i, j * 128 + (i & 1) * 64, h * 2, sm + OFF_WIN);
            TS(1);
            uint32_t slot = 0, use = 0;
            int nuv = 0;
#pragma unroll 1
            for (int n = 0; n < 2 * NTILE; n++) {
                if (n == RING) {
                    mbar_wait(bars + B_FREE * 8, 0);
#pragma unroll 1
                    for (int q = 0; q < 4; q++) side(&maps.ckv, sm + OFF_S0 + q * CH, B_CKV + q, cta * 64 + q * 16, 0, sm + OFF_WIN);
                }
                if (nuv < 2 && n > RING && (n >= 2 * NTILE - 8 || mbar_test(bars + B_FREE * 8, 1))) {
                    mbar_wait(bars + B_FREE * 8, 1);
                    side(&maps.wuv, sm + OFF_S1 + nuv * CH, B_WUV + nuv, j * 128 + nuv * 64, h * 2, sm + OFF_WIN);
                    nuv++;
                }
                const uint32_t fb = bars + slot * 8;
                pace(fb, use & 1, sm + OFF_WIN);
                mbar_wait(fb + B_EMPTY * 8, (use & 1) ^ 1);
                mbar_expect(fb, CH);
                bulk1d(sm + OFF_RING + slot * CH, ((n & RUN) ? vp : kp) + (size_t)((n / (2 * RUN) * RUN + n % RUN) ^ (TX)) * CH, fb, pol);
                asm volatile("red.relaxed.gpu.global.add.u32 [%0], 1;" ::"l"(&g_cnt[64]) : "memory");
                stsv(sm + OFF_NOW, n + 1);
                if (++slot == RING) { slot = 0; use++; }
            }
            TS(2);
            mbar_wait(bars + B_FREE * 8, 0);
#pragma unroll 1
            for (int i = 0; i < 4; i++) {
                const uint32_t bar = bars + (B_WO + 2 * i) * 8;
                pace(bar + 8, 0, sm + OFF_TWIN);
                TS(32 + i);
#pragma unroll
                for (int k = 0; k < 2; k++) {
                    const uint32_t bk = (ONEBAR && i >= 2) ? bar + 8 : bar + k * 8;
                    if (ONEBAR && i >= 2) { if (!k) mbar_expect(bk, CH); } else mbar_expect(bk, CH / 2);
                    tma3d(sm + OFF_S0 + i * CH + k * (CH / 2), &maps.woB + (i >> 1), (i & 1) * 64 + k * 32, h & ~3, bk, pol, (cta & 15) * 32);
                }
            }
            TS(3);
        }
    } else if (warp == 13) {
        if (lane == 0) {
#pragma unroll
            for (int i = 0; i < NBAR; i++)
                if (i < B_WQB || i >= B_WQB + WIN)
                    mbar_init(bars + i * 8, i == B_FREE ? 8 : (i >= B_EMPTY && i < B_EMPTY + RING) ? 4 : 1);
            asm volatile("fence.mbarrier_init.release.cluster;" ::: "memory");
#pragma unroll
            for (int i = 2; i < 8; i++) asm volatile("prefetch.tensormap [%0];" ::"l"(&maps.wqB + i) : "memory");
            stsv(sm + OFF_NOW, 0); stsv(sm + OFF_WIN, WIN); stsv(sm + OFF_TWIN, PREWIN);
        }
        __syncwarp();
        bar_arrive(3, 64);
        bar_sync(0, NTHREADS);
        if (lane == 0) {
            const uint32_t base = (lds32(sm + OFF_TAG) - 1u) * (NCTA * 2 * NTILE);
            mbar_wait(bars + (B_WUK + 1) * 8, 0);
            uint32_t it = 0;
            while (true) {
                const uint32_t n = ldsv(sm + OFF_NOW);
                uint32_t v;
                asm volatile("ld.relaxed.gpu.global.u32 %0, [%1];" : "=r"(v) : "l"(&g_cnt[64]) : "memory");
                v -= base;
                if (v >= NCTA * 2 * NTILE - GATE_W) break;
                const int diff = (int)(n * NCTA) - (int)v;
                stsv(sm + OFF_WIN, diff < -THETA ? WHI : WIN - (diff > THETA) - (v >= NCTA * END_V));
                if (++it > SPIN_MAX) __trap();
                __nanosleep(BACKOFF2);
            }
            stsv(sm + OFF_WIN, WHI); stsv(sm + OFF_TWIN, TAILWIN);
            TS(24);
        }
    } else if (warp < 4) {
        const int g = lane >> 2, t = lane & 3, i = lane >> 3, rr = lane & 7;
        if (tid == 0) {
            const unsigned e = atomicAdd(&g_epoch, 1u);
            sts32(sm + OFF_TAG, (e >> 7) + 1u);
        }
        bar_sync(0, NTHREADS);
        const uint32_t tag = lds32(sm + OFF_TAG);
        {
            mbar_wait(bars + 8, 0);
            float q0, q1;
            ll_gather4(&g_e1[0][h * 4][tid], tag, q0, q1);
            sts16(sm + OFF_QB + tid * 2, f2bf((j >> 1) ? q1 : q0));
        }
        bar_sync(1, 128);
        if (tid == 0) TS(4);
        uint32_t qf[8][2];
#pragma unroll
        for (int c = 0; c < 8; c++) {
            const uint32_t a = sm + OFF_QB + (((c + g) & 7) * 8 + 2 * t) * 2;
            qf[c][0] = lds32(a); qf[c][1] = lds32(a + 128);
        }
        float acc[8][4];
#pragma unroll
        for (int c = 0; c < 8; c++) { acc[c][0] = acc[c][1] = acc[c][2] = acc[c][3] = 0.f; }
        float m = -INFINITY, l = 0.f;
        const bool diag = (t == (g >> 1));
        const uint32_t krow = sm + OFF_RING + (warp * 16 + rr + 8 * (i & 1)) * 256 + (i >> 1) * 128;
        const uint32_t vrow = sm + OFF_RING + (warp * 16 + rr + 8 * (i >> 1)) * 256 + (i & 1) * 128;
        uint32_t slot = 0, ph = 0;
        uint32_t* const e5own = pin((uint32_t*)g_e5[cta] + tid);
        uint32_t a[8][4] = {}, b0[RUN], b1[RUN];
        auto release = [&]() {
            __syncwarp();
            if (lane == 0) mbar_arrive(bars + (B_EMPTY + slot) * 8 + ((a[0][0] | a[1][0] | a[2][0] | a[3][0] | a[4][0] | a[5][0] | a[6][0] | a[7][0]) & zero));
            if (++slot == RING) { slot = 0; ph ^= 1; }
        };
        auto load_v = [&]() {
            mbar_wait(bars + slot * 8, ph);
#pragma unroll
            for (int c = 0; c < 8; c++) ldsm4t(a[c], vrow + slot * CH + (((c + rr) & 7) << 4));
        };
#pragma unroll 1
        for (int run = 0;; run++) {
            float slo[RUN], shi[RUN], mx = -INFINITY;
#pragma unroll
            for (int u = 0; u < RUN; u++) {
                mbar_wait(bars + slot * 8, ph);
#pragma unroll
                for (int c = 0; c < 8; c++) ldsm4(a[c], krow + slot * CH + (((c + rr) & 7) << 4));
                release();
                float s0[4] = {0.f, 0.f, 0.f, 0.f}, s1[4] = {0.f, 0.f, 0.f, 0.f};
#pragma unroll
                for (int c = 0; c < 8; c += 2) { mma(s0, a[c], qf[c][0], qf[c][1]); mma(s1, a[c + 1], qf[c + 1][0], qf[c + 1][1]); }
                slo[u] = diag ? bfround(bfround((g & 1) ? s0[1] + s1[1] : s0[0] + s1[0]) * SCALE) : -INFINITY;
                shi[u] = diag ? bfround(bfround((g & 1) ? s0[3] + s1[3] : s0[2] + s1[2]) * SCALE) : -INFINITY;
                mx = fmaxf(mx, fmaxf(slo[u], shi[u]));
            }
            int key = __float_as_int(mx);
            key ^= (key >> 31) & 0x7fffffff;
            key = __reduce_max_sync(0xffffffffu, key);
            key ^= (key >> 31) & 0x7fffffff;
            const float mn = fmaxf(m, __int_as_float(key));
            const float alpha = ex2((m - mn) * LOG2E);
            m = mn;
            l *= alpha;
#pragma unroll
            for (int u = 0; u < RUN; u++) {
                const float plo = ex2((slo[u] - mn) * LOG2E), phi = ex2((shi[u] - mn) * LOG2E);
                l += plo + phi;
                b0[u] = (g & 1) ? pack2(0.f, plo) : pack2(plo, 0.f);
                b1[u] = (g & 1) ? pack2(0.f, phi) : pack2(phi, 0.f);
            }
#pragma unroll
            for (int c = 0; c < 8; c++) { acc[c][0] *= alpha; acc[c][1] *= alpha; acc[c][2] *= alpha; acc[c][3] *= alpha; }
            if (run == NTILE / RUN - 1) break;
#pragma unroll
            for (int u = 0; u < RUN; u++) {
                load_v();
                release();
#pragma unroll
                for (int c = 0; c < 8; c++) mma(acc[c], a[c], b0[u], b1[u]);
            }
        }
#pragma unroll
        for (int o = 16; o; o >>= 1) l += __shfl_xor_sync(0xffffffffu, l, o);
        if (lane == 0) stsf2(sm + OFF_ML + warp * 8, m, l);
        mbar_wait(bars + B_S2 * 8, 0);
        bar_sync(1, 128);
        {
            const uint4 ml0 = lds128(sm + OFF_ML), ml1 = lds128(sm + OFF_ML + 16);
            const float m0 = __uint_as_float(ml0.x), m1 = __uint_as_float(ml0.z), m2 = __uint_as_float(ml1.x), m3 = __uint_as_float(ml1.z);
            const float M = fmaxf(fmaxf(m0, m1), fmaxf(m2, m3));
            const float L = (ex2((m0 - M) * LOG2E) * __uint_as_float(ml0.y) + ex2((m1 - M) * LOG2E) * __uint_as_float(ml0.w))
                          + (ex2((m2 - M) * LOG2E) * __uint_as_float(ml1.y) + ex2((m3 - M) * LOG2E) * __uint_as_float(ml1.w));
            const float f = ex2((m - M) * LOG2E) * rcp(L);
            const float lse = M * LOG2E + lg2(L);
            float* const l5own = pin((float*)g_l5[h] + j);
            const uint32_t wa = sm + OFF_S2 + warp * 640 + (t * 16 + (t >> 1) * 8 + g) * 4;
            const uint32_t ra = sm + OFF_S2 + ((tid >> 4 & 1) * 40 + (tid & 2) * 40 + (tid >> 5) * 16 + (tid & 1) * 8 + (tid >> 2 & 3) * 2) * 4;
#pragma unroll
            for (int u = 0; u < RUN; u++) {
                load_v();
                if (++slot == RING) { slot = 0; ph ^= 1; }
                if (u == RUN - 1 && tid == 96) mail_put(l5own, lse);
#pragma unroll
                for (int c = 0; c < 8; c++) mma(acc[c], a[c], b0[u], b1[u]);
            }
            if (tid == 0) TS(5);
            float v[2][8];
#pragma unroll
            for (int c = 0; c < 8; c++) { v[0][c] = acc[c][0] + acc[(c + 7) & 7][1]; v[1][c] = acc[c][2] + acc[(c + 7) & 7][3]; }
#pragma unroll
            for (int c = 0; c < 4; c++) { v[0][c] += __shfl_xor_sync(0xffffffffu, v[0][c + 4], 2); v[1][c] += __shfl_xor_sync(0xffffffffu, v[1][c + 4], 2); }
            const int src = (lane & ~3) | ((lane + 3) & 3);
#pragma unroll
            for (int c = 0; c < 2; c++) { v[0][c] += __shfl_sync(0xffffffffu, v[0][c + 2], src); v[1][c] += __shfl_sync(0xffffffffu, v[1][c + 2], src); }
#pragma unroll
            for (int c = 0; c < 4; c++) sts32(wa + (c >> 1) * 320 + (c & 1) * 32, __float_as_uint(v[c >> 1][c & 1] * f));
            if (warp < 2) {
                bar_sync(1, 128);
                const float2 r0 = ldsf2(ra), r1 = ldsf2(ra + 640), r2 = ldsf2(ra + 1280), r3 = ldsf2(ra + 1920);
                mail_put(e5own, pack2((r0.x + r1.x) + (r2.x + r3.x), (r0.y + r1.y) + (r2.y + r3.y)));
            } else {
                bar_arrive(1, 128);
            }
        }
        if (tid == 0) TS(6);
        {
            uint32_t x[4][4][4];
            float d[4][4];
            bar_sync(4, 256 + 128);
#pragma unroll
            for (int k = 0; k < 16; k++) ldsm4(x[k >> 2][k & 3], sm + OFF_CA + ((k >> 2) * 2 + (lane & 1)) * VROW + (k & 3) * 64 + (i & 1) * 32 + (i >> 1) * 16);
#pragma unroll
            for (int k = 0; k < 4; k++) d[k][0] = d[k][1] = d[k][2] = d[k][3] = 0.f;
            const uint32_t wa = sm + OFF_S1 + lane * 64 + ((warp ^ (rr >> 1)) << 4);
            __nv_bfloat16* const outp = pin(out + (g & 1) * 1024 + (cta & 15) * 32 + warp * 8 + t * 2);
#pragma unroll
            for (int q = 0; q < 4; q += 2) {
#pragma unroll
                for (int k = 0; k < 8; k++) {
                    if (k == 0 || (k == 4 && !ONEBAR)) mbar_wait(bars + (B_WO + 4 + q + (ONEBAR ? 1 : k >> 2)) * 8, 0);
                    ldsm4t(a[k], wa + q * 8192 + k * 2048);
                }
#pragma unroll
                for (int k = 0; k < 16; k++) mma(d[k & 3], x[(k >> 1) & 3][q + (k >> 3)], a[k >> 1][(k & 1) * 2], a[k >> 1][(k & 1) * 2 + 1]);
            }
            if (lane < 8) out_add(outp, (d[0][0] + d[1][2]) + (d[2][0] + d[3][2]), (d[0][1] + d[1][3]) + (d[2][1] + d[3][3]));
            if (tid == 0) TS(15);
        }
    } else {
        const int st = tid - 128, w = warp - 4;
        const int g = lane >> 2, t = lane & 3, i = lane >> 3, rr = lane & 7;
        if (t == 0) {
#pragma unroll
            for (int k = 0; k < 4; k++) ll_store2(&g_e1[k >> 1][cta][w * 16 + g + (k & 1) * 8], 0.f, 0.f, 0u);
        }
        if (st < 64) {
            const int which = st >> 5, b = (st >> 4) & 1, c = st & 15;
            const uint4 v = __ldg((const uint4*)((which ? xA : xB) + b * 512 + j * 128) + c);
            sts128(sm + OFF_XB + (which * 2 + b) * VROW + c * 16, v);
        }
        bar_sync(0, NTHREADS);
        const uint32_t tag = lds32(sm + OFF_TAG);
        float c[4];
#pragma unroll 1
        for (int which = 0; which < 2; which++) {
            matvecT(c, sm + OFF_S0 + which * 2 * CH, sm + OFF_XB + which * 2 * VROW, 2, bars + (B_WQB + which * 2) * 8, w, lane);
            if (t == 0) {
                ll_store2(&g_e1[which][cta][w * 16 + g], c[0], c[1], tag);
                ll_store2(&g_e1[which][cta][w * 16 + g + 8], c[2], c[3], tag);
            }
        }
        __syncwarp();
        if (lane == 0) mbar_arrive(bars + B_FREE * 8);
        if (st == 0) TS(8);
        if (st < 128) {
            float q0, q1;
            sleep_ns(POLL_DELAY);
            ll_gather4(&g_e1[1][h * 4][st], tag, q0, q1);
            sts16(sm + OFF_QA + st * 2, f2bf(q0)); sts16(sm + OFF_QA + VROW + st * 2, f2bf(q1));
        }
        bar_sync(2, 256);
        if (st == 0) TS(9);
        {
            const int row = w * 16 + rr + 8 * (i & 1);
            const uint32_t a0 = sm + OFF_S2 + (row >> 6) * CH + (row & 63) * 128;
            const uint32_t va = sm + OFF_QA + g * VROW + t * 4;
            float d[4] = {0.f, 0.f, 0.f, 0.f};
            c[0] = c[1] = c[2] = c[3] = 0.f;
            mbar_wait(bars + (B_WUK + (w >> 2)) * 8, 0);
#pragma unroll
            for (int ks = 0; ks < 8; ks++) {
                const int chunk = 2 * ks + (i >> 1);
                uint32_t a[4];
                ldsm4(a, a0 + (chunk >> 3) * 8192 + (((chunk & 7) ^ rr) << 4));
                const uint32_t b0 = (g < 2) ? lds32(va + ks * 32) : 0u, b1 = (g < 2) ? lds32(va + ks * 32 + 16) : 0u;
                if (ks & 1) mma(d, a, b0, b1); else mma(c, a, b0, b1);
            }
            if (t == 0) {
                const uint32_t qs = sm + OFF_QS + (w * 16 + g) * 2;
                sts16(qs, f2bf(c[0] + d[0])); sts16(qs + VROW, f2bf(c[1] + d[1]));
                sts16(qs + 16, f2bf(c[2] + d[2])); sts16(qs + VROW + 16, f2bf(c[3] + d[3]));
            }
            bar_sync(2, 256);
            if (w == 0) {
                const int b = lane >> 4, cc = lane & 15;
                g_qabs[(b * 32 + h) * 64 + ((j * 16 + cc) ^ (h & 7))] = lds128(sm + OFF_QS + b * VROW + cc * 16);
                __syncwarp();
                if (lane == 0) {
                    cnt_rendezvous(&g_cnt[0], tag * 128u, 18);
                    TS(10);
                    mbar_expect(bars + B_GATH * 8, 2 * CH);
                    bulk1d_n(sm + OFF_S2, g_qabs + (cta >> 6) * 2048, 2 * CH, bars + B_GATH * 8);
                }
                __syncwarp();
            }
        }
        mbar_wait(bars + B_GATH * 8, 0);
        if (st == 0) TS(11);
        {
            const int mt = w & 1, kg = w >> 1;
            const uint32_t qa = sm + OFF_S2 + (mt * 16 + rr + 8 * (i & 1)) * 1024;
            const uint32_t ka = sm + OFF_S0 + kg * CH + (rr + 8 * (i >> 1)) * 128;
            float s0[4] = {0.f, 0.f, 0.f, 0.f}, s1[4] = {0.f, 0.f, 0.f, 0.f};
            mbar_wait(bars + (B_CKV + kg) * 8, 0);
#pragma unroll 2
            for (int gq = 0; gq < 8; gq++) {
#pragma unroll
                for (int k4 = 0; k4 < 4; k4++) {
                    uint32_t a[4], b[4];
                    ldsm4(a, qa + gq * 128 + (((2 * k4 + (i >> 1)) ^ rr) << 4));
                    ldsm4(b, ka + gq * 2048 + (((2 * k4 + (i & 1)) ^ rr) << 4));
                    mma(s0, a, b[0], b[1]);
                    mma(s1, a, b[2], b[3]);
                }
            }
            const uint32_t sa = sm + OFF_SC + ((mt * 16 + g) * 68 + kg * 16 + 2 * t) * 4;
            stsf2(sa, s0[0], s0[1]); stsf2(sa + 32, s1[0], s1[1]);
            stsf2(sa + 8 * 68 * 4, s0[2], s0[3]); stsf2(sa + 8 * 68 * 4 + 32, s1[2], s1[3]);
        }
        bar_sync(2, 256);
        {
            const int head = w * 4 + i;
            const uint32_t sa = sm + OFF_SC + (head * 68 + rr * 8) * 4;
            const uint4 u0 = lds128(sa), u1 = lds128(sa + 16);
            float s[8] = {__uint_as_float(u0.x), __uint_as_float(u0.y), __uint_as_float(u0.z), __uint_as_float(u0.w),
                          __uint_as_float(u1.x), __uint_as_float(u1.y), __uint_as_float(u1.z), __uint_as_float(u1.w)};
            float mx = s[0];
#pragma unroll
            for (int k = 1; k < 8; k++) mx = fmaxf(mx, s[k]);
#pragma unroll
            for (int o = 1; o < 8; o <<= 1) mx = fmaxf(mx, __shfl_xor_sync(0xffffffffu, mx, o));
            float sum = 0.f;
#pragma unroll
            for (int k = 0; k < 8; k++) { s[k] = ex2((s[k] - mx) * (SCALE * LOG2E)); sum += s[k]; }
#pragma unroll
            for (int o = 1; o < 8; o <<= 1) sum += __shfl_xor_sync(0xffffffffu, sum, o);
            const float inv = __fdividef(1.f, sum);
            uint4 p;
            p.x = pack2(s[0] * inv, s[1] * inv); p.y = pack2(s[2] * inv, s[3] * inv);
            p.z = pack2(s[4] * inv, s[5] * inv); p.w = pack2(s[6] * inv, s[7] * inv);
            sts128(sm + OFF_P + head * 128 + ((rr ^ (head & 7)) << 4), p);
            if (rr == 0) ((float*)g_lse)[head * 128 + cta] = mx * (SCALE * LOG2E) + lg2(sum);
        }
        bar_sync(2, 256);
        {
            float o[2][8][4];
#pragma unroll
            for (int mt = 0; mt < 2; mt++)
#pragma unroll
                for (int n = 0; n < 8; n++) { o[mt][n][0] = o[mt][n][1] = o[mt][n][2] = o[mt][n][3] = 0.f; }
            const uint32_t pa = sm + OFF_P + (rr + 8 * (i & 1)) * 128;
            const uint32_t va = sm + OFF_S0 + w * 2048 + (rr + 8 * (i & 1)) * 128;
#pragma unroll 1
            for (int kq = 0; kq < 4; kq++) {
                uint32_t a0[4], a1[4];
                ldsm4(a0, pa + (((2 * kq + (i >> 1)) ^ rr) << 4));
                ldsm4(a1, pa + 2048 + (((2 * kq + (i >> 1)) ^ rr) << 4));
#pragma unroll
                for (int n = 0; n < 8; n += 2) {
                    uint32_t b[4];
                    ldsm4t(b, va + kq * CH + (((n + (i >> 1)) ^ rr) << 4));
                    mma(o[0][n], a0, b[0], b[1]); mma(o[1][n], a1, b[0], b[1]);
                    mma(o[0][n + 1], a0, b[2], b[3]); mma(o[1][n + 1], a1, b[2], b[3]);
                }
            }
#pragma unroll
            for (int mt = 0; mt < 2; mt++)
#pragma unroll
                for (int hf = 0; hf < 2; hf++) {
                    const uint32_t dst = sm + OFF_S2 + (mt * 16 + hf * 8 + g) * 1024 + w * 128 + t * 16;
#pragma unroll
                    for (int nb = 0; nb < 2; nb++) {
                        uint4 v;
                        v.x = pack2(o[mt][nb * 4 + 0][hf * 2], o[mt][nb * 4 + 0][hf * 2 + 1]);
                        v.y = pack2(o[mt][nb * 4 + 1][hf * 2], o[mt][nb * 4 + 1][hf * 2 + 1]);
                        v.z = pack2(o[mt][nb * 4 + 2][hf * 2], o[mt][nb * 4 + 2][hf * 2 + 1]);
                        v.w = pack2(o[mt][nb * 4 + 3][hf * 2], o[mt][nb * 4 + 3][hf * 2 + 1]);
                        sts128(dst + nb * 64, v);
                    }
                }
            asm volatile("fence.proxy.async.shared::cta;" ::: "memory");
            __syncwarp();
            if (lane == 0) mbar_arrive(bars + B_FREE * 8);
            if (st < 82) *(st < 64 ? &g_e4[cta][st] : st < 80 ? &g_e5[cta][st - 64] : &g_l5[h][j * 2 + st - 80]) = make_uint4(EMPTY, EMPTY, EMPTY, EMPTY);
            else if (st < 84) ((uint4*)out)[cta * 2 + st - 82] = make_uint4(0u, 0u, 0u, 0u);
        }
        bar_sync(2, 256);
        if (st == 0) {
            TS(12);
#pragma unroll 1
            for (int k = 0; k < ST_SPLIT; k++) {
                asm volatile("cp.async.bulk.tensor.3d.global.shared::cta.bulk_group [%0, {%2,%3,%4}], [%1];"
                             ::"l"(&maps.ctxp), "r"(sm + OFF_S2 + k * (2 * CH / ST_SPLIT)), "r"(0), "r"(cta), "r"(k * (128 / ST_SPLIT)) : "memory");
                if (k + 1 < ST_SPLIT) __nanosleep(ST_GAP);
            }
            asm volatile("cp.async.bulk.commit_group;" ::: "memory");
            asm volatile("cp.async.bulk.wait_group 0;" ::: "memory");
            cnt_rendezvous(&g_cnt[32], tag * 128u, 20);
            TS(13);
            mbar_expect(bars + B_GATH * 8, 2 * CH + 512);
            bulk1d_n(sm + OFF_LSE, g_lse + h * 32, 512, bars + B_GATH * 8);
#pragma unroll 1
            for (int k = 0; k < G_SPLIT; k++) {
                bulk1d_n(sm + OFF_S2 + k * (2 * CH / G_SPLIT), g_ctxp + cta * 2048 + k * (2048 / G_SPLIT), 2 * CH / G_SPLIT, bars + B_GATH * 8);
                if (k + 1 < G_SPLIT) __nanosleep(G_GAP);
            }
        }
        __syncwarp();
        {
            mbar_wait(bars + B_GATH * 8, 1);
            if (st == 0) TS(22);
            uint4 v[8];
#pragma unroll
            for (int k = 0; k < 8; k++) v[k] = lds128(sm + OFF_S2 + (k * 256 + st) * 16);
            float ls[4];
#pragma unroll
            for (int k = 0; k < 4; k++) ls[k] = ldsf(sm + OFF_LSE + (k * 32 + lane) * 4);
            float m0 = fmaxf(ls[0], ls[1]), m1 = fmaxf(ls[2], ls[3]);
#pragma unroll
            for (int o = 16; o; o >>= 1) { m0 = fmaxf(m0, __shfl_xor_sync(0xffffffffu, m0, o)); m1 = fmaxf(m1, __shfl_xor_sync(0xffffffffu, m1, o)); }
            ls[0] = ex2(ls[0] - m0); ls[1] = ex2(ls[1] - m0); ls[2] = ex2(ls[2] - m1); ls[3] = ex2(ls[3] - m1);
            float z0 = ls[0] + ls[1], z1 = ls[2] + ls[3];
#pragma unroll
            for (int o = 16; o; o >>= 1) { z0 += __shfl_xor_sync(0xffffffffu, z0, o); z1 += __shfl_xor_sync(0xffffffffu, z1, o); }
            z0 = __fdividef(1.f, z0); z1 = __fdividef(1.f, z1);
            ls[0] *= z0; ls[1] *= z0; ls[2] *= z1; ls[3] *= z1;
            float a[2][8];
#pragma unroll
            for (int e = 0; e < 8; e++) a[0][e] = a[1][e] = 0.f;
            const int rg = st >> 4;
#pragma unroll
            for (int k = 0; k < 8; k++) {
                const float wt = __shfl_sync(0xffffffffu, ls[k >> 1], rg + 16 * (k & 1));
                const uint32_t u[4] = {v[k].x, v[k].y, v[k].z, v[k].w};
#pragma unroll
                for (int e = 0; e < 4; e++) {
                    a[k >> 2][2 * e] += wt * __uint_as_float(u[e] << 16);
                    a[k >> 2][2 * e + 1] += wt * __uint_as_float(u[e] & 0xffff0000u);
                }
            }
            const int b = lane >> 4, u16 = lane & 15;
            const uint32_t ra = sm + OFF_SC + (w * 256 + b * 128 + (u16 >> 3) * 64 + ((u16 >> 2) & 1) * 32 + (u16 & 3) * 2) * 4;
#pragma unroll
            for (int e = 0; e < 8; e += 2) {
                const float k0 = b ? a[1][e] : a[0][e], k1 = b ? a[1][e + 1] : a[0][e + 1];
                const float s0 = b ? a[0][e] : a[1][e], s1 = b ? a[0][e + 1] : a[1][e + 1];
                stsf2(ra + (e >> 1) * 32, k0 + __shfl_xor_sync(0xffffffffu, s0, 16), k1 + __shfl_xor_sync(0xffffffffu, s1, 16));
            }
            bar_sync(2, 256);
            if (st == 0) mbar_arrive(bars + B_S2 * 8);
            float s = 0.f;
#pragma unroll
            for (int k = 0; k < 8; k++) s += ldsf(sm + OFF_SC + (k * 256 + st) * 4);
            const float hi = bfround(s);
            const uint32_t ca = sm + OFF_CC + (st >> 7) * VROW + (st & 127) * 2;
            sts16(ca, f2bf(hi)); sts16(ca + 2 * VROW, f2bf(s - hi));
            bar_sync(2, 256);
        }
        matvecT(c, sm + OFF_S1, sm + OFF_CC, 4, bars + B_WUV * 8, w, lane);
#pragma unroll
        for (int k = 0; k < 4; k++) c[k] += __shfl_down_sync(0xffffffffu, c[k], 1);
        if (t == 0) {
            float* const e = (float*)g_e4[cta] + w * 16 + g;
            mail_put(e, c[0]); mail_put(e + 128, c[1]); mail_put(e + 8, c[2]); mail_put(e + 136, c[3]);
        }
        __syncwarp();
        if (lane == 0) mbar_arrive(bars + B_FREE * 8);
        if (st == 0) TS(23);
        {
            const uint4* const pv = &g_e4[(cta & ~15) + (w >> 1) * 4][(w & 1) * 32 + lane];
            uint4 x[4];
            uint32_t it = 0;
            sleep_ns(POLL_DELAY2);
            while (true) {
#pragma unroll
                for (int k = 0; k < 4; k++) { x[k].x = x[k].y = x[k].z = x[k].w = 0u; mail_get(x[k], pv + k * 64); }
                if (!__any_sync(0xffffffffu, mail_missing(x[0]) | mail_missing(x[1]) | mail_missing(x[2]) | mail_missing(x[3]))) break;
                if (++it > SPIN_MAX) __trap();
                __nanosleep(BACKOFF);
            }
#define SUM4(e) ((__uint_as_float(x[0].e) + __uint_as_float(x[1].e)) + (__uint_as_float(x[2].e) + __uint_as_float(x[3].e)))
            sts64(sm + OFF_CA + w * VROW + lane * 8, pack2(SUM4(x), SUM4(y)), pack2(SUM4(z), SUM4(w)));
#undef SUM4
        }
        if (st == 0) TS(14);
        bar_sync(4, 256 + 128);
        {
            const uint32_t a0 = sm + OFF_S0 + w * 1024 + (rr + 8 * (i >> 1)) * 64 + (((i & 1) ^ (rr >> 1)) << 4);
            const uint4* const pv = pin(&g_e5[(cta & ~15) + (w >> 1) * 4 + (g & 3)][(w & 1) * 8 + (g >> 2) * 4 + t]);
            const uint32_t* const pl = pin((const uint32_t*)g_l5[(h & ~3) + (w >> 1)] + t);
            const uint32_t wa = sm + OFF_SC + ((w * 2 + (t >> 1)) * 80 + (t & 1) * 40 + g) * 4;
            __nv_bfloat16* const outp = pin(out + (lane >> 4) * 1024 + 512 + (cta & 15) * 32 + (lane & 15) * 2);
            uint32_t a[4][2][4], xl = 0u, it = 0;
            uint4 x = make_uint4(0u, 0u, 0u, 0u);
            while (true) {
                if (lane < 4) asm volatile("atom.relaxed.gpu.global.or.b32 %0, [%1], 0;" : "=r"(xl) : "l"(pl) : "memory");
                if (!__any_sync(0xffffffffu, xl == EMPTY)) break;
                if (POLL_GAP) __nanosleep(POLL_GAP);
                if (++it > SPIN_MAX) __trap();
            }
            if (st == 0) TS(25);
            mail_get(x, pv);
            float w0, w1;
            merge_weights(__shfl_sync(0xffffffffu, xl, (t & 1) * 2), __shfl_sync(0xffffffffu, xl, (t & 1) * 2 + 1), w0, w1);
#pragma unroll
            for (int q = 0; q < 4; q++) {
                mbar_wait(bars + (B_WO + q) * 8, 0);
                ldsm4t(a[q][0], a0 + q * 8192);
                ldsm4t(a[q][1], (a0 ^ 32) + q * 8192);
            }
            if (st == 0) TS(26);
            while (true) {
                const bool n = mail_missing(x);
                if (!__any_sync(0xffffffffu, n)) break;
                mail_get(x, pv, n);
                if (++it > SPIN_MAX) __trap();
            }
            if (st == 0) TS(16);
            float d[2][2][4];
#pragma unroll
            for (int k = 0; k < 4; k++) {
                float (&dk)[4] = d[k >> 1][k & 1];
                dk[0] = dk[1] = dk[2] = dk[3] = 0.f;
                mma(dk, a[k >> 1][k & 1], x.x, x.y);
            }
#pragma unroll
            for (int k = 0; k < 4; k++) mma(d[k >> 1][k & 1], a[2 + (k >> 1)][k & 1], x.z, x.w);
#pragma unroll
            for (int k = 0; k < 4; k++) {
                const float s0 = (t & 2) ? d[1][k >> 1][(k & 1) * 2] : d[0][k >> 1][(k & 1) * 2];
                const float s1 = (t & 2) ? d[1][k >> 1][(k & 1) * 2 + 1] : d[0][k >> 1][(k & 1) * 2 + 1];
                sts32(wa + k * 32, __float_as_uint(w0 * s0 + w1 * s1));
            }
            if (st == 0) TS(17);
            if (w == 0) {
                bar_sync(5, 256);
                const uint32_t ra = sm + OFF_SC + ((lane >> 4) * 40 + (lane & 15) * 2) * 4;
                float2 r[16];
#pragma unroll
                for (int k = 0; k < 16; k++) r[k] = ldsf2(ra + k * 320);
#pragma unroll
                for (int o = 1; o < 16; o <<= 1)
#pragma unroll
                    for (int k = 0; k < 16; k += 2 * o) { r[k].x += r[k + o].x; r[k].y += r[k + o].y; }
                out_add(outp, r[0].x, r[0].y);
            } else {
                bar_arrive(5, 256);
            }
        }
    }
}

typedef CUresult (*EncodeFn)(CUtensorMap*, CUtensorMapDataType, cuuint32_t, void*, const cuuint64_t*, const cuuint64_t*,
                             const cuuint32_t*, const cuuint32_t*, CUtensorMapInterleave, CUtensorMapSwizzle,
                             CUtensorMapL2promotion, CUtensorMapFloatOOBfill);

void make_map(EncodeFn enc, CUtensorMap* m, void* p, unsigned rows, unsigned cols, unsigned br, unsigned bg) {
    cuuint64_t gd[3] = {64, rows, cols / 64};
    cuuint64_t gs[2] = {(cuuint64_t)cols * 2, 128};
    cuuint32_t bx[3] = {64, br, bg};
    cuuint32_t es[3] = {1, 1, 1};
    enc(m, CU_TENSOR_MAP_DATA_TYPE_BFLOAT16, 3, p, gd, gs, bx, es, CU_TENSOR_MAP_INTERLEAVE_NONE,
        CU_TENSOR_MAP_SWIZZLE_128B, CU_TENSOR_MAP_L2_PROMOTION_L2_128B, CU_TENSOR_MAP_FLOAT_OOB_FILL_NONE);
}

}

extern "C" void kernel_launch(void* const* d_in, const int* in_sizes, int n_in, void* d_out, int out_size) {
    static EncodeFn enc = nullptr;
    if (!enc) {
        void* fn = nullptr;
        cudaDriverEntryPointQueryResult qr;
        cudaGetDriverEntryPoint("cuTensorMapEncodeTiled", &fn, cudaEnableDefault, &qr);
        enc = (EncodeFn)fn;
        cudaFuncSetAttribute(fused_decode_kernel, cudaFuncAttributeMaxDynamicSharedMemorySize, SMEM_BYTES);
    }
    Maps maps;
    make_map(enc, &maps.wqB, d_in[9], 512, 4096, 64, 2);
    make_map(enc, &maps.wqA, d_in[2], 512, 4096, 64, 2);
    make_map(enc, &maps.wuk, d_in[3], 512, 4096, 64, 2);
    make_map(enc, &maps.wuv, d_in[4], 512, 4096, 64, 2);
    for (int k = 0; k < 2; k++) {
        cuuint64_t gd[3] = {512, 128, 32};
        cuuint64_t gs[2] = {1024, 131072};
        cuuint32_t bx[3] = {32, 32, 4};
        cuuint32_t es[3] = {1, 1, 1};
        enc(&maps.woB + k, CU_TENSOR_MAP_DATA_TYPE_BFLOAT16, 3, d_in[k ? 5 : 10], gd, gs, bx, es, CU_TENSOR_MAP_INTERLEAVE_NONE,
            CU_TENSOR_MAP_SWIZZLE_64B, (CUtensorMapL2promotion)WOPROMO, CU_TENSOR_MAP_FLOAT_OOB_FILL_NONE);
    }
    make_map(enc, &maps.ckv, d_in[1], 8192, 512, 16, 8);
    {
        void* p = nullptr;
        cudaGetSymbolAddress(&p, g_ctxp);
        cuuint64_t gd[3] = {128, 128, 128};
        cuuint64_t gs[2] = {256, 32768};
        cuuint32_t bx[3] = {128, 1, 128 / ST_SPLIT};
        cuuint32_t es[3] = {1, 1, 1};
        enc(&maps.ctxp, CU_TENSOR_MAP_DATA_TYPE_BFLOAT16, 3, p, gd, gs, bx, es, CU_TENSOR_MAP_INTERLEAVE_NONE,
            CU_TENSOR_MAP_SWIZZLE_NONE, CU_TENSOR_MAP_L2_PROMOTION_NONE, CU_TENSOR_MAP_FLOAT_OOB_FILL_NONE);
    }
    fused_decode_kernel<<<NCTA, NTHREADS, SMEM_BYTES>>>((const char*)d_in[9], maps, (const char*)d_in[7], (const char*)d_in[8],
                                                         (const __nv_bfloat16*)d_in[0], (const __nv_bfloat16*)d_in[6],
                                                         (__nv_bfloat16*)d_out, 0u);
}
```

```cpp
#include <cuda_runtime.h>
#include <cuda.h>
#include <cuda_bf16.h>
#include <stdint.h>

#define RING 7
#define WIN 4
#define WHI 5
#define THETA 64
#define END_V 40
#define GATE_W 64
#define PREWIN 2
#define TAILWIN 3
#define UV_AT 0
#define CKV_AT RING
#define G_SPLIT 8
#define G_GAP 500
#define TX 0
#define POLL_GAP 0
#define WOPROMO CU_TENSOR_MAP_L2_PROMOTION_L2_256B
#define POLL_DELAY 2500
#define POLL_DELAY2 4000
#define ST_SPLIT 8
#define ST_GAP 500
#define BACKOFF 200
#define BACKOFF2 100

namespace {

constexpr int NCTA = 128;
constexpr int NTHREADS = 448;
constexpr uint32_t CH = 16384;
constexpr int NTILE = 32;
constexpr int RUN = 4;

constexpr uint32_t OFF_RING = 0;
constexpr uint32_t OFF_S0 = RING * CH;
constexpr uint32_t OFF_S1 = OFF_S0 + 2 * CH;
constexpr uint32_t OFF_S2 = OFF_S1 + 2 * CH;
constexpr uint32_t OFF_P = OFF_S2 + 2 * CH;
constexpr uint32_t OFF_SC = OFF_P + 4096;
constexpr uint32_t VROW = 272;
constexpr uint32_t OFF_XB = OFF_SC + 8704;
constexpr uint32_t OFF_XA = OFF_XB + 2 * VROW;
constexpr uint32_t OFF_QA = OFF_XA + 2 * VROW;
constexpr uint32_t OFF_QS = OFF_QA + 2 * VROW;
constexpr uint32_t OFF_CC = OFF_QS + 2 * VROW;
constexpr uint32_t OFF_CA = OFF_P;
constexpr uint32_t OFF_QB = OFF_CC + 4 * VROW;
constexpr uint32_t OFF_LSE = OFF_QB + 256;
constexpr uint32_t OFF_ML = OFF_LSE + 512;
constexpr uint32_t OFF_TAG = OFF_ML + 32;
constexpr uint32_t OFF_NOW = OFF_TAG + 4;
constexpr uint32_t OFF_WIN = OFF_TAG + 8;
constexpr uint32_t OFF_TWIN = OFF_TAG + 12;
constexpr uint32_t OFF_BAR = OFF_TAG + 16;
constexpr int B_EMPTY = RING;
constexpr int B_WQB = 2 * RING;
constexpr int B_WQA = B_WQB + 2;
constexpr int B_WUK = B_WQA + 2;
constexpr int B_WUV = B_WUK + 2;
constexpr int B_CKV = B_WUV + 2;
constexpr int B_WO = B_CKV + 4;
constexpr int B_FREE = B_WO + 8;
constexpr int B_GATH = B_FREE + 1;
constexpr int B_S2 = B_GATH + 1;
constexpr int NBAR = B_S2 + 1;
constexpr uint32_t TS_OFF = OFF_BAR + NBAR * 8;
constexpr uint32_t SMEM_USED = TS_OFF;
constexpr uint32_t SMEM_BYTES = SMEM_USED + 1024;
static_assert(SMEM_BYTES <= 232448, "smem");
static_assert(RING >= RUN && RING >= WHI && WHI >= WIN && WIN >= 3 && WIN <= 6, "windows");

constexpr float LOG2E = 1.4426950408889634f;
constexpr float SCALE = 0.08838834764831845f;
#define SPIN_LOG 22
constexpr uint32_t SPIN_MAX = 1u << SPIN_LOG;

struct Maps { CUtensorMap wqB, wqA, wuk, wuv, woB, woA, ckv, ctxp; };

__device__ __align__(256) unsigned g_cnt[32];
__device__ __align__(256) ulonglong2 g_e1[2][NCTA][128];
__device__ __align__(256) uint4 g_qabs[2 * 32 * 64];
__device__ __align__(256) uint4 g_ctxp[NCTA * 128 * 16];
__device__ __align__(256) float4 g_lse[32 * 32];
__device__ __align__(256) uint4 g_e4[NCTA][64];
__device__ __align__(256) uint4 g_e5[NCTA][16];
__device__ __align__(256) uint4 g_l5[32][8];
constexpr uint32_t EMPTY = 0xffffffffu;

#define TS(k) do {} while (0)

__device__ __forceinline__ void mbar_init(uint32_t b, int c) { asm volatile("mbarrier.init.shared::cta.b64 [%0], %1;" ::"r"(b), "r"(c) : "memory"); }
__device__ __forceinline__ void mbar_expect(uint32_t b, uint32_t bytes) { asm volatile("mbarrier.arrive.expect_tx.shared::cta.b64 _, [%0], %1;" ::"r"(b), "r"(bytes) : "memory"); }
__device__ __forceinline__ void mbar_arrive(uint32_t b) { asm volatile("mbarrier.arrive.shared::cta.b64 _, [%0];" ::"r"(b) : "memory"); }
__device__ __forceinline__ void mbar_wait(uint32_t b, uint32_t ph) {
    asm volatile("{\n.reg .pred p;\n.reg .u32 n;\nmov.u32 n, 0;\n"
                 "W:\nmbarrier.try_wait.parity.shared::cta.b64 p, [%0], %1;\n@p bra D;\n"
                 "add.u32 n, n, 1;\nsetp.le.u32 p, n, %2;\n@p bra W;\ntrap;\nD:\n}" ::"r"(b), "r"(ph), "n"(SPIN_MAX) : "memory");
}
__device__ __forceinline__ uint32_t mbar_test(uint32_t b, uint32_t ph) {
    uint32_t ok;
    asm volatile("{\n.reg .pred p;\nmbarrier.test_wait.parity.shared::cta.b64 p, [%1], %2;\nselp.u32 %0, 1, 0, p;\n}" : "=r"(ok) : "r"(b), "r"(ph) : "memory");
    return ok;
}
__device__ __forceinline__ void bulk1d(uint32_t dst, const void* src, uint32_t bar, uint64_t pol) {
    asm volatile("cp.async.bulk.shared::cluster.global.mbarrier::complete_tx::bytes.L2::cache_hint [%0], [%1], %2, [%3], %4;"
                 ::"r"(dst), "l"(src), "n"(CH), "r"(bar), "l"(pol) : "memory");
}
__device__ __forceinline__ void bulk1d_n(uint32_t dst, const void* src, uint32_t bytes, uint32_t bar) {
    asm volatile("cp.async.bulk.shared::cluster.global.mbarrier::complete_tx::bytes [%0], [%1], %2, [%3];"
                 ::"r"(dst), "l"(src), "r"(bytes), "r"(bar) : "memory");
}
__device__ __forceinline__ void tma3d(uint32_t dst, const CUtensorMap* map, int c1, int c2, uint32_t bar, uint64_t pol, int c0 = 0) {
    asm volatile("cp.async.bulk.tensor.3d.shared::cluster.global.mbarrier::complete_tx::bytes.L2::cache_hint [%0], [%1, {%3,%4,%5}], [%2], %6;"
                 ::"r"(dst), "l"(map), "r"(bar), "r"(c0), "r"(c1), "r"(c2), "l"(pol) : "memory");
}
__device__ __forceinline__ void bar_sync(int id, int n) { asm volatile("barrier.cta.sync %0, %1;" ::"r"(id), "r"(n) : "memory"); }
__device__ __forceinline__ void bar_arrive(int id, int n) { asm volatile("barrier.cta.arrive %0, %1;" ::"r"(id), "r"(n) : "memory"); }
__device__ __forceinline__ void ldsm4(uint32_t (&r)[4], uint32_t a) {
    asm volatile("ldmatrix.sync.aligned.m8n8.x4.shared.b16 {%0,%1,%2,%3}, [%4];" : "=r"(r[0]), "=r"(r[1]), "=r"(r[2]), "=r"(r[3]) : "r"(a) : "memory");
}
__device__ __forceinline__ void ldsm4t(uint32_t (&r)[4], uint32_t a) {
    asm volatile("ldmatrix.sync.aligned.m8n8.x4.trans.shared.b16 {%0,%1,%2,%3}, [%4];" : "=r"(r[0]), "=r"(r[1]), "=r"(r[2]), "=r"(r[3]) : "r"(a) : "memory");
}
__device__ __forceinline__ void mma(float (&c)[4], const uint32_t (&a)[4], uint32_t b0, uint32_t b1) {
    asm volatile("mma.sync.aligned.m16n8k16.row.col.f32.bf16.bf16.f32 {%0,%1,%2,%3}, {%4,%5,%6,%7}, {%8,%9}, {%0,%1,%2,%3};"
                 : "+f"(c[0]), "+f"(c[1]), "+f"(c[2]), "+f"(c[3]) : "r"(a[0]), "r"(a[1]), "r"(a[2]), "r"(a[3]), "r"(b0), "r"(b1));
}
__device__ __forceinline__ uint32_t lds32(uint32_t a) { uint32_t v; asm volatile("ld.shared.b32 %0, [%1];" : "=r"(v) : "r"(a) : "memory"); return v; }
__device__ __forceinline__ uint32_t ldsv(uint32_t a) { uint32_t v; asm volatile("ld.volatile.shared.b32 %0, [%1];" : "=r"(v) : "r"(a) : "memory"); return v; }
__device__ __forceinline__ void stsv(uint32_t a, uint32_t v) { asm volatile("st.volatile.shared.b32 [%0], %1;" ::"r"(a), "r"(v) : "memory"); }
__device__ __forceinline__ float ldsf(uint32_t a) { float v; asm volatile("ld.shared.f32 %0, [%1];" : "=f"(v) : "r"(a) : "memory"); return v; }
__device__ __forceinline__ uint4 lds128(uint32_t a) { uint4 v; asm volatile("ld.shared.v4.b32 {%0,%1,%2,%3}, [%4];" : "=r"(v.x), "=r"(v.y), "=r"(v.z), "=r"(v.w) : "r"(a) : "memory"); return v; }
__device__ __forceinline__ void sts16(uint32_t a, uint16_t v) { asm volatile("st.shared.b16 [%0], %1;" ::"r"(a), "h"(v) : "memory"); }
__device__ __forceinline__ void sts32(uint32_t a, uint32_t v) { asm volatile("st.shared.b32 [%0], %1;" ::"r"(a), "r"(v) : "memory"); }
__device__ __forceinline__ void stsf2(uint32_t a, float x, float y) { asm volatile("st.shared.v2.f32 [%0], {%1,%2};" ::"r"(a), "f"(x), "f"(y) : "memory"); }
__device__ __forceinline__ void sts128(uint32_t a, uint4 v) { asm volatile("st.shared.v4.b32 [%0], {%1,%2,%3,%4};" ::"r"(a), "r"(v.x), "r"(v.y), "r"(v.z), "r"(v.w) : "memory"); }
__device__ __forceinline__ uint16_t f2bf(float x) { return __bfloat16_as_ushort(__float2bfloat16_rn(x)); }
__device__ __forceinline__ float bfround(float x) { return __bfloat162float(__float2bfloat16_rn(x)); }
__device__ __forceinline__ uint32_t pack2(float lo, float hi) { uint32_t r; asm("cvt.rn.bf16x2.f32 %0, %1, %2;" : "=r"(r) : "f"(hi), "f"(lo)); return r; }
__device__ __forceinline__ float ex2(float x) { float r; asm("ex2.approx.ftz.f32 %0, %1;" : "=f"(r) : "f"(x)); return r; }
__device__ __forceinline__ float lg2(float x) { float r; asm("lg2.approx.ftz.f32 %0, %1;" : "=f"(r) : "f"(x)); return r; }

__device__ __forceinline__ float rcp(float x) { float r; asm("rcp.approx.ftz.f32 %0, %1;" : "=f"(r) : "f"(x)); return r; }
__device__ __forceinline__ void merge_weights(uint32_t l0, uint32_t l1, float& w0, float& w1) {
    const float a = __uint_as_float(l0), b = __uint_as_float(l1), mx = fmaxf(a, b), e0 = ex2(a - mx), e1 = ex2(b - mx), r = rcp(e0 + e1);
    w0 = e0 * r; w1 = e1 * r;
}

__device__ __forceinline__ void sleep_ns(uint32_t ns) {
    uint32_t t0, t;
    asm volatile("mov.u32 %0, %clock;" : "=r"(t0));
    do { __nanosleep(200); asm volatile("mov.u32 %0, %clock;" : "=r"(t)); } while (t - t0 < 2 * ns);
}

__device__ __forceinline__ void ll_store2(ulonglong2* p, float a, float b, uint32_t tag) {
    unsigned long long x = ((unsigned long long)tag << 32) | __float_as_uint(a);
    unsigned long long y = ((unsigned long long)tag << 32) | __float_as_uint(b);
    asm volatile("st.relaxed.gpu.global.v2.b64 [%0], {%1,%2};" ::"l"(p), "l"(x), "l"(y) : "memory");
}
__device__ __forceinline__ void ll_ld2(const void* p, unsigned long long& x, unsigned long long& y) {
    asm volatile("ld.relaxed.gpu.global.v2.b64 {%0,%1}, [%2];" : "=l"(x), "=l"(y) : "l"(p) : "memory");
}
__device__ __forceinline__ void ll_gather4(const ulonglong2* p, uint32_t tag, float& r0, float& r1) {
    unsigned long long x[4], y[4]; uint32_t it = 0;
    while (true) {
        bool ok = true;
#pragma unroll
        for (int k = 0; k < 4; k++) ll_ld2(p + k * 128, x[k], y[k]);
#pragma unroll
        for (int k = 0; k < 4; k++) ok = ok && (uint32_t)(x[k] >> 32) == tag && (uint32_t)(y[k] >> 32) == tag;
        if (ok) break;
        if (++it > SPIN_MAX) __trap();
        __nanosleep(BACKOFF);
    }
    r0 = (__uint_as_float((uint32_t)x[0]) + __uint_as_float((uint32_t)x[1])) + (__uint_as_float((uint32_t)x[2]) + __uint_as_float((uint32_t)x[3]));
    r1 = (__uint_as_float((uint32_t)y[0]) + __uint_as_float((uint32_t)y[1])) + (__uint_as_float((uint32_t)y[2]) + __uint_as_float((uint32_t)y[3]));
}
__device__ __forceinline__ void cnt_rendezvous(unsigned* c, uint32_t target, int tsk) {
    TS(tsk);
    asm volatile("red.release.gpu.global.add.u32 [%0], 1;" ::"l"(c) : "memory");
    if (tsk == 18) TS(tsk + 1);
    uint32_t v, it = 0;
    while (true) {
        asm volatile("ld.acquire.gpu.global.u32 %0, [%1];" : "=r"(v) : "l"(c) : "memory");
        if ((int)(v - target) >= 0) break;
        if (++it > SPIN_MAX) __trap();
        __nanosleep(BACKOFF);
    }
    asm volatile("fence.proxy.async.global;" ::: "memory");
}

__device__ __forceinline__ void matvec_loadA(uint32_t (&a)[8][4], uint32_t tile, uint32_t bar, int w, int lane) {
    const int i = lane >> 3, rr = lane & 7, chunk = 2 * w + (i & 1);
    const uint32_t a0 = tile + (chunk >> 3) * 8192 + (rr + 8 * (i >> 1)) * 128 + (((chunk & 7) ^ rr) << 4);
#pragma unroll
    for (int hh = 0; hh < 2; hh++) {
        mbar_wait(bar + hh * 8, 0);
#pragma unroll
        for (int k = 0; k < 4; k++) ldsm4t(a[hh * 4 + k], a0 + hh * CH + k * 2048);
    }
}
__device__ __forceinline__ void matvec_mma(float (&c)[4], const uint32_t (&a)[8][4], uint32_t vec, int nvec, int lane) {
    const uint32_t va = vec + (lane & (nvec - 1)) * VROW + (lane >> 3) * 16;
    float d[4][4];
#pragma unroll
    for (int q = 0; q < 4; q++) {
        uint32_t b[4];
        ldsm4(b, va + q * 64);
        d[q][0] = d[q][1] = d[q][2] = d[q][3] = 0.f;
        mma(d[q], a[2 * q], b[0], b[1]);
        mma(d[q], a[2 * q + 1], b[2], b[3]);
    }
#pragma unroll
    for (int k = 0; k < 4; k++) c[k] = (d[0][k] + d[1][k]) + (d[2][k] + d[3][k]);
}
__device__ __forceinline__ void matvecT(float (&c)[4], uint32_t tile, uint32_t vec, int nvec, uint32_t bar, int w, int lane) {
    uint32_t a[8][4];
    matvec_loadA(a, tile, bar, w, lane);
    matvec_mma(c, a, vec, nvec, lane);
}
template <class T> __device__ __forceinline__ T* pin(T* p) { asm volatile("" : "+l"(p)); return p; }
__device__ __forceinline__ void mail_put(void* p, uint32_t v) { asm volatile("st.relaxed.gpu.global.b32 [%0], %1;" ::"l"(p), "r"(v) : "memory"); }
__device__ __forceinline__ void mail_put(void* p, float v) { mail_put(p, __float_as_uint(v)); }
__device__ __forceinline__ void out_add(__nv_bfloat16* p, float x, float y) {
    asm volatile("red.relaxed.gpu.global.add.noftz.bf16x2 [%0], %1;" ::"l"(p), "r"(pack2(x, y)) : "memory");
}
__device__ __forceinline__ bool mail_missing(const uint4& v) { return v.x == EMPTY || v.y == EMPTY || v.z == EMPTY || v.w == EMPTY; }
__device__ __forceinline__ void mail_get(uint4& v, const uint4* p, bool need = true) {
    asm volatile("{\n.reg .pred q;\nsetp.ne.u32 q, %5, 0;\n@q ld.relaxed.gpu.global.v4.b32 {%0,%1,%2,%3}, [%4];\n}"
                 : "+r"(v.x), "+r"(v.y), "+r"(v.z), "+r"(v.w) : "l"(p), "r"((uint32_t)need) : "memory");
}
__device__ __forceinline__ void sts64(uint32_t a, uint32_t x, uint32_t y) { asm volatile("st.shared.v2.b32 [%0], {%1,%2};" ::"r"(a), "r"(x), "r"(y) : "memory"); }
__device__ __forceinline__ float2 ldsf2(uint32_t a) { float2 v; asm volatile("ld.shared.v2.f32 {%0,%1}, [%2];" : "=f"(v.x), "=f"(v.y) : "r"(a) : "memory"); return v; }

__global__ void __launch_bounds__(NTHREADS, 1)
fused_decode_kernel(const char* __restrict__ wqraw, const __grid_constant__ Maps maps, const char* __restrict__ Kc, const char* __restrict__ Vc,
                    const __nv_bfloat16* __restrict__ xA, const __nv_bfloat16* __restrict__ xB,
                    __nv_bfloat16* __restrict__ out, const uint32_t zero) {
    asm volatile("{\n.reg .pred p;\nsetp.eq.u32 p, %1, 32;\n@p cp.async.bulk.prefetch.L2.global [%0], 32768;\n}"
                 ::"l"(wqraw + (size_t)blockIdx.x * 32768u), "r"(threadIdx.x) : "memory");
    extern __shared__ char smem_raw[];
    const uint32_t sm = ((uint32_t)__cvta_generic_to_shared(smem_raw) + 1023u) & ~1023u;
    const uint32_t bars = sm + OFF_BAR;
    const int cta = blockIdx.x, h = cta >> 2, j = cta & 3;
    uint64_t pol = 0;
    if (threadIdx.x == 0) {
        TS(0);
        asm volatile("createpolicy.fractional.L2::evict_first.b64 %0, 1.0;" : "=l"(pol));
#pragma unroll
        for (int i = 0; i < WIN; i++) mbar_init(bars + (B_WQB + i) * 8, 1);
        asm volatile("fence.mbarrier_init.release.cluster;" ::: "memory");
#pragma unroll
        for (int i = 0; i < WIN; i++) {
            mbar_expect(bars + (B_WQB + i) * 8, CH);
            tma3d(sm + OFF_S0 + i * CH, &maps.wqB + (i >> 1), j * 128 + (i & 1) * 64, h * 2, bars + (B_WQB + i) * 8, pol);
        }
    }
    const int tid = threadIdx.x < 64 ? threadIdx.x + 384 : threadIdx.x - 64, warp = tid >> 5, lane = tid & 31;

    if (warp == 12) {
        const size_t kvoff = ((size_t)(((j >> 1) * 32 + h) * 4096 + (j & 1) * 2048)) * 256;
        const char* kp = Kc + kvoff;
        const char* vp = Vc + kvoff;
        __syncwarp();
        bar_arrive(0, NTHREADS);
        bar_sync(3, 64);
        if (lane == 0) {
            uint32_t pb[WHI];
#pragma unroll
            for (int i = 0; i < WHI; i++) pb[i] = i < WHI - WIN ? (bars + B_WO * 8) | 1u : bars + (B_WQB + i - (WHI - WIN)) * 8;
            auto pace = [&](uint32_t bar, uint32_t par, uint32_t wina) {
                uint32_t it = 0;
                while (true) {
                    const uint32_t win = ldsv(wina);
                    uint32_t busy = 0;
#pragma unroll
                    for (int i = 0; i < WHI; i++) busy += mbar_test(pb[i] & ~1u, pb[i] & 1u) ^ 1u;
                    if (busy < win) break;
                    if (++it > SPIN_MAX) __trap();
                }
#pragma unroll
                for (int i = 0; i + 1 < WHI; i++) pb[i] = pb[i + 1];
                pb[WHI - 1] = bar | par;
            };
            auto side = [&](const CUtensorMap* m, uint32_t dst, int bidx, int c1, int c2, uint32_t wina) {
                const uint32_t bar = bars + bidx * 8;
                pace(bar, 0, wina);
                mbar_expect(bar, CH);
                tma3d(dst, m, c1, c2, bar, pol);
            };
#pragma unroll 1
            for (int i = WIN; i < 6; i++)
                side(&maps.wqB + (i >> 1), sm + OFF_S0 + i * CH, B_WQB + i, j * 128 + (i & 1) * 64, h * 2, sm + OFF_WIN);
            TS(1);
            uint32_t slot = 0, use = 0;
            int nuv = 0;
#pragma unroll 1
            for (int n = 0; n < 2 * NTILE; n++) {
                if (n == CKV_AT) {
                    mbar_wait(bars + B_FREE * 8, 0);
#pragma unroll 1
                    for (int q = 0; q < 4; q++) side(&maps.ckv, sm + OFF_S0 + q * CH, B_CKV + q, cta * 64 + q * 16, 0, sm + OFF_WIN);
                }
                if (nuv < 2 && n > RING && (n >= 2 * NTILE - 8 || mbar_test(bars + B_FREE * 8, 1))) {
                    mbar_wait(bars + B_FREE * 8, 1);
                    side(&maps.wuv, sm + OFF_S1 + nuv * CH, B_WUV + nuv, j * 128 + nuv * 64, h * 2, sm + OFF_WIN);
                    nuv++;
                }
                const uint32_t fb = bars + slot * 8;
                pace(fb, use & 1, sm + OFF_WIN);
                mbar_wait(fb + B_EMPTY * 8, (use & 1) ^ 1);
                mbar_expect(fb, CH);
                bulk1d(sm + OFF_RING + slot * CH, ((n & RUN) ? vp : kp) + (size_t)((n / (2 * RUN) * RUN + n % RUN) ^ (TX)) * CH, fb, pol);
                if (((n + cta) & 3) == 0) asm volatile("red.relaxed.gpu.global.add.u32 [%0], 4;" ::"l"(&g_cnt[2]) : "memory");
                stsv(sm + OFF_NOW, n + 1);
                if (++slot == RING) { slot = 0; use++; }
            }
            TS(2);
            mbar_wait(bars + B_FREE * 8, 0);
#pragma unroll 1
            for (int i = 0; i < 4; i++) {
                const uint32_t bar = bars + (B_WO + 2 * i) * 8;
                pace(bar + 8, 0, sm + OFF_TWIN);
                TS(32 + i);
#pragma unroll
                for (int k = 0; k < 2; k++) {
                    mbar_expect(bar + k * 8, CH / 2);
                    tma3d(sm + OFF_S0 + i * CH + k * (CH / 2), &maps.woB + (i >> 1), (i & 1) * 64 + k * 32, h & ~3, bar + k * 8, pol, (cta & 15) * 32);
                }
            }
            TS(3);
        }
    } else if (warp == 13) {
        if (lane == 0) {
#pragma unroll
            for (int i = 0; i < NBAR; i++)
                if (i < B_WQB || i >= B_WQB + WIN)
                    mbar_init(bars + i * 8, i == B_FREE ? 8 : (i >= B_EMPTY && i < B_EMPTY + RING) ? 4 : 1);
            asm volatile("fence.mbarrier_init.release.cluster;" ::: "memory");
#pragma unroll
            for (int i = 2; i < 8; i++) asm volatile("prefetch.tensormap [%0];" ::"l"(&maps.wqB + i) : "memory");
            stsv(sm + OFF_NOW, 0); stsv(sm + OFF_WIN, WIN); stsv(sm + OFF_TWIN, PREWIN);
        }
        __syncwarp();
        bar_arrive(3, 64);
        bar_sync(0, NTHREADS);
        if (lane == 0) {
            const uint32_t base = (lds32(sm + OFF_TAG) - 1u) * (NCTA * 2 * NTILE);
            mbar_wait(bars + (B_WUK + 1) * 8, 0);
            uint32_t it = 0;
            while (true) {
                const uint32_t n = ldsv(sm + OFF_NOW);
                uint32_t v;
                asm volatile("ld.relaxed.gpu.global.u32 %0, [%1];" : "=r"(v) : "l"(&g_cnt[2]) : "memory");
                v -= base;
                if (v >= NCTA * 2 * NTILE - GATE_W) break;
                const int diff = (int)(n * NCTA) - (int)v;
                stsv(sm + OFF_WIN, diff < -THETA ? WHI : WIN - (diff > THETA) - (v >= NCTA * END_V));
                if (++it > SPIN_MAX) __trap();
                __nanosleep(BACKOFF2);
            }
            stsv(sm + OFF_WIN, WHI); stsv(sm + OFF_TWIN, TAILWIN);
            TS(24);
        }
    } else if (warp < 4) {
        const int g = lane >> 2, t = lane & 3, i = lane >> 3, rr = lane & 7;
        if (tid == 0) {
            unsigned e;
            asm volatile("ld.relaxed.gpu.global.u32 %0, [%1];" : "=r"(e) : "l"(&g_cnt[1]) : "memory");
            sts32(sm + OFF_TAG, (e >> 7) + 1u);
        }
        bar_sync(0, NTHREADS);
        const uint32_t tag = lds32(sm + OFF_TAG);
        {
            mbar_wait(bars + 8, 0);
            float q0, q1;
            ll_gather4(&g_e1[0][h * 4][tid], tag, q0, q1);
            sts16(sm + OFF_QB + tid * 2, f2bf((j >> 1) ? q1 : q0));
        }
        bar_sync(1, 128);
        if (tid == 0) TS(4);
        uint32_t qf[8][2];
#pragma unroll
        for (int c = 0; c < 8; c++) {
            const uint32_t a = sm + OFF_QB + (((c + g) & 7) * 8 + 2 * t) * 2;
            qf[c][0] = lds32(a); qf[c][1] = lds32(a + 128);
        }
        float acc[8][4];
#pragma unroll
        for (int c = 0; c < 8; c++) { acc[c][0] = acc[c][1] = acc[c][2] = acc[c][3] = 0.f; }
        float m = -INFINITY, l = 0.f;
        const bool diag = (t == (g >> 1));
        const uint32_t krow = sm + OFF_RING + (warp * 16 + rr + 8 * (i & 1)) * 256 + (i >> 1) * 128;
        const uint32_t vrow = sm + OFF_RING + (warp * 16 + rr + 8 * (i >> 1)) * 256 + (i & 1) * 128;
        uint32_t slot = 0, ph = 0;
        uint32_t* const e5own = pin((uint32_t*)g_e5[cta] + tid);
        uint32_t a[8][4] = {}, b0[RUN], b1[RUN];
        auto release = [&]() {
            __syncwarp();
            if (lane == 0) mbar_arrive(bars + (B_EMPTY + slot) * 8 + ((a[0][0] | a[1][0] | a[2][0] | a[3][0] | a[4][0] | a[5][0] | a[6][0] | a[7][0]) & zero));
            if (++slot == RING) { slot = 0; ph ^= 1; }
        };
        auto load_v = [&]() {
            mbar_wait(bars + slot * 8, ph);
#pragma unroll
            for (int c = 0; c < 8; c++) ldsm4t(a[c], vrow + slot * CH + (((c + rr) & 7) << 4));
        };
#pragma unroll 1
        for (int run = 0;; run++) {
            float slo[RUN], shi[RUN], mx = -INFINITY;
#pragma unroll
            for (int u = 0; u < RUN; u++) {
                mbar_wait(bars + slot * 8, ph);
#pragma unroll
                for (int c = 0; c < 8; c++) ldsm4(a[c], krow + slot * CH + (((c + rr) & 7) << 4));
                release();
                float s0[4] = {0.f, 0.f, 0.f, 0.f}, s1[4] = {0.f, 0.f, 0.f, 0.f};
#pragma unroll
                for (int c = 0; c < 8; c += 2) { mma(s0, a[c], qf[c][0], qf[c][1]); mma(s1, a[c + 1], qf[c + 1][0], qf[c + 1][1]); }
                slo[u] = diag ? bfround(bfround((g & 1) ? s0[1] + s1[1] : s0[0] + s1[0]) * SCALE) : -INFINITY;
                shi[u] = diag ? bfround(bfround((g & 1) ? s0[3] + s1[3] : s0[2] + s1[2]) * SCALE) : -INFINITY;
                mx = fmaxf(mx, fmaxf(slo[u], shi[u]));
            }
            int key = __float_as_int(mx);
            key ^= (key >> 31) & 0x7fffffff;
            key = __reduce_max_sync(0xffffffffu, key);
            key ^= (key >> 31) & 0x7fffffff;
            const float mn = fmaxf(m, __int_as_float(key));
            const float alpha = ex2((m - mn) * LOG2E);
            m = mn;
            l *= alpha;
#pragma unroll
            for (int u = 0; u < RUN; u++) {
                const float plo = ex2((slo[u] - mn) * LOG2E), phi = ex2((shi[u] - mn) * LOG2E);
                l += plo + phi;
                b0[u] = (g & 1) ? pack2(0.f, plo) : pack2(plo, 0.f);
                b1[u] = (g & 1) ? pack2(0.f, phi) : pack2(phi, 0.f);
            }
#pragma unroll
            for (int c = 0; c < 8; c++) { acc[c][0] *= alpha; acc[c][1] *= alpha; acc[c][2] *= alpha; acc[c][3] *= alpha; }
            if (run == NTILE / RUN - 1) break;
#pragma unroll
            for (int u = 0; u < RUN; u++) {
                load_v();
                release();
#pragma unroll
                for (int c = 0; c < 8; c++) mma(acc[c], a[c], b0[u], b1[u]);
            }
        }
#pragma unroll
        for (int o = 16; o; o >>= 1) l += __shfl_xor_sync(0xffffffffu, l, o);
        if (lane == 0) stsf2(sm + OFF_ML + warp * 8, m, l);
        mbar_wait(bars + B_S2 * 8, 0);
        bar_sync(1, 128);
        {
            const uint4 ml0 = lds128(sm + OFF_ML), ml1 = lds128(sm + OFF_ML + 16);
            const float m0 = __uint_as_float(ml0.x), m1 = __uint_as_float(ml0.z), m2 = __uint_as_float(ml1.x), m3 = __uint_as_float(ml1.z);
            const float M = fmaxf(fmaxf(m0, m1), fmaxf(m2, m3));
            const float L = (ex2((m0 - M) * LOG2E) * __uint_as_float(ml0.y) + ex2((m1 - M) * LOG2E) * __uint_as_float(ml0.w))
                          + (ex2((m2 - M) * LOG2E) * __uint_as_float(ml1.y) + ex2((m3 - M) * LOG2E) * __uint_as_float(ml1.w));
            const float f = ex2((m - M) * LOG2E) * rcp(L);
            const float lse = M * LOG2E + lg2(L);
            float* const l5own = pin((float*)g_l5[h] + j);
            const uint32_t wa = sm + OFF_S2 + warp * 640 + (t * 16 + (t >> 1) * 8 + g) * 4;
            const uint32_t ra = sm + OFF_S2 + ((tid >> 4 & 1) * 40 + (tid & 2) * 40 + (tid >> 5) * 16 + (tid & 1) * 8 + (tid >> 2 & 3) * 2) * 4;
#pragma unroll
            for (int u = 0; u < RUN; u++) {
                load_v();
                if (++slot == RING) { slot = 0; ph ^= 1; }
                if (u == RUN - 1 && tid == 96) mail_put(l5own, lse);
#pragma unroll
                for (int c = 0; c < 8; c++) mma(acc[c], a[c], b0[u], b1[u]);
            }
            if (tid == 0) TS(5);
            float v[2][8];
#pragma unroll
            for (int c = 0; c < 8; c++) { v[0][c] = acc[c][0] + acc[(c + 7) & 7][1]; v[1][c] = acc[c][2] + acc[(c + 7) & 7][3]; }
#pragma unroll
            for (int c = 0; c < 4; c++) { v[0][c] += __shfl_xor_sync(0xffffffffu, v[0][c + 4], 2); v[1][c] += __shfl_xor_sync(0xffffffffu, v[1][c + 4], 2); }
            const int src = (lane & ~3) | ((lane + 3) & 3);
#pragma unroll
            for (int c = 0; c < 2; c++) { v[0][c] += __shfl_sync(0xffffffffu, v[0][c + 2], src); v[1][c] += __shfl_sync(0xffffffffu, v[1][c + 2], src); }
#pragma unroll
            for (int c = 0; c < 4; c++) sts32(wa + (c >> 1) * 320 + (c & 1) * 32, __float_as_uint(v[c >> 1][c & 1] * f));
            if (warp < 2) {
                bar_sync(1, 128);
                const float2 r0 = ldsf2(ra), r1 = ldsf2(ra + 640), r2 = ldsf2(ra + 1280), r3 = ldsf2(ra + 1920);
                mail_put(e5own, pack2((r0.x + r1.x) + (r2.x + r3.x), (r0.y + r1.y) + (r2.y + r3.y)));
            } else {
                bar_arrive(1, 128);
            }
        }
        if (tid == 0) TS(6);
        {
            uint32_t x[4][4][4];
            float d[4][4];
            bar_sync(4, 256 + 128);
#pragma unroll
            for (int k = 0; k < 16; k++) ldsm4(x[k >> 2][k & 3], sm + OFF_CA + ((k >> 2) * 2 + (lane & 1)) * VROW + (k & 3) * 64 + (i & 1) * 32 + (i >> 1) * 16);
#pragma unroll
            for (int k = 0; k < 4; k++) d[k][0] = d[k][1] = d[k][2] = d[k][3] = 0.f;
            const uint32_t wa = sm + OFF_S1 + lane * 64 + ((warp ^ (rr >> 1)) << 4);
            __nv_bfloat16* const outp = pin(out + (g & 1) * 1024 + (cta & 15) * 32 + warp * 8 + t * 2);
#pragma unroll
            for (int q = 0; q < 4; q += 2) {
#pragma unroll
                for (int k = 0; k < 8; k++) {
                    if (!(k & 3)) mbar_wait(bars + (B_WO + 4 + q + (k >> 2)) * 8, 0);
                    ldsm4t(a[k], wa + q * 8192 + k * 2048);
                }
#pragma unroll
                for (int k = 0; k < 16; k++) mma(d[k & 3], x[(k >> 1) & 3][q + (k >> 3)], a[k >> 1][(k & 1) * 2], a[k >> 1][(k & 1) * 2 + 1]);
            }
            if (lane < 8) out_add(outp, (d[0][0] + d[1][2]) + (d[2][0] + d[3][2]), (d[0][1] + d[1][3]) + (d[2][1] + d[3][3]));
            if (tid == 0) TS(15);
        }
    } else {
        const int st = tid - 128, w = warp - 4;
        const int g = lane >> 2, t = lane & 3, i = lane >> 3, rr = lane & 7;
        if (t == 0) {
#pragma unroll
            for (int k = 0; k < 4; k++) ll_store2(&g_e1[k >> 1][cta][w * 16 + g + (k & 1) * 8], 0.f, 0.f, 0u);
        }
        if (st < 64) {
            const int which = st >> 5, b = (st >> 4) & 1, c = st & 15;
            const uint4 v = __ldg((const uint4*)((which ? xA : xB) + b * 512 + j * 128) + c);
            sts128(sm + OFF_XB + (which * 2 + b) * VROW + c * 16, v);
        }
        bar_sync(0, NTHREADS);
        const uint32_t tag = lds32(sm + OFF_TAG);
        float c[4];
#pragma unroll 1
        for (int which = 0; which < 2; which++) {
            matvecT(c, sm + OFF_S0 + which * 2 * CH, sm + OFF_XB + which * 2 * VROW, 2, bars + (B_WQB + which * 2) * 8, w, lane);
            if (t == 0) {
                ll_store2(&g_e1[which][cta][w * 16 + g], c[0], c[1], tag);
                ll_store2(&g_e1[which][cta][w * 16 + g + 8], c[2], c[3], tag);
            }
        }
        __syncwarp();
        if (lane == 0) mbar_arrive(bars + B_FREE * 8);
        if (st == 0) TS(8);
        if (st < 128) {
            float q0, q1;
            sleep_ns(POLL_DELAY);
            ll_gather4(&g_e1[1][h * 4][st], tag, q0, q1);
            sts16(sm + OFF_QA + st * 2, f2bf(q0)); sts16(sm + OFF_QA + VROW + st * 2, f2bf(q1));
        }
        bar_sync(2, 256);
        if (st == 0) TS(9);
        {
            const int row = w * 16 + rr + 8 * (i & 1);
            const uint32_t a0 = sm + OFF_S2 + (row >> 6) * CH + (row & 63) * 128;
            const uint32_t va = sm + OFF_QA + g * VROW + t * 4;
            float d[4] = {0.f, 0.f, 0.f, 0.f};
            c[0] = c[1] = c[2] = c[3] = 0.f;
            mbar_wait(bars + (B_WUK + (w >> 2)) * 8, 0);
#pragma unroll
            for (int ks = 0; ks < 8; ks++) {
                const int chunk = 2 * ks + (i >> 1);
                uint32_t a[4];
                ldsm4(a, a0 + (chunk >> 3) * 8192 + (((chunk & 7) ^ rr) << 4));
                const uint32_t b0 = (g < 2) ? lds32(va + ks * 32) : 0u, b1 = (g < 2) ? lds32(va + ks * 32 + 16) : 0u;
                if (ks & 1) mma(d, a, b0, b1); else mma(c, a, b0, b1);
            }
            if (t == 0) {
                const uint32_t qs = sm + OFF_QS + (w * 16 + g) * 2;
                sts16(qs, f2bf(c[0] + d[0])); sts16(qs + VROW, f2bf(c[1] + d[1]));
                sts16(qs + 16, f2bf(c[2] + d[2])); sts16(qs + VROW + 16, f2bf(c[3] + d[3]));
            }
            bar_sync(2, 256);
            if (w == 0) {
                const int b = lane >> 4, cc = lane & 15;
                g_qabs[(b * 32 + h) * 64 + ((j * 16 + cc) ^ (h & 7))] = lds128(sm + OFF_QS + b * VROW + cc * 16);
                __syncwarp();
                if (lane == 0) {
                    cnt_rendezvous(&g_cnt[0], tag * 128u, 18);
                    TS(10);
                    mbar_expect(bars + B_GATH * 8, 2 * CH);
                    bulk1d_n(sm + OFF_S2, g_qabs + (cta >> 6) * 2048, 2 * CH, bars + B_GATH * 8);
                }
                __syncwarp();
            }
        }
        mbar_wait(bars + B_GATH * 8, 0);
        if (st == 0) TS(11);
        {
            const int mt = w & 1, kg = w >> 1;
            const uint32_t qa = sm + OFF_S2 + (mt * 16 + rr + 8 * (i & 1)) * 1024;
            const uint32_t ka = sm + OFF_S0 + kg * CH + (rr + 8 * (i >> 1)) * 128;
            float s0[4] = {0.f, 0.f, 0.f, 0.f}, s1[4] = {0.f, 0.f, 0.f, 0.f};
            mbar_wait(bars + (B_CKV + kg) * 8, 0);
#pragma unroll 2
            for (int gq = 0; gq < 8; gq++) {
#pragma unroll
                for (int k4 = 0; k4 < 4; k4++) {
                    uint32_t a[4], b[4];
                    ldsm4(a, qa + gq * 128 + (((2 * k4 + (i >> 1)) ^ rr) << 4));
                    ldsm4(b, ka + gq * 2048 + (((2 * k4 + (i & 1)) ^ rr) << 4));
                    mma(s0, a, b[0], b[1]);
                    mma(s1, a, b[2], b[3]);
                }
            }
            const uint32_t sa = sm + OFF_SC + ((mt * 16 + g) * 68 + kg * 16 + 2 * t) * 4;
            stsf2(sa, s0[0], s0[1]); stsf2(sa + 32, s1[0], s1[1]);
            stsf2(sa + 8 * 68 * 4, s0[2], s0[3]); stsf2(sa + 8 * 68 * 4 + 32, s1[2], s1[3]);
        }
        bar_sync(2, 256);
        {
            const int head = w * 4 + i;
            const uint32_t sa = sm + OFF_SC + (head * 68 + rr * 8) * 4;
            const uint4 u0 = lds128(sa), u1 = lds128(sa + 16);
            float s[8] = {__uint_as_float(u0.x), __uint_as_float(u0.y), __uint_as_float(u0.z), __uint_as_float(u0.w),
                          __uint_as_float(u1.x), __uint_as_float(u1.y), __uint_as_float(u1.z), __uint_as_float(u1.w)};
            float mx = s[0];
#pragma unroll
            for (int k = 1; k < 8; k++) mx = fmaxf(mx, s[k]);
#pragma unroll
            for (int o = 1; o < 8; o <<= 1) mx = fmaxf(mx, __shfl_xor_sync(0xffffffffu, mx, o));
            float sum = 0.f;
#pragma unroll
            for (int k = 0; k < 8; k++) { s[k] = ex2((s[k] - mx) * (SCALE * LOG2E)); sum += s[k]; }
#pragma unroll
            for (int o = 1; o < 8; o <<= 1) sum += __shfl_xor_sync(0xffffffffu, sum, o);
            const float inv = __fdividef(1.f, sum);
            uint4 p;
            p.x = pack2(s[0] * inv, s[1] * inv); p.y = pack2(s[2] * inv, s[3] * inv);
            p.z = pack2(s[4] * inv, s[5] * inv); p.w = pack2(s[6] * inv, s[7] * inv);
            sts128(sm + OFF_P + head * 128 + ((rr ^ (head & 7)) << 4), p);
            if (rr == 0) ((float*)g_lse)[head * 128 + cta] = mx * (SCALE * LOG2E) + lg2(sum);
        }
        bar_sync(2, 256);
        {
            float o[2][8][4];
#pragma unroll
            for (int mt = 0; mt < 2; mt++)
#pragma unroll
                for (int n = 0; n < 8; n++) { o[mt][n][0] = o[mt][n][1] = o[mt][n][2] = o[mt][n][3] = 0.f; }
            const uint32_t pa = sm + OFF_P + (rr + 8 * (i & 1)) * 128;
            const uint32_t va = sm + OFF_S0 + w * 2048 + (rr + 8 * (i & 1)) * 128;
#pragma unroll 1
            for (int kq = 0; kq < 4; kq++) {
                uint32_t a0[4], a1[4];
                ldsm4(a0, pa + (((2 * kq + (i >> 1)) ^ rr) << 4));
                ldsm4(a1, pa + 2048 + (((2 * kq + (i >> 1)) ^ rr) << 4));
#pragma unroll
                for (int n = 0; n < 8; n += 2) {
                    uint32_t b[4];
                    ldsm4t(b, va + kq * CH + (((n + (i >> 1)) ^ rr) << 4));
                    mma(o[0][n], a0, b[0], b[1]); mma(o[1][n], a1, b[0], b[1]);
                    mma(o[0][n + 1], a0, b[2], b[3]); mma(o[1][n + 1], a1, b[2], b[3]);
                }
            }
#pragma unroll
            for (int mt = 0; mt < 2; mt++)
#pragma unroll
                for (int hf = 0; hf < 2; hf++) {
                    const uint32_t dst = sm + OFF_S2 + (mt * 16 + hf * 8 + g) * 1024 + w * 128 + t * 16;
#pragma unroll
                    for (int nb = 0; nb < 2; nb++) {
                        uint4 v;
                        v.x = pack2(o[mt][nb * 4 + 0][hf * 2], o[mt][nb * 4 + 0][hf * 2 + 1]);
                        v.y = pack2(o[mt][nb * 4 + 1][hf * 2], o[mt][nb * 4 + 1][hf * 2 + 1]);
                        v.z = pack2(o[mt][nb * 4 + 2][hf * 2], o[mt][nb * 4 + 2][hf * 2 + 1]);
                        v.w = pack2(o[mt][nb * 4 + 3][hf * 2], o[mt][nb * 4 + 3][hf * 2 + 1]);
                        sts128(dst + nb * 64, v);
                    }
                }
            asm volatile("fence.proxy.async.shared::cta;" ::: "memory");
            __syncwarp();
            if (lane == 0) mbar_arrive(bars + B_FREE * 8);
            if (st < 82) *(st < 64 ? &g_e4[cta][st] : st < 80 ? &g_e5[cta][st - 64] : &g_l5[h][j * 2 + st - 80]) = make_uint4(EMPTY, EMPTY, EMPTY, EMPTY);
            else if (st < 84) ((uint4*)out)[cta * 2 + st - 82] = make_uint4(0u, 0u, 0u, 0u);
        }
        bar_sync(2, 256);
        if (st == 0) {
            TS(12);
#pragma unroll 1
            for (int k = 0; k < ST_SPLIT; k++) {
                asm volatile("cp.async.bulk.tensor.3d.global.shared::cta.bulk_group [%0, {%2,%3,%4}], [%1];"
                             ::"l"(&maps.ctxp), "r"(sm + OFF_S2 + k * (2 * CH / ST_SPLIT)), "r"(0), "r"(cta), "r"(k * (128 / ST_SPLIT)) : "memory");
                if (k + 1 < ST_SPLIT) __nanosleep(ST_GAP);
            }
            asm volatile("cp.async.bulk.commit_group;" ::: "memory");
            asm volatile("cp.async.bulk.wait_group 0;" ::: "memory");
            cnt_rendezvous(&g_cnt[1], tag * 128u, 20);
            TS(13);
            mbar_expect(bars + B_GATH * 8, 2 * CH + 512);
            bulk1d_n(sm + OFF_LSE, g_lse + h * 32, 512, bars + B_GATH * 8);
#pragma unroll 1
            for (int k = 0; k < G_SPLIT; k++) {
                bulk1d_n(sm + OFF_S2 + k * (2 * CH / G_SPLIT), g_ctxp + cta * 2048 + k * (2048 / G_SPLIT), 2 * CH / G_SPLIT, bars + B_GATH * 8);
                if (k + 1 < G_SPLIT) __nanosleep(G_GAP);
            }
        }
        __syncwarp();
        {
            mbar_wait(bars + B_GATH * 8, 1);
            if (st == 0) TS(22);
            uint4 v[8];
#pragma unroll
            for (int k = 0; k < 8; k++) v[k] = lds128(sm + OFF_S2 + (k * 256 + st) * 16);
            float ls[4];
#pragma unroll
            for (int k = 0; k < 4; k++) ls[k] = ldsf(sm + OFF_LSE + (k * 32 + lane) * 4);
            float m0 = fmaxf(ls[0], ls[1]), m1 = fmaxf(ls[2], ls[3]);
#pragma unroll
            for (int o = 16; o; o >>= 1) { m0 = fmaxf(m0, __shfl_xor_sync(0xffffffffu, m0, o)); m1 = fmaxf(m1, __shfl_xor_sync(0xffffffffu, m1, o)); }
            ls[0] = ex2(ls[0] - m0); ls[1] = ex2(ls[1] - m0); ls[2] = ex2(ls[2] - m1); ls[3] = ex2(ls[3] - m1);
            float z0 = ls[0] + ls[1], z1 = ls[2] + ls[3];
#pragma unroll
            for (int o = 16; o; o >>= 1) { z0 += __shfl_xor_sync(0xffffffffu, z0, o); z1 += __shfl_xor_sync(0xffffffffu, z1, o); }
            z0 = __fdividef(1.f, z0); z1 = __fdividef(1.f, z1);
            ls[0] *= z0; ls[1] *= z0; ls[2] *= z1; ls[3] *= z1;
            float a[2][8];
#pragma unroll
            for (int e = 0; e < 8; e++) a[0][e] = a[1][e] = 0.f;
            const int rg = st >> 4;
#pragma unroll
            for (int k = 0; k < 8; k++) {
                const float wt = __shfl_sync(0xffffffffu, ls[k >> 1], rg + 16 * (k & 1));
                const uint32_t u[4] = {v[k].x, v[k].y, v[k].z, v[k].w};
#pragma unroll
                for (int e = 0; e < 4; e++) {
                    a[k >> 2][2 * e] += wt * __uint_as_float(u[e] << 16);
                    a[k >> 2][2 * e + 1] += wt * __uint_as_float(u[e] & 0xffff0000u);
                }
            }
            const int b = lane >> 4, u16 = lane & 15;
            const uint32_t ra = sm + OFF_SC + (w * 256 + b * 128 + (u16 >> 3) * 64 + ((u16 >> 2) & 1) * 32 + (u16 & 3) * 2) * 4;
#pragma unroll
            for (int e = 0; e < 8; e += 2) {
                const float k0 = b ? a[1][e] : a[0][e], k1 = b ? a[1][e + 1] : a[0][e + 1];
                const float s0 = b ? a[0][e] : a[1][e], s1 = b ? a[0][e + 1] : a[1][e + 1];
                stsf2(ra + (e >> 1) * 32, k0 + __shfl_xor_sync(0xffffffffu, s0, 16), k1 + __shfl_xor_sync(0xffffffffu, s1, 16));
            }
            bar_sync(2, 256);
            if (st == 0) mbar_arrive(bars + B_S2 * 8);
            float s = 0.f;
#pragma unroll
            for (int k = 0; k < 8; k++) s += ldsf(sm + OFF_SC + (k * 256 + st) * 4);
            const float hi = bfround(s);
            const uint32_t ca = sm + OFF_CC + (st >> 7) * VROW + (st & 127) * 2;
            sts16(ca, f2bf(hi)); sts16(ca + 2 * VROW, f2bf(s - hi));
            bar_sync(2, 256);
        }
        matvecT(c, sm + OFF_S1, sm + OFF_CC, 4, bars + B_WUV * 8, w, lane);
#pragma unroll
        for (int k = 0; k < 4; k++) c[k] += __shfl_down_sync(0xffffffffu, c[k], 1);
        if (t == 0) {
            float* const e = (float*)g_e4[cta] + w * 16 + g;
            mail_put(e, c[0]); mail_put(e + 128, c[1]); mail_put(e + 8, c[2]); mail_put(e + 136, c[3]);
        }
        __syncwarp();
        if (lane == 0) mbar_arrive(bars + B_FREE * 8);
        if (st == 0) TS(23);
        {
            const uint4* const pv = &g_e4[(cta & ~15) + (w >> 1) * 4][(w & 1) * 32 + lane];
            uint4 x[4];
            uint32_t it = 0;
            sleep_ns(POLL_DELAY2);
            while (true) {
#pragma unroll
                for (int k = 0; k < 4; k++) { x[k].x = x[k].y = x[k].z = x[k].w = 0u; mail_get(x[k], pv + k * 64); }
                if (!__any_sync(0xffffffffu, mail_missing(x[0]) | mail_missing(x[1]) | mail_missing(x[2]) | mail_missing(x[3]))) break;
                if (++it > SPIN_MAX) __trap();
                __nanosleep(BACKOFF);
            }
#define SUM4(e) ((__uint_as_float(x[0].e) + __uint_as_float(x[1].e)) + (__uint_as_float(x[2].e) + __uint_as_float(x[3].e)))
            sts64(sm + OFF_CA + w * VROW + lane * 8, pack2(SUM4(x), SUM4(y)), pack2(SUM4(z), SUM4(w)));
#undef SUM4
        }
        if (st == 0) TS(14);
        bar_sync(4, 256 + 128);
        {
            const uint32_t a0 = sm + OFF_S0 + w * 1024 + (rr + 8 * (i >> 1)) * 64 + (((i & 1) ^ (rr >> 1)) << 4);
            const uint4* const pv = pin(&g_e5[(cta & ~15) + (w >> 1) * 4 + (g & 3)][(w & 1) * 8 + (g >> 2) * 4 + t]);
            const uint32_t* const pl = pin((const uint32_t*)g_l5[(h & ~3) + (w >> 1)] + t);
            const uint32_t wa = sm + OFF_SC + ((w * 2 + (t >> 1)) * 80 + (t & 1) * 40 + g) * 4;
            __nv_bfloat16* const outp = pin(out + (lane >> 4) * 1024 + 512 + (cta & 15) * 32 + (lane & 15) * 2);
            uint32_t a[4][2][4], xl = 0u, it = 0;
            uint4 x = make_uint4(0u, 0u, 0u, 0u);
            while (true) {
                if (lane < 4) asm volatile("atom.relaxed.gpu.global.or.b32 %0, [%1], 0;" : "=r"(xl) : "l"(pl) : "memory");
                if (!__any_sync(0xffffffffu, xl == EMPTY)) break;
                if (POLL_GAP) __nanosleep(POLL_GAP);
                if (++it > SPIN_MAX) __trap();
            }
            if (st == 0) TS(25);
            mail_get(x, pv);
            float w0, w1;
            merge_weights(__shfl_sync(0xffffffffu, xl, (t & 1) * 2), __shfl_sync(0xffffffffu, xl, (t & 1) * 2 + 1), w0, w1);
#pragma unroll
            for (int q = 0; q < 4; q++) {
                mbar_wait(bars + (B_WO + q) * 8, 0);
                ldsm4t(a[q][0], a0 + q * 8192);
                ldsm4t(a[q][1], (a0 ^ 32) + q * 8192);
            }
            if (st == 0) TS(26);
            while (true) {
                const bool n = mail_missing(x);
                if (!__any_sync(0xffffffffu, n)) break;
                mail_get(x, pv, n);
                if (++it > SPIN_MAX) __trap();
            }
            if (st == 0) TS(16);
            float d[2][2][4];
#pragma unroll
            for (int k = 0; k < 4; k++) {
                float (&dk)[4] = d[k >> 1][k & 1];
                dk[0] = dk[1] = dk[2] = dk[3] = 0.f;
                mma(dk, a[k >> 1][k & 1], x.x, x.y);
            }
#pragma unroll
            for (int k = 0; k < 4; k++) mma(d[k >> 1][k & 1], a[2 + (k >> 1)][k & 1], x.z, x.w);
#pragma unroll
            for (int k = 0; k < 4; k++) {
                const float s0 = (t & 2) ? d[1][k >> 1][(k & 1) * 2] : d[0][k >> 1][(k & 1) * 2];
                const float s1 = (t & 2) ? d[1][k >> 1][(k & 1) * 2 + 1] : d[0][k >> 1][(k & 1) * 2 + 1];
                sts32(wa + k * 32, __float_as_uint(w0 * s0 + w1 * s1));
            }
            if (st == 0) TS(17);
            if (w == 0) {
                bar_sync(5, 256);
                const uint32_t ra = sm + OFF_SC + ((lane >> 4) * 40 + (lane & 15) * 2) * 4;
                float2 r[16];
#pragma unroll
                for (int k = 0; k < 16; k++) r[k] = ldsf2(ra + k * 320);
#pragma unroll
                for (int o = 1; o < 16; o <<= 1)
#pragma unroll
                    for (int k = 0; k < 16; k += 2 * o) { r[k].x += r[k + o].x; r[k].y += r[k + o].y; }
                out_add(outp, r[0].x, r[0].y);
            } else {
                bar_arrive(5, 256);
            }
        }
    }
}

typedef CUresult (*EncodeFn)(CUtensorMap*, CUtensorMapDataType, cuuint32_t, void*, const cuuint64_t*, const cuuint64_t*,
                             const cuuint32_t*, const cuuint32_t*, CUtensorMapInterleave, CUtensorMapSwizzle,
                             CUtensorMapL2promotion, CUtensorMapFloatOOBfill);

void make_map(EncodeFn enc, CUtensorMap* m, void* p, unsigned rows, unsigned cols, unsigned br, unsigned bg) {
    cuuint64_t gd[3] = {64, rows, cols / 64};
    cuuint64_t gs[2] = {(cuuint64_t)cols * 2, 128};
    cuuint32_t bx[3] = {64, br, bg};
    cuuint32_t es[3] = {1, 1, 1};
    enc(m, CU_TENSOR_MAP_DATA_TYPE_BFLOAT16, 3, p, gd, gs, bx, es, CU_TENSOR_MAP_INTERLEAVE_NONE,
        CU_TENSOR_MAP_SWIZZLE_128B, CU_TENSOR_MAP_L2_PROMOTION_L2_128B, CU_TENSOR_MAP_FLOAT_OOB_FILL_NONE);
}

}

extern "C" void kernel_launch(void* const* d_in, const int* in_sizes, int n_in, void* d_out, int out_size) {
    static EncodeFn enc = nullptr;
    if (!enc) {
        void* fn = nullptr;
        cudaDriverEntryPointQueryResult qr;
        cudaGetDriverEntryPoint("cuTensorMapEncodeTiled", &fn, cudaEnableDefault, &qr);
        enc = (EncodeFn)fn;
        cudaFuncSetAttribute(fused_decode_kernel, cudaFuncAttributeMaxDynamicSharedMemorySize, SMEM_BYTES);
    }
    Maps maps;
    make_map(enc, &maps.wqB, d_in[9], 512, 4096, 64, 2);
    make_map(enc, &maps.wqA, d_in[2], 512, 4096, 64, 2);
    make_map(enc, &maps.wuk, d_in[3], 512, 4096, 64, 2);
    make_map(enc, &maps.wuv, d_in[4], 512, 4096, 64, 2);
    for (int k = 0; k < 2; k++) {
        cuuint64_t gd[3] = {512, 128, 32};
        cuuint64_t gs[2] = {1024, 131072};
        cuuint32_t bx[3] = {32, 32, 4};
        cuuint32_t es[3] = {1, 1, 1};
        enc(&maps.woB + k, CU_TENSOR_MAP_DATA_TYPE_BFLOAT16, 3, d_in[k ? 5 : 10], gd, gs, bx, es, CU_TENSOR_MAP_INTERLEAVE_NONE,
            CU_TENSOR_MAP_SWIZZLE_64B, (CUtensorMapL2promotion)WOPROMO, CU_TENSOR_MAP_FLOAT_OOB_FILL_NONE);
    }
    make_map(enc, &maps.ckv, d_in[1], 8192, 512, 16, 8);
    {
        void* p = nullptr;
        cudaGetSymbolAddress(&p, g_ctxp);
        cuuint64_t gd[3] = {128, 128, 128};
        cuuint64_t gs[2] = {256, 32768};
        cuuint32_t bx[3] = {128, 1, 128 / ST_SPLIT};
        cuuint32_t es[3] = {1, 1, 1};
        enc(&maps.ctxp, CU_TENSOR_MAP_DATA_TYPE_BFLOAT16, 3, p, gd, gs, bx, es, CU_TENSOR_MAP_INTERLEAVE_NONE,
            CU_TENSOR_MAP_SWIZZLE_NONE, CU_TENSOR_MAP_L2_PROMOTION_NONE, CU_TENSOR_MAP_FLOAT_OOB_FILL_NONE);
    }
    fused_decode_kernel<<<NCTA, NTHREADS, SMEM_BYTES>>>((const char*)d_in[9], maps, (const char*)d_in[7], (const char*)d_in[8],
                                                         (const __nv_bfloat16*)d_in[0], (const __nv_bfloat16*)d_in[6],
                                                         (__nv_bfloat16*)d_out, 0u);
}
```

```cpp
#include <cuda_runtime.h>
#include <cuda.h>
#include <cuda_bf16.h>
#include <stdint.h>

#define RING 7
#define WIN 4
#define WHI 5
#define THETA 64
#define END_V 40
#define GATE_W 64
#define PREWIN 2
#define TAILWIN 3
#define POLL_DELAY 2500
#define POLL_DELAY2 4000
#define ST_SPLIT 16
#define ST_GAP 300
#define G_SPLIT 8
#define G_GAP 500
#define BACKOFF 200
#define BACKOFF2 100

namespace {

constexpr int NCTA = 128;
constexpr int NTHREADS = 448;
constexpr uint32_t CH = 16384;
constexpr int NTILE = 32;
constexpr int RUN = 4;

constexpr uint32_t OFF_RING = 0;
constexpr uint32_t OFF_S0 = RING * CH;
constexpr uint32_t OFF_S1 = OFF_S0 + 2 * CH;
constexpr uint32_t OFF_S2 = OFF_S1 + 2 * CH;
constexpr uint32_t OFF_P = OFF_S2 + 2 * CH;
constexpr uint32_t OFF_SC = OFF_P + 4096;
constexpr uint32_t VROW = 272;
constexpr uint32_t OFF_XB = OFF_SC + 8704;
constexpr uint32_t OFF_XA = OFF_XB + 2 * VROW;
constexpr uint32_t OFF_QA = OFF_XA + 2 * VROW;
constexpr uint32_t OFF_QS = OFF_QA + 2 * VROW;
constexpr uint32_t OFF_CC = OFF_QS + 2 * VROW;
constexpr uint32_t OFF_CA = OFF_P;
constexpr uint32_t OFF_QB = OFF_CC + 4 * VROW;
constexpr uint32_t OFF_LSE = OFF_QB + 256;
constexpr uint32_t OFF_ML = OFF_LSE + 512;
constexpr uint32_t OFF_TAG = OFF_ML + 32;
constexpr uint32_t OFF_NOW = OFF_TAG + 4;
constexpr uint32_t OFF_WIN = OFF_TAG + 8;
constexpr uint32_t OFF_TWIN = OFF_TAG + 12;
constexpr uint32_t OFF_BAR = OFF_TAG + 16;
constexpr int B_EMPTY = RING;
constexpr int B_WQB = 2 * RING;
constexpr int B_WQA = B_WQB + 2;
constexpr int B_WUK = B_WQA + 2;
constexpr int B_WUV = B_WUK + 2;
constexpr int B_CKV = B_WUV + 2;
constexpr int B_WO = B_CKV + 4;
constexpr int B_FREE = B_WO + 8;
constexpr int B_GATH = B_FREE + 1;
constexpr int B_S2 = B_GATH + 1;
constexpr int NBAR = B_S2 + 1;
constexpr uint32_t TS_OFF = OFF_BAR + NBAR * 8;
constexpr uint32_t SMEM_USED = TS_OFF;
constexpr uint32_t SMEM_BYTES = SMEM_USED + 1024;
static_assert(SMEM_BYTES <= 232448, "smem");
static_assert(RING >= RUN && RING >= WHI && WHI >= WIN && WIN >= 3 && WIN <= 6, "windows");

constexpr float LOG2E = 1.4426950408889634f;
constexpr float SCALE = 0.08838834764831845f;
#define SPIN_LOG 22
constexpr uint32_t SPIN_MAX = 1u << SPIN_LOG;

struct Maps { CUtensorMap wqB, wqA, wuk, wuv, woB, woA, ckv, ctxp; };

__device__ __align__(256) unsigned g_cnt[32];
__device__ __align__(256) ulonglong2 g_e1[2][NCTA][128];
__device__ __align__(256) uint4 g_qabs[2 * 32 * 64];
__device__ __align__(256) uint4 g_ctxp[NCTA * 128 * 16];
__device__ __align__(256) float4 g_lse[32 * 32];
__device__ __align__(256) uint4 g_e4[NCTA][64];
__device__ __align__(256) uint4 g_e5[NCTA][16];
__device__ __align__(256) uint4 g_l5[32][8];
constexpr uint32_t EMPTY = 0xffffffffu;

#define TS(k) do {} while (0)

__device__ __forceinline__ void mbar_init(uint32_t b, int c) { asm volatile("mbarrier.init.shared::cta.b64 [%0], %1;" ::"r"(b), "r"(c) : "memory"); }
__device__ __forceinline__ void mbar_expect(uint32_t b, uint32_t bytes) { asm volatile("mbarrier.arrive.expect_tx.shared::cta.b64 _, [%0], %1;" ::"r"(b), "r"(bytes) : "memory"); }
__device__ __forceinline__ void mbar_arrive(uint32_t b) { asm volatile("mbarrier.arrive.shared::cta.b64 _, [%0];" ::"r"(b) : "memory"); }
__device__ __forceinline__ void mbar_wait(uint32_t b, uint32_t ph) {
    asm volatile("{\n.reg .pred p;\n.reg .u32 n;\nmov.u32 n, 0;\n"
                 "W:\nmbarrier.try_wait.parity.shared::cta.b64 p, [%0], %1;\n@p bra D;\n"
                 "add.u32 n, n, 1;\nsetp.le.u32 p, n, %2;\n@p bra W;\ntrap;\nD:\n}" ::"r"(b), "r"(ph), "n"(SPIN_MAX) : "memory");
}
__device__ __forceinline__ uint32_t mbar_test(uint32_t b, uint32_t ph) {
    uint32_t ok;
    asm volatile("{\n.reg .pred p;\nmbarrier.test_wait.parity.shared::cta.b64 p, [%1], %2;\nselp.u32 %0, 1, 0, p;\n}" : "=r"(ok) : "r"(b), "r"(ph) : "memory");
    return ok;
}
__device__ __forceinline__ void bulk1d(uint32_t dst, const void* src, uint32_t bar, uint64_t pol) {
    asm volatile("cp.async.bulk.shared::cluster.global.mbarrier::complete_tx::bytes.L2::cache_hint [%0], [%1], %2, [%3], %4;"
                 ::"r"(dst), "l"(src), "n"(CH), "r"(bar), "l"(pol) : "memory");
}
__device__ __forceinline__ void bulk1d_n(uint32_t dst, const void* src, uint32_t bytes, uint32_t bar) {
    asm volatile("cp.async.bulk.shared::cluster.global.mbarrier::complete_tx::bytes [%0], [%1], %2, [%3];"
                 ::"r"(dst), "l"(src), "r"(bytes), "r"(bar) : "memory");
}
__device__ __forceinline__ void tma3d(uint32_t dst, const CUtensorMap* map, int c1, int c2, uint32_t bar, uint64_t pol, int c0 = 0) {
    asm volatile("cp.async.bulk.tensor.3d.shared::cluster.global.mbarrier::complete_tx::bytes.L2::cache_hint [%0], [%1, {%3,%4,%5}], [%2], %6;"
                 ::"r"(dst), "l"(map), "r"(bar), "r"(c0), "r"(c1), "r"(c2), "l"(pol) : "memory");
}
__device__ __forceinline__ void bar_sync(int id, int n) { asm volatile("barrier.cta.sync %0, %1;" ::"r"(id), "r"(n) : "memory"); }
__device__ __forceinline__ void bar_arrive(int id, int n) { asm volatile("barrier.cta.arrive %0, %1;" ::"r"(id), "r"(n) : "memory"); }
__device__ __forceinline__ void ldsm4(uint32_t (&r)[4], uint32_t a) {
    asm volatile("ldmatrix.sync.aligned.m8n8.x4.shared.b16 {%0,%1,%2,%3}, [%4];" : "=r"(r[0]), "=r"(r[1]), "=r"(r[2]), "=r"(r[3]) : "r"(a) : "memory");
}
__device__ __forceinline__ void ldsm4t(uint32_t (&r)[4], uint32_t a) {
    asm volatile("ldmatrix.sync.aligned.m8n8.x4.trans.shared.b16 {%0,%1,%2,%3}, [%4];" : "=r"(r[0]), "=r"(r[1]), "=r"(r[2]), "=r"(r[3]) : "r"(a) : "memory");
}
__device__ __forceinline__ void mma(float (&c)[4], const uint32_t (&a)[4], uint32_t b0, uint32_t b1) {
    asm volatile("mma.sync.aligned.m16n8k16.row.col.f32.bf16.bf16.f32 {%0,%1,%2,%3}, {%4,%5,%6,%7}, {%8,%9}, {%0,%1,%2,%3};"
                 : "+f"(c[0]), "+f"(c[1]), "+f"(c[2]), "+f"(c[3]) : "r"(a[0]), "r"(a[1]), "r"(a[2]), "r"(a[3]), "r"(b0), "r"(b1));
}
__device__ __forceinline__ uint32_t lds32(uint32_t a) { uint32_t v; asm volatile("ld.shared.b32 %0, [%1];" : "=r"(v) : "r"(a) : "memory"); return v; }
__device__ __forceinline__ uint32_t ldsv(uint32_t a) { uint32_t v; asm volatile("ld.volatile.shared.b32 %0, [%1];" : "=r"(v) : "r"(a) : "memory"); return v; }
__device__ __forceinline__ void stsv(uint32_t a, uint32_t v) { asm volatile("st.volatile.shared.b32 [%0], %1;" ::"r"(a), "r"(v) : "memory"); }
__device__ __forceinline__ float ldsf(uint32_t a) { float v; asm volatile("ld.shared.f32 %0, [%1];" : "=f"(v) : "r"(a) : "memory"); return v; }
__device__ __forceinline__ uint4 lds128(uint32_t a) { uint4 v; asm volatile("ld.shared.v4.b32 {%0,%1,%2,%3}, [%4];" : "=r"(v.x), "=r"(v.y), "=r"(v.z), "=r"(v.w) : "r"(a) : "memory"); return v; }
__device__ __forceinline__ void sts16(uint32_t a, uint16_t v) { asm volatile("st.shared.b16 [%0], %1;" ::"r"(a), "h"(v) : "memory"); }
__device__ __forceinline__ void sts32(uint32_t a, uint32_t v) { asm volatile("st.shared.b32 [%0], %1;" ::"r"(a), "r"(v) : "memory"); }
__device__ __forceinline__ void stsf2(uint32_t a, float x, float y) { asm volatile("st.shared.v2.f32 [%0], {%1,%2};" ::"r"(a), "f"(x), "f"(y) : "memory"); }
__device__ __forceinline__ void sts128(uint32_t a, uint4 v) { asm volatile("st.shared.v4.b32 [%0], {%1,%2,%3,%4};" ::"r"(a), "r"(v.x), "r"(v.y), "r"(v.z), "r"(v.w) : "memory"); }
__device__ __forceinline__ uint16_t f2bf(float x) { return __bfloat16_as_ushort(__float2bfloat16_rn(x)); }
__device__ __forceinline__ float bfround(float x) { return __bfloat162float(__float2bfloat16_rn(x)); }
__device__ __forceinline__ uint32_t pack2(float lo, float hi) { uint32_t r; asm("cvt.rn.bf16x2.f32 %0, %1, %2;" : "=r"(r) : "f"(hi), "f"(lo)); return r; }
__device__ __forceinline__ float ex2(float x) { float r; asm("ex2.approx.ftz.f32 %0, %1;" : "=f"(r) : "f"(x)); return r; }
__device__ __forceinline__ float lg2(float x) { float r; asm("lg2.approx.ftz.f32 %0, %1;" : "=f"(r) : "f"(x)); return r; }

__device__ __forceinline__ float rcp(float x) { float r; asm("rcp.approx.ftz.f32 %0, %1;" : "=f"(r) : "f"(x)); return r; }
__device__ __forceinline__ void merge_weights(uint32_t l0, uint32_t l1, float& w0, float& w1) {
    const float a = __uint_as_float(l0), b = __uint_as_float(l1), mx = fmaxf(a, b), e0 = ex2(a - mx), e1 = ex2(b - mx), r = rcp(e0 + e1);
    w0 = e0 * r; w1 = e1 * r;
}

__device__ __forceinline__ void sleep_ns(uint32_t ns) {
    uint32_t t0, t;
    asm volatile("mov.u32 %0, %clock;" : "=r"(t0));
    do { __nanosleep(200); asm volatile("mov.u32 %0, %clock;" : "=r"(t)); } while (t - t0 < 2 * ns);
}

__device__ __forceinline__ void ll_store2(ulonglong2* p, float a, float b, uint32_t tag) {
    unsigned long long x = ((unsigned long long)tag << 32) | __float_as_uint(a);
    unsigned long long y = ((unsigned long long)tag << 32) | __float_as_uint(b);
    asm volatile("st.relaxed.gpu.global.v2.b64 [%0], {%1,%2};" ::"l"(p), "l"(x), "l"(y) : "memory");
}
__device__ __forceinline__ void ll_ld2(const void* p, unsigned long long& x, unsigned long long& y) {
    asm volatile("ld.relaxed.gpu.global.v2.b64 {%0,%1}, [%2];" : "=l"(x), "=l"(y) : "l"(p) : "memory");
}
__device__ __forceinline__ void ll_gather4(const ulonglong2* p, uint32_t tag, float& r0, float& r1) {
    unsigned long long x[4], y[4]; uint32_t it = 0;
    while (true) {
        bool ok = true;
#pragma unroll
        for (int k = 0; k < 4; k++) ll_ld2(p + k * 128, x[k], y[k]);
#pragma unroll
        for (int k = 0; k < 4; k++) ok = ok && (uint32_t)(x[k] >> 32) == tag && (uint32_t)(y[k] >> 32) == tag;
        if (ok) break;
        if (++it > SPIN_MAX) __trap();
        __nanosleep(BACKOFF);
    }
    r0 = (__uint_as_float((uint32_t)x[0]) + __uint_as_float((uint32_t)x[1])) + (__uint_as_float((uint32_t)x[2]) + __uint_as_float((uint32_t)x[3]));
    r1 = (__uint_as_float((uint32_t)y[0]) + __uint_as_float((uint32_t)y[1])) + (__uint_as_float((uint32_t)y[2]) + __uint_as_float((uint32_t)y[3]));
}
__device__ __forceinline__ void cnt_rendezvous(unsigned* c, uint32_t target, int tsk) {
    TS(tsk);
    asm volatile("red.release.gpu.global.add.u32 [%0], 1;" ::"l"(c) : "memory");
    if (tsk == 18) TS(tsk + 1);
    uint32_t v, it = 0;
    while (true) {
        asm volatile("ld.acquire.gpu.global.u32 %0, [%1];" : "=r"(v) : "l"(c) : "memory");
        if ((int)(v - target) >= 0) break;
        if (++it > SPIN_MAX) __trap();
        __nanosleep(BACKOFF);
    }
    asm volatile("fence.proxy.async.global;" ::: "memory");
}

__device__ __forceinline__ void matvec_loadA(uint32_t (&a)[8][4], uint32_t tile, uint32_t bar, int w, int lane) {
    const int i = lane >> 3, rr = lane & 7, chunk = 2 * w + (i & 1);
    const uint32_t a0 = tile + (chunk >> 3) * 8192 + (rr + 8 * (i >> 1)) * 128 + (((chunk & 7) ^ rr) << 4);
#pragma unroll
    for (int hh = 0; hh < 2; hh++) {
        mbar_wait(bar + hh * 8, 0);
#pragma unroll
        for (int k = 0; k < 4; k++) ldsm4t(a[hh * 4 + k], a0 + hh * CH + k * 2048);
    }
}
__device__ __forceinline__ void matvec_mma(float (&c)[4], const uint32_t (&a)[8][4], uint32_t vec, int nvec, int lane) {
    const uint32_t va = vec + (lane & (nvec - 1)) * VROW + (lane >> 3) * 16;
    float d[4][4];
#pragma unroll
    for (int q = 0; q < 4; q++) {
        uint32_t b[4];
        ldsm4(b, va + q * 64);
        d[q][0] = d[q][1] = d[q][2] = d[q][3] = 0.f;
        mma(d[q], a[2 * q], b[0], b[1]);
        mma(d[q], a[2 * q + 1], b[2], b[3]);
    }
#pragma unroll
    for (int k = 0; k < 4; k++) c[k] = (d[0][k] + d[1][k]) + (d[2][k] + d[3][k]);
}
__device__ __forceinline__ void matvecT(float (&c)[4], uint32_t tile, uint32_t vec, int nvec, uint32_t bar, int w, int lane) {
    uint32_t a[8][4];
    matvec_loadA(a, tile, bar, w, lane);
    matvec_mma(c, a, vec, nvec, lane);
}
template <class T> __device__ __forceinline__ T* pin(T* p) { asm volatile("" : "+l"(p)); return p; }
__device__ __forceinline__ void mail_put(void* p, uint32_t v) { asm volatile("st.relaxed.gpu.global.b32 [%0], %1;" ::"l"(p), "r"(v) : "memory"); }
__device__ __forceinline__ void mail_put(void* p, float v) { mail_put(p, __float_as_uint(v)); }
__device__ __forceinline__ void out_add(__nv_bfloat16* p, float x, float y) {
    asm volatile("red.relaxed.gpu.global.add.noftz.bf16x2 [%0], %1;" ::"l"(p), "r"(pack2(x, y)) : "memory");
}
__device__ __forceinline__ bool mail_missing(const uint4& v) { return v.x == EMPTY || v.y == EMPTY || v.z == EMPTY || v.w == EMPTY; }
__device__ __forceinline__ void mail_get(uint4& v, const uint4* p, bool need = true) {
    asm volatile("{\n.reg .pred q;\nsetp.ne.u32 q, %5, 0;\n@q ld.relaxed.gpu.global.v4.b32 {%0,%1,%2,%3}, [%4];\n}"
                 : "+r"(v.x), "+r"(v.y), "+r"(v.z), "+r"(v.w) : "l"(p), "r"((uint32_t)need) : "memory");
}
__device__ __forceinline__ void sts64(uint32_t a, uint32_t x, uint32_t y) { asm volatile("st.shared.v2.b32 [%0], {%1,%2};" ::"r"(a), "r"(x), "r"(y) : "memory"); }
__device__ __forceinline__ float2 ldsf2(uint32_t a) { float2 v; asm volatile("ld.shared.v2.f32 {%0,%1}, [%2];" : "=f"(v.x), "=f"(v.y) : "r"(a) : "memory"); return v; }

__global__ void __launch_bounds__(NTHREADS, 1)
fused_decode_kernel(const char* __restrict__ wqraw, const __grid_constant__ Maps maps, const char* __restrict__ Kc, const char* __restrict__ Vc,
                    const __nv_bfloat16* __restrict__ xA, const __nv_bfloat16* __restrict__ xB,
                    __nv_bfloat16* __restrict__ out, const uint32_t zero) {
    asm volatile("{\n.reg .pred p;\nsetp.eq.u32 p, %1, 32;\n@p cp.async.bulk.prefetch.L2.global [%0], 32768;\n}"
                 ::"l"(wqraw + (size_t)blockIdx.x * 32768u), "r"(threadIdx.x) : "memory");
    extern __shared__ char smem_raw[];
    const uint32_t sm = ((uint32_t)__cvta_generic_to_shared(smem_raw) + 1023u) & ~1023u;
    const uint32_t bars = sm + OFF_BAR;
    const int cta = blockIdx.x, h = cta >> 2, j = cta & 3;
    uint64_t pol = 0;
    if (threadIdx.x == 0) {
        TS(0);
        asm volatile("createpolicy.fractional.L2::evict_first.b64 %0, 1.0;" : "=l"(pol));
#pragma unroll
        for (int i = 0; i < WIN; i++) mbar_init(bars + (B_WQB + i) * 8, 1);
        asm volatile("fence.mbarrier_init.release.cluster;" ::: "memory");
#pragma unroll
        for (int i = 0; i < WIN; i++) {
            mbar_expect(bars + (B_WQB + i) * 8, CH);
            tma3d(sm + OFF_S0 + i * CH, &maps.wqB + (i >> 1), j * 128 + (i & 1) * 64, h * 2, bars + (B_WQB + i) * 8, pol);
        }
    }
    const int tid = threadIdx.x < 64 ? threadIdx.x + 384 : threadIdx.x - 64, warp = tid >> 5, lane = tid & 31;

    if (warp == 12) {
        const size_t kvoff = ((size_t)(((j >> 1) * 32 + h) * 4096 + (j & 1) * 2048)) * 256;
        const char* kp = Kc + kvoff;
        const char* vp = Vc + kvoff;
        __syncwarp();
        bar_arrive(0, NTHREADS);
        bar_sync(3, 64);
        if (lane == 0) {
            uint32_t pb[WHI];
#pragma unroll
            for (int i = 0; i < WHI; i++) pb[i] = i < WHI - WIN ? (bars + B_WO * 8) | 1u : bars + (B_WQB + i - (WHI - WIN)) * 8;
            auto pace = [&](uint32_t bar, uint32_t par, uint32_t wina) {
                uint32_t it = 0;
                while (true) {
                    const uint32_t win = ldsv(wina);
                    uint32_t busy = 0;
#pragma unroll
                    for (int i = 0; i < WHI; i++) busy += mbar_test(pb[i] & ~1u, pb[i] & 1u) ^ 1u;
                    if (busy < win) break;
                    if (++it > SPIN_MAX) __trap();
                }
#pragma unroll
                for (int i = 0; i + 1 < WHI; i++) pb[i] = pb[i + 1];
                pb[WHI - 1] = bar | par;
            };
            auto side = [&](const CUtensorMap* m, uint32_t dst, int bidx, int c1, int c2, uint32_t wina) {
                const uint32_t bar = bars + bidx * 8;
                pace(bar, 0, wina);
                mbar_expect(bar, CH);
                tma3d(dst, m, c1, c2, bar, pol);
            };
#pragma unroll 1
            for (int i = WIN; i < 6; i++)
                side(&maps.wqB + (i >> 1), sm + OFF_S0 + i * CH, B_WQB + i, j * 128 + (i & 1) * 64, h * 2, sm + OFF_WIN);
            TS(1);
            uint32_t slot = 0, use = 0;
            int nuv = 0;
#pragma unroll 1
            for (int n = 0; n < 2 * NTILE; n++) {
                if (n == RING) {
                    mbar_wait(bars + B_FREE * 8, 0);
#pragma unroll 1
                    for (int q = 0; q < 4; q++) side(&maps.ckv, sm + OFF_S0 + q * CH, B_CKV + q, cta * 64 + q * 16, 0, sm + OFF_WIN);
                }
                if (nuv < 2 && n > RING && (n >= 2 * NTILE - 8 || mbar_test(bars + B_FREE * 8, 1))) {
                    mbar_wait(bars + B_FREE * 8, 1);
                    side(&maps.wuv, sm + OFF_S1 + nuv * CH, B_WUV + nuv, j * 128 + nuv * 64, h * 2, sm + OFF_WIN);
                    nuv++;
                }
                const uint32_t fb = bars + slot * 8;
                pace(fb, use & 1, sm + OFF_WIN);
                mbar_wait(fb + B_EMPTY * 8, (use & 1) ^ 1);
                mbar_expect(fb, CH);
                bulk1d(sm + OFF_RING + slot * CH, ((n & RUN) ? vp : kp) + (size_t)(n / (2 * RUN) * RUN + n % RUN) * CH, fb, pol);
                if (((n + cta) & 3) == 0) asm volatile("red.relaxed.gpu.global.add.u32 [%0], 4;" ::"l"(&g_cnt[2]) : "memory");
                stsv(sm + OFF_NOW, n + 1);
                if (++slot == RING) { slot = 0; use++; }
            }
            TS(2);
            mbar_wait(bars + B_FREE * 8, 0);
#pragma unroll 1
            for (int i = 0; i < 4; i++) {
                const uint32_t bar = bars + (B_WO + 2 * i) * 8;
                pace(bar + 8, 0, sm + OFF_TWIN);
                TS(32 + i);
#pragma unroll
                for (int k = 0; k < 2; k++) {
                    mbar_expect(bar + k * 8, CH / 2);
                    tma3d(sm + OFF_S0 + i * CH + k * (CH / 2), &maps.woB + (i >> 1), (i & 1) * 64 + k * 32, h & ~3, bar + k * 8, pol, (cta & 15) * 32);
                }
            }
            TS(3);
        }
    } else if (warp == 13) {
        if (lane == 0) {
#pragma unroll
            for (int i = 0; i < NBAR; i++)
                if (i < B_WQB || i >= B_WQB + WIN)
                    mbar_init(bars + i * 8, i == B_FREE ? 8 : (i >= B_EMPTY && i < B_EMPTY + RING) ? 4 : 1);
            asm volatile("fence.mbarrier_init.release.cluster;" ::: "memory");
#pragma unroll
            for (int i = 2; i < 8; i++) asm volatile("prefetch.tensormap [%0];" ::"l"(&maps.wqB + i) : "memory");
            stsv(sm + OFF_NOW, 0); stsv(sm + OFF_WIN, WIN); stsv(sm + OFF_TWIN, PREWIN);
        }
        __syncwarp();
        bar_arrive(3, 64);
        bar_sync(0, NTHREADS);
        if (lane == 0) {
            const uint32_t base = (lds32(sm + OFF_TAG) - 1u) * (NCTA * 2 * NTILE);
            mbar_wait(bars + (B_WUK + 1) * 8, 0);
            uint32_t it = 0;
            while (true) {
                const uint32_t n = ldsv(sm + OFF_NOW);
                uint32_t v;
                asm volatile("ld.relaxed.gpu.global.u32 %0, [%1];" : "=r"(v) : "l"(&g_cnt[2]) : "memory");
                v -= base;
                if (v >= NCTA * 2 * NTILE - GATE_W) break;
                const int diff = (int)(n * NCTA) - (int)v;
                stsv(sm + OFF_WIN, diff < -THETA ? WHI : WIN - (diff > THETA) - (v >= NCTA * END_V));
                if (++it > SPIN_MAX) __trap();
                __nanosleep(BACKOFF2);
            }
            stsv(sm + OFF_WIN, WHI); stsv(sm + OFF_TWIN, TAILWIN);
            TS(24);
        }
    } else if (warp < 4) {
        const int g = lane >> 2, t = lane & 3, i = lane >> 3, rr = lane & 7;
        if (tid == 0) {
            unsigned e;
            asm volatile("ld.relaxed.gpu.global.u32 %0, [%1];" : "=r"(e) : "l"(&g_cnt[1]) : "memory");
            sts32(sm + OFF_TAG, (e >> 7) + 1u);
        }
        bar_sync(0, NTHREADS);
        const uint32_t tag = lds32(sm + OFF_TAG);
        {
            mbar_wait(bars + 8, 0);
            float q0, q1;
            ll_gather4(&g_e1[0][h * 4][tid], tag, q0, q1);
            sts16(sm + OFF_QB + tid * 2, f2bf((j >> 1) ? q1 : q0));
        }
        bar_sync(1, 128);
        if (tid == 0) TS(4);
        uint32_t qf[8][2];
#pragma unroll
        for (int c = 0; c < 8; c++) {
            const uint32_t a = sm + OFF_QB + (((c + g) & 7) * 8 + 2 * t) * 2;
            qf[c][0] = lds32(a); qf[c][1] = lds32(a + 128);
        }
        float acc[8][4];
#pragma unroll
        for (int c = 0; c < 8; c++) { acc[c][0] = acc[c][1] = acc[c][2] = acc[c][3] = 0.f; }
        float m = -INFINITY, l = 0.f;
        const bool diag = (t == (g >> 1));
        const uint32_t krow = sm + OFF_RING + (warp * 16 + rr + 8 * (i & 1)) * 256 + (i >> 1) * 128;
        const uint32_t vrow = sm + OFF_RING + (warp * 16 + rr + 8 * (i >> 1)) * 256 + (i & 1) * 128;
        uint32_t slot = 0, ph = 0;
        uint32_t* const e5own = pin((uint32_t*)g_e5[cta] + tid);
        uint32_t a[8][4] = {}, b0[RUN], b1[RUN];
        auto release = [&]() {
            __syncwarp();
            if (lane == 0) mbar_arrive(bars + (B_EMPTY + slot) * 8 + ((a[0][0] | a[1][0] | a[2][0] | a[3][0] | a[4][0] | a[5][0] | a[6][0] | a[7][0]) & zero));
            if (++slot == RING) { slot = 0; ph ^= 1; }
        };
        auto load_v = [&]() {
            mbar_wait(bars + slot * 8, ph);
#pragma unroll
            for (int c = 0; c < 8; c++) ldsm4t(a[c], vrow + slot * CH + (((c + rr) & 7) << 4));
        };
#pragma unroll 1
        for (int run = 0;; run++) {
            float slo[RUN], shi[RUN], mx = -INFINITY;
#pragma unroll
            for (int u = 0; u < RUN; u++) {
                mbar_wait(bars + slot * 8, ph);
#pragma unroll
                for (int c = 0; c < 8; c++) ldsm4(a[c], krow + slot * CH + (((c + rr) & 7) << 4));
                release();
                float s0[4] = {0.f, 0.f, 0.f, 0.f}, s1[4] = {0.f, 0.f, 0.f, 0.f};
#pragma unroll
                for (int c = 0; c < 8; c += 2) { mma(s0, a[c], qf[c][0], qf[c][1]); mma(s1, a[c + 1], qf[c + 1][0], qf[c + 1][1]); }
                slo[u] = diag ? bfround(bfround((g & 1) ? s0[1] + s1[1] : s0[0] + s1[0]) * SCALE) : -INFINITY;
                shi[u] = diag ? bfround(bfround((g & 1) ? s0[3] + s1[3] : s0[2] + s1[2]) * SCALE) : -INFINITY;
                mx = fmaxf(mx, fmaxf(slo[u], shi[u]));
            }
            int key = __float_as_int(mx);
            key ^= (key >> 31) & 0x7fffffff;
            key = __reduce_max_sync(0xffffffffu, key);
            key ^= (key >> 31) & 0x7fffffff;
            const float mn = fmaxf(m, __int_as_float(key));
            const float alpha = ex2((m - mn) * LOG2E);
            m = mn;
            l *= alpha;
#pragma unroll
            for (int u = 0; u < RUN; u++) {
                const float plo = ex2((slo[u] - mn) * LOG2E), phi = ex2((shi[u] - mn) * LOG2E);
                l += plo + phi;
                b0[u] = (g & 1) ? pack2(0.f, plo) : pack2(plo, 0.f);
                b1[u] = (g & 1) ? pack2(0.f, phi) : pack2(phi, 0.f);
            }
#pragma unroll
            for (int c = 0; c < 8; c++) { acc[c][0] *= alpha; acc[c][1] *= alpha; acc[c][2] *= alpha; acc[c][3] *= alpha; }
            if (run == NTILE / RUN - 1) break;
#pragma unroll
            for (int u = 0; u < RUN; u++) {
                load_v();
                release();
#pragma unroll
                for (int c = 0; c < 8; c++) mma(acc[c], a[c], b0[u], b1[u]);
            }
        }
#pragma unroll
        for (int o = 16; o; o >>= 1) l += __shfl_xor_sync(0xffffffffu, l, o);
        if (lane == 0) stsf2(sm + OFF_ML + warp * 8, m, l);
        mbar_wait(bars + B_S2 * 8, 0);
        bar_sync(1, 128);
        {
            const uint4 ml0 = lds128(sm + OFF_ML), ml1 = lds128(sm + OFF_ML + 16);
            const float m0 = __uint_as_float(ml0.x), m1 = __uint_as_float(ml0.z), m2 = __uint_as_float(ml1.x), m3 = __uint_as_float(ml1.z);
            const float M = fmaxf(fmaxf(m0, m1), fmaxf(m2, m3));
            const float L = (ex2((m0 - M) * LOG2E) * __uint_as_float(ml0.y) + ex2((m1 - M) * LOG2E) * __uint_as_float(ml0.w))
                          + (ex2((m2 - M) * LOG2E) * __uint_as_float(ml1.y) + ex2((m3 - M) * LOG2E) * __uint_as_float(ml1.w));
            const float f = ex2((m - M) * LOG2E) * rcp(L);
            const float lse = M * LOG2E + lg2(L);
            float* const l5own = pin((float*)g_l5[h] + j);
            const uint32_t wa = sm + OFF_S2 + warp * 640 + (t * 16 + (t >> 1) * 8 + g) * 4;
            const uint32_t ra = sm + OFF_S2 + ((tid >> 4 & 1) * 40 + (tid & 2) * 40 + (tid >> 5) * 16 + (tid & 1) * 8 + (tid >> 2 & 3) * 2) * 4;
#pragma unroll
            for (int u = 0; u < RUN; u++) {
                load_v();
                if (++slot == RING) { slot = 0; ph ^= 1; }
                if (u == RUN - 1 && tid == 96) mail_put(l5own, lse);
#pragma unroll
                for (int c = 0; c < 8; c++) mma(acc[c], a[c], b0[u], b1[u]);
            }
            if (tid == 0) TS(5);
            float v[2][8];
#pragma unroll
            for (int c = 0; c < 8; c++) { v[0][c] = acc[c][0] + acc[(c + 7) & 7][1]; v[1][c] = acc[c][2] + acc[(c + 7) & 7][3]; }
#pragma unroll
            for (int c = 0; c < 4; c++) { v[0][c] += __shfl_xor_sync(0xffffffffu, v[0][c + 4], 2); v[1][c] += __shfl_xor_sync(0xffffffffu, v[1][c + 4], 2); }
            const int src = (lane & ~3) | ((lane + 3) & 3);
#pragma unroll
            for (int c = 0; c < 2; c++) { v[0][c] += __shfl_sync(0xffffffffu, v[0][c + 2], src); v[1][c] += __shfl_sync(0xffffffffu, v[1][c + 2], src); }
#pragma unroll
            for (int c = 0; c < 4; c++) sts32(wa + (c >> 1) * 320 + (c & 1) * 32, __float_as_uint(v[c >> 1][c & 1] * f));
            if (warp < 2) {
                bar_sync(1, 128);
                const float2 r0 = ldsf2(ra), r1 = ldsf2(ra + 640), r2 = ldsf2(ra + 1280), r3 = ldsf2(ra + 1920);
                mail_put(e5own, pack2((r0.x + r1.x) + (r2.x + r3.x), (r0.y + r1.y) + (r2.y + r3.y)));
            } else {
                bar_arrive(1, 128);
            }
        }
        if (tid == 0) TS(6);
        {
            uint32_t x[4][4][4];
            float d[4][4];
            bar_sync(4, 256 + 128);
#pragma unroll
            for (int k = 0; k < 16; k++) ldsm4(x[k >> 2][k & 3], sm + OFF_CA + ((k >> 2) * 2 + (lane & 1)) * VROW + (k & 3) * 64 + (i & 1) * 32 + (i >> 1) * 16);
#pragma unroll
            for (int k = 0; k < 4; k++) d[k][0] = d[k][1] = d[k][2] = d[k][3] = 0.f;
            const uint32_t wa = sm + OFF_S1 + lane * 64 + ((warp ^ (rr >> 1)) << 4);
            __nv_bfloat16* const outp = pin(out + (g & 1) * 1024 + (cta & 15) * 32 + warp * 8 + t * 2);
#pragma unroll
            for (int q = 0; q < 4; q += 2) {
#pragma unroll
                for (int k = 0; k < 8; k++) {
                    if (!(k & 3)) mbar_wait(bars + (B_WO + 4 + q + (k >> 2)) * 8, 0);
                    ldsm4t(a[k], wa + q * 8192 + k * 2048);
                }
#pragma unroll
                for (int k = 0; k < 16; k++) mma(d[k & 3], x[(k >> 1) & 3][q + (k >> 3)], a[k >> 1][(k & 1) * 2], a[k >> 1][(k & 1) * 2 + 1]);
            }
            if (lane < 8) out_add(outp, (d[0][0] + d[1][2]) + (d[2][0] + d[3][2]), (d[0][1] + d[1][3]) + (d[2][1] + d[3][3]));
            if (tid == 0) TS(15);
        }
    } else {
        const int st = tid - 128, w = warp - 4;
        const int g = lane >> 2, t = lane & 3, i = lane >> 3, rr = lane & 7;
        if (t == 0) {
#pragma unroll
            for (int k = 0; k < 4; k++) ll_store2(&g_e1[k >> 1][cta][w * 16 + g + (k & 1) * 8], 0.f, 0.f, 0u);
        }
        if (st < 64) {
            const int which = st >> 5, b = (st >> 4) & 1, c = st & 15;
            const uint4 v = __ldg((const uint4*)((which ? xA : xB) + b * 512 + j * 128) + c);
            sts128(sm + OFF_XB + (which * 2 + b) * VROW + c * 16, v);
        }
        bar_sync(0, NTHREADS);
        const uint32_t tag = lds32(sm + OFF_TAG);
        float c[4];
#pragma unroll 1
        for (int which = 0; which < 2; which++) {
            matvecT(c, sm + OFF_S0 + which * 2 * CH, sm + OFF_XB + which * 2 * VROW, 2, bars + (B_WQB + which * 2) * 8, w, lane);
            if (t == 0) {
                ll_store2(&g_e1[which][cta][w * 16 + g], c[0], c[1], tag);
                ll_store2(&g_e1[which][cta][w * 16 + g + 8], c[2], c[3], tag);
            }
        }
        __syncwarp();
        if (lane == 0) mbar_arrive(bars + B_FREE * 8);
        if (st == 0) TS(8);
        if (st < 128) {
            float q0, q1;
            sleep_ns(POLL_DELAY);
            ll_gather4(&g_e1[1][h * 4][st], tag, q0, q1);
            sts16(sm + OFF_QA + st * 2, f2bf(q0)); sts16(sm + OFF_QA + VROW + st * 2, f2bf(q1));
        }
        bar_sync(2, 256);
        if (st == 0) TS(9);
        {
            const int row = w * 16 + rr + 8 * (i & 1);
            const uint32_t a0 = sm + OFF_S2 + (row >> 6) * CH + (row & 63) * 128;
            const uint32_t va = sm + OFF_QA + g * VROW + t * 4;
            float d[4] = {0.f, 0.f, 0.f, 0.f};
            c[0] = c[1] = c[2] = c[3] = 0.f;
            mbar_wait(bars + (B_WUK + (w >> 2)) * 8, 0);
#pragma unroll
            for (int ks = 0; ks < 8; ks++) {
                const int chunk = 2 * ks + (i >> 1);
                uint32_t a[4];
                ldsm4(a, a0 + (chunk >> 3) * 8192 + (((chunk & 7) ^ rr) << 4));
                const uint32_t b0 = (g < 2) ? lds32(va + ks * 32) : 0u, b1 = (g < 2) ? lds32(va + ks * 32 + 16) : 0u;
                if (ks & 1) mma(d, a, b0, b1); else mma(c, a, b0, b1);
            }
            if (t == 0) {
                const uint32_t qs = sm + OFF_QS + (w * 16 + g) * 2;
                sts16(qs, f2bf(c[0] + d[0])); sts16(qs + VROW, f2bf(c[1] + d[1]));
                sts16(qs + 16, f2bf(c[2] + d[2])); sts16(qs + VROW + 16, f2bf(c[3] + d[3]));
            }
            bar_sync(2, 256);
            if (w == 0) {
                const int b = lane >> 4, cc = lane & 15;
                g_qabs[(b * 32 + h) * 64 + ((j * 16 + cc) ^ (h & 7))] = lds128(sm + OFF_QS + b * VROW + cc * 16);
                __syncwarp();
                if (lane == 0) {
                    cnt_rendezvous(&g_cnt[0], tag * 128u, 18);
                    TS(10);
                    mbar_expect(bars + B_GATH * 8, 2 * CH);
                    bulk1d_n(sm + OFF_S2, g_qabs + (cta >> 6) * 2048, 2 * CH, bars + B_GATH * 8);
                }
                __syncwarp();
            }
        }
        mbar_wait(bars + B_GATH * 8, 0);
        if (st == 0) TS(11);
        {
            const int mt = w & 1, kg = w >> 1;
            const uint32_t qa = sm + OFF_S2 + (mt * 16 + rr + 8 * (i & 1)) * 1024;
            const uint32_t ka = sm + OFF_S0 + kg * CH + (rr + 8 * (i >> 1)) * 128;
            float s0[4] = {0.f, 0.f, 0.f, 0.f}, s1[4] = {0.f, 0.f, 0.f, 0.f};
            mbar_wait(bars + (B_CKV + kg) * 8, 0);
#pragma unroll 2
            for (int gq = 0; gq < 8; gq++) {
#pragma unroll
                for (int k4 = 0; k4 < 4; k4++) {
                    uint32_t a[4], b[4];
                    ldsm4(a, qa + gq * 128 + (((2 * k4 + (i >> 1)) ^ rr) << 4));
                    ldsm4(b, ka + gq * 2048 + (((2 * k4 + (i & 1)) ^ rr) << 4));
                    mma(s0, a, b[0], b[1]);
                    mma(s1, a, b[2], b[3]);
                }
            }
            const uint32_t sa = sm + OFF_SC + ((mt * 16 + g) * 68 + kg * 16 + 2 * t) * 4;
            stsf2(sa, s0[0], s0[1]); stsf2(sa + 32, s1[0], s1[1]);
            stsf2(sa + 8 * 68 * 4, s0[2], s0[3]); stsf2(sa + 8 * 68 * 4 + 32, s1[2], s1[3]);
        }
        bar_sync(2, 256);
        {
            const int head = w * 4 + i;
            const uint32_t sa = sm + OFF_SC + (head * 68 + rr * 8) * 4;
            const uint4 u0 = lds128(sa), u1 = lds128(sa + 16);
            float s[8] = {__uint_as_float(u0.x), __uint_as_float(u0.y), __uint_as_float(u0.z), __uint_as_float(u0.w),
                          __uint_as_float(u1.x), __uint_as_float(u1.y), __uint_as_float(u1.z), __uint_as_float(u1.w)};
            float mx = s[0];
#pragma unroll
            for (int k = 1; k < 8; k++) mx = fmaxf(mx, s[k]);
#pragma unroll
            for (int o = 1; o < 8; o <<= 1) mx = fmaxf(mx, __shfl_xor_sync(0xffffffffu, mx, o));
            float sum = 0.f;
#pragma unroll
            for (int k = 0; k < 8; k++) { s[k] = ex2((s[k] - mx) * (SCALE * LOG2E)); sum += s[k]; }
#pragma unroll
            for (int o = 1; o < 8; o <<= 1) sum += __shfl_xor_sync(0xffffffffu, sum, o);
            const float inv = __fdividef(1.f, sum);
            uint4 p;
            p.x = pack2(s[0] * inv, s[1] * inv); p.y = pack2(s[2] * inv, s[3] * inv);
            p.z = pack2(s[4] * inv, s[5] * inv); p.w = pack2(s[6] * inv, s[7] * inv);
            sts128(sm + OFF_P + head * 128 + ((rr ^ (head & 7)) << 4), p);
            if (rr == 0) ((float*)g_lse)[head * 128 + cta] = mx * (SCALE * LOG2E) + lg2(sum);
        }
        bar_sync(2, 256);
        {
            float o[2][8][4];
#pragma unroll
            for (int mt = 0; mt < 2; mt++)
#pragma unroll
                for (int n = 0; n < 8; n++) { o[mt][n][0] = o[mt][n][1] = o[mt][n][2] = o[mt][n][3] = 0.f; }
            const uint32_t pa = sm + OFF_P + (rr + 8 * (i & 1)) * 128;
            const uint32_t va = sm + OFF_S0 + w * 2048 + (rr + 8 * (i & 1)) * 128;
#pragma unroll 1
            for (int kq = 0; kq < 4; kq++) {
                uint32_t a0[4], a1[4];
                ldsm4(a0, pa + (((2 * kq + (i >> 1)) ^ rr) << 4));
                ldsm4(a1, pa + 2048 + (((2 * kq + (i >> 1)) ^ rr) << 4));
#pragma unroll
                for (int n = 0; n < 8; n += 2) {
                    uint32_t b[4];
                    ldsm4t(b, va + kq * CH + (((n + (i >> 1)) ^ rr) << 4));
                    mma(o[0][n], a0, b[0], b[1]); mma(o[1][n], a1, b[0], b[1]);
                    mma(o[0][n + 1], a0, b[2], b[3]); mma(o[1][n + 1], a1, b[2], b[3]);
                }
            }
#pragma unroll
            for (int mt = 0; mt < 2; mt++)
#pragma unroll
                for (int hf = 0; hf < 2; hf++) {
                    const uint32_t dst = sm + OFF_S2 + (mt * 16 + hf * 8 + g) * 1024 + w * 128 + t * 16;
#pragma unroll
                    for (int nb = 0; nb < 2; nb++) {
                        uint4 v;
                        v.x = pack2(o[mt][nb * 4 + 0][hf * 2], o[mt][nb * 4 + 0][hf * 2 + 1]);
                        v.y = pack2(o[mt][nb * 4 + 1][hf * 2], o[mt][nb * 4 + 1][hf * 2 + 1]);
                        v.z = pack2(o[mt][nb * 4 + 2][hf * 2], o[mt][nb * 4 + 2][hf * 2 + 1]);
                        v.w = pack2(o[mt][nb * 4 + 3][hf * 2], o[mt][nb * 4 + 3][hf * 2 + 1]);
                        sts128(dst + nb * 64, v);
                    }
                }
            asm volatile("fence.proxy.async.shared::cta;" ::: "memory");
            __syncwarp();
            if (lane == 0) mbar_arrive(bars + B_FREE * 8);
            if (st < 82) *(st < 64 ? &g_e4[cta][st] : st < 80 ? &g_e5[cta][st - 64] : &g_l5[h][j * 2 + st - 80]) = make_uint4(EMPTY, EMPTY, EMPTY, EMPTY);
            else if (st < 84) ((uint4*)out)[cta * 2 + st - 82] = make_uint4(0u, 0u, 0u, 0u);
        }
        bar_sync(2, 256);
        if (st == 0) {
            TS(12);
#pragma unroll 1
            for (int k = 0; k < ST_SPLIT; k++) {
                asm volatile("cp.async.bulk.tensor.3d.global.shared::cta.bulk_group [%0, {%2,%3,%4}], [%1];"
                             ::"l"(&maps.ctxp), "r"(sm + OFF_S2 + k * (2 * CH / ST_SPLIT)), "r"(0), "r"(cta), "r"(k * (128 / ST_SPLIT)) : "memory");
                if (k + 1 < ST_SPLIT) __nanosleep(ST_GAP);
            }
            asm volatile("cp.async.bulk.commit_group;" ::: "memory");
            asm volatile("cp.async.bulk.wait_group 0;" ::: "memory");
            cnt_rendezvous(&g_cnt[1], tag * 128u, 20);
            TS(13);
            mbar_expect(bars + B_GATH * 8, 2 * CH + 512);
            bulk1d_n(sm + OFF_LSE, g_lse + h * 32, 512, bars + B_GATH * 8);
#pragma unroll 1
            for (int k = 0; k < G_SPLIT; k++) {
                bulk1d_n(sm + OFF_S2 + k * (2 * CH / G_SPLIT), g_ctxp + cta * 2048 + k * (2048 / G_SPLIT), 2 * CH / G_SPLIT, bars + B_GATH * 8);
                if (k + 1 < G_SPLIT) __nanosleep(G_GAP);
            }
        }
        __syncwarp();
        {
            mbar_wait(bars + B_GATH * 8, 1);
            if (st == 0) TS(22);
            uint4 v[8];
#pragma unroll
            for (int k = 0; k < 8; k++) v[k] = lds128(sm + OFF_S2 + (k * 256 + st) * 16);
            float ls[4];
#pragma unroll
            for (int k = 0; k < 4; k++) ls[k] = ldsf(sm + OFF_LSE + (k * 32 + lane) * 4);
            float m0 = fmaxf(ls[0], ls[1]), m1 = fmaxf(ls[2], ls[3]);
#pragma unroll
            for (int o = 16; o; o >>= 1) { m0 = fmaxf(m0, __shfl_xor_sync(0xffffffffu, m0, o)); m1 = fmaxf(m1, __shfl_xor_sync(0xffffffffu, m1, o)); }
            ls[0] = ex2(ls[0] - m0); ls[1] = ex2(ls[1] - m0); ls[2] = ex2(ls[2] - m1); ls[3] = ex2(ls[3] - m1);
            float z0 = ls[0] + ls[1], z1 = ls[2] + ls[3];
#pragma unroll
            for (int o = 16; o; o >>= 1) { z0 += __shfl_xor_sync(0xffffffffu, z0, o); z1 += __shfl_xor_sync(0xffffffffu, z1, o); }
            z0 = __fdividef(1.f, z0); z1 = __fdividef(1.f, z1);
            ls[0] *= z0; ls[1] *= z0; ls[2] *= z1; ls[3] *= z1;
            float a[2][8];
#pragma unroll
            for (int e = 0; e < 8; e++) a[0][e] = a[1][e] = 0.f;
            const int rg = st >> 4;
#pragma unroll
            for (int k = 0; k < 8; k++) {
                const float wt = __shfl_sync(0xffffffffu, ls[k >> 1], rg + 16 * (k & 1));
                const uint32_t u[4] = {v[k].x, v[k].y, v[k].z, v[k].w};
#pragma unroll
                for (int e = 0; e < 4; e++) {
                    a[k >> 2][2 * e] += wt * __uint_as_float(u[e] << 16);
                    a[k >> 2][2 * e + 1] += wt * __uint_as_float(u[e] & 0xffff0000u);
                }
            }
            const int b = lane >> 4, u16 = lane & 15;
            const uint32_t ra = sm + OFF_SC + (w * 256 + b * 128 + (u16 >> 3) * 64 + ((u16 >> 2) & 1) * 32 + (u16 & 3) * 2) * 4;
#pragma unroll
            for (int e = 0; e < 8; e += 2) {
                const float k0 = b ? a[1][e] : a[0][e], k1 = b ? a[1][e + 1] : a[0][e + 1];
                const float s0 = b ? a[0][e] : a[1][e], s1 = b ? a[0][e + 1] : a[1][e + 1];
                stsf2(ra + (e >> 1) * 32, k0 + __shfl_xor_sync(0xffffffffu, s0, 16), k1 + __shfl_xor_sync(0xffffffffu, s1, 16));
            }
            bar_sync(2, 256);
            if (st == 0) mbar_arrive(bars + B_S2 * 8);
            float s = 0.f;
#pragma unroll
            for (int k = 0; k < 8; k++) s += ldsf(sm + OFF_SC + (k * 256 + st) * 4);
            const float hi = bfround(s);
            const uint32_t ca = sm + OFF_CC + (st >> 7) * VROW + (st & 127) * 2;
            sts16(ca, f2bf(hi)); sts16(ca + 2 * VROW, f2bf(s - hi));
            bar_sync(2, 256);
        }
        matvecT(c, sm + OFF_S1, sm + OFF_CC, 4, bars + B_WUV * 8, w, lane);
#pragma unroll
        for (int k = 0; k < 4; k++) c[k] += __shfl_down_sync(0xffffffffu, c[k], 1);
        if (t == 0) {
            float* const e = (float*)g_e4[cta] + w * 16 + g;
            mail_put(e, c[0]); mail_put(e + 128, c[1]); mail_put(e + 8, c[2]); mail_put(e + 136, c[3]);
        }
        __syncwarp();
        if (lane == 0) mbar_arrive(bars + B_FREE * 8);
        if (st == 0) TS(23);
        {
            const uint4* const pv = &g_e4[(cta & ~15) + (w >> 1) * 4][(w & 1) * 32 + lane];
            uint4 x[4];
            uint32_t it = 0;
            sleep_ns(POLL_DELAY2);
            while (true) {
#pragma unroll
                for (int k = 0; k < 4; k++) { x[k].x = x[k].y = x[k].z = x[k].w = 0u; mail_get(x[k], pv + k * 64); }
                if (!__any_sync(0xffffffffu, mail_missing(x[0]) | mail_missing(x[1]) | mail_missing(x[2]) | mail_missing(x[3]))) break;
                if (++it > SPIN_MAX) __trap();
                __nanosleep(BACKOFF);
            }
#define SUM4(e) ((__uint_as_float(x[0].e) + __uint_as_float(x[1].e)) + (__uint_as_float(x[2].e) + __uint_as_float(x[3].e)))
            sts64(sm + OFF_CA + w * VROW + lane * 8, pack2(SUM4(x), SUM4(y)), pack2(SUM4(z), SUM4(w)));
#undef SUM4
        }
        if (st == 0) TS(14);
        bar_sync(4, 256 + 128);
        {
            const uint32_t a0 = sm + OFF_S0 + w * 1024 + (rr + 8 * (i >> 1)) * 64 + (((i & 1) ^ (rr >> 1)) << 4);
            const uint4* const pv = pin(&g_e5[(cta & ~15) + (w >> 1) * 4 + (g & 3)][(w & 1) * 8 + (g >> 2) * 4 + t]);
            const uint32_t* const pl = pin((const uint32_t*)g_l5[(h & ~3) + (w >> 1)] + t);
            const uint32_t wa = sm + OFF_SC + ((w * 2 + (t >> 1)) * 80 + (t & 1) * 40 + g) * 4;
            __nv_bfloat16* const outp = pin(out + (lane >> 4) * 1024 + 512 + (cta & 15) * 32 + (lane & 15) * 2);
            uint32_t a[4][2][4], xl = 0u, it = 0;
            uint4 x = make_uint4(0u, 0u, 0u, 0u);
            while (true) {
                if (lane < 4) asm volatile("atom.relaxed.gpu.global.or.b32 %0, [%1], 0;" : "=r"(xl) : "l"(pl) : "memory");
                if (!__any_sync(0xffffffffu, xl == EMPTY)) break;
                if (++it > SPIN_MAX) __trap();
            }
            if (st == 0) TS(25);
            mail_get(x, pv);
            float w0, w1;
            merge_weights(__shfl_sync(0xffffffffu, xl, (t & 1) * 2), __shfl_sync(0xffffffffu, xl, (t & 1) * 2 + 1), w0, w1);
#pragma unroll
            for (int q = 0; q < 4; q++) {
                mbar_wait(bars + (B_WO + q) * 8, 0);
                ldsm4t(a[q][0], a0 + q * 8192);
                ldsm4t(a[q][1], (a0 ^ 32) + q * 8192);
            }
            if (st == 0) TS(26);
            while (true) {
                const bool n = mail_missing(x);
                if (!__any_sync(0xffffffffu, n)) break;
                mail_get(x, pv, n);
                if (++it > SPIN_MAX) __trap();
            }
            if (st == 0) TS(16);
            float d[2][2][4];
#pragma unroll
            for (int k = 0; k < 4; k++) {
                float (&dk)[4] = d[k >> 1][k & 1];
                dk[0] = dk[1] = dk[2] = dk[3] = 0.f;
                mma(dk, a[k >> 1][k & 1], x.x, x.y);
            }
#pragma unroll
            for (int k = 0; k < 4; k++) mma(d[k >> 1][k & 1], a[2 + (k >> 1)][k & 1], x.z, x.w);
#pragma unroll
            for (int k = 0; k < 4; k++) {
                const float s0 = (t & 2) ? d[1][k >> 1][(k & 1) * 2] : d[0][k >> 1][(k & 1) * 2];
                const float s1 = (t & 2) ? d[1][k >> 1][(k & 1) * 2 + 1] : d[0][k >> 1][(k & 1) * 2 + 1];
                sts32(wa + k * 32, __float_as_uint(w0 * s0 + w1 * s1));
            }
            if (st == 0) TS(17);
            if (w == 0) {
                bar_sync(5, 256);
                const uint32_t ra = sm + OFF_SC + ((lane >> 4) * 40 + (lane & 15) * 2) * 4;
                float2 r[16];
#pragma unroll
                for (int k = 0; k < 16; k++) r[k] = ldsf2(ra + k * 320);
#pragma unroll
                for (int o = 1; o < 16; o <<= 1)
#pragma unroll
                    for (int k = 0; k < 16; k += 2 * o) { r[k].x += r[k + o].x; r[k].y += r[k + o].y; }
                out_add(outp, r[0].x, r[0].y);
            } else {
                bar_arrive(5, 256);
            }
        }
    }
}

typedef CUresult (*EncodeFn)(CUtensorMap*, CUtensorMapDataType, cuuint32_t, void*, const cuuint64_t*, const cuuint64_t*,
                             const cuuint32_t*, const cuuint32_t*, CUtensorMapInterleave, CUtensorMapSwizzle,
                             CUtensorMapL2promotion, CUtensorMapFloatOOBfill);

void make_map(EncodeFn enc, CUtensorMap* m, void* p, unsigned rows, unsigned cols, unsigned br, unsigned bg) {
    cuuint64_t gd[3] = {64, rows, cols / 64};
    cuuint64_t gs[2] = {(cuuint64_t)cols * 2, 128};
    cuuint32_t bx[3] = {64, br, bg};
    cuuint32_t es[3] = {1, 1, 1};
    enc(m, CU_TENSOR_MAP_DATA_TYPE_BFLOAT16, 3, p, gd, gs, bx, es, CU_TENSOR_MAP_INTERLEAVE_NONE,
        CU_TENSOR_MAP_SWIZZLE_128B, CU_TENSOR_MAP_L2_PROMOTION_L2_128B, CU_TENSOR_MAP_FLOAT_OOB_FILL_NONE);
}

}

extern "C" void kernel_launch(void* const* d_in, const int* in_sizes, int n_in, void* d_out, int out_size) {
    static EncodeFn enc = nullptr;
    if (!enc) {
        void* fn = nullptr;
        cudaDriverEntryPointQueryResult qr;
        cudaGetDriverEntryPoint("cuTensorMapEncodeTiled", &fn, cudaEnableDefault, &qr);
        enc = (EncodeFn)fn;
        cudaFuncSetAttribute(fused_decode_kernel, cudaFuncAttributeMaxDynamicSharedMemorySize, SMEM_BYTES);
    }
    Maps maps;
    make_map(enc, &maps.wqB, d_in[9], 512, 4096, 64, 2);
    make_map(enc, &maps.wqA, d_in[2], 512, 4096, 64, 2);
    make_map(enc, &maps.wuk, d_in[3], 512, 4096, 64, 2);
    make_map(enc, &maps.wuv, d_in[4], 512, 4096, 64, 2);
    for (int k = 0; k < 2; k++) {
        cuuint64_t gd[3] = {512, 128, 32};
        cuuint64_t gs[2] = {1024, 131072};
        cuuint32_t bx[3] = {32, 32, 4};
        cuuint32_t es[3] = {1, 1, 1};
        enc(&maps.woB + k, CU_TENSOR_MAP_DATA_TYPE_BFLOAT16, 3, d_in[k ? 5 : 10], gd, gs, bx, es, CU_TENSOR_MAP_INTERLEAVE_NONE,
            CU_TENSOR_MAP_SWIZZLE_64B, CU_TENSOR_MAP_L2_PROMOTION_L2_256B, CU_TENSOR_MAP_FLOAT_OOB_FILL_NONE);
    }
    make_map(enc, &maps.ckv, d_in[1], 8192, 512, 16, 8);
    {
        void* p = nullptr;
        cudaGetSymbolAddress(&p, g_ctxp);
        cuuint64_t gd[3] = {128, 128, 128};
        cuuint64_t gs[2] = {256, 32768};
        cuuint32_t bx[3] = {128, 1, 128 / ST_SPLIT};
        cuuint32_t es[3] = {1, 1, 1};
        enc(&maps.ctxp, CU_TENSOR_MAP_DATA_TYPE_BFLOAT16, 3, p, gd, gs, bx, es, CU_TENSOR_MAP_INTERLEAVE_NONE,
            CU_TENSOR_MAP_SWIZZLE_NONE, CU_TENSOR_MAP_L2_PROMOTION_NONE, CU_TENSOR_MAP_FLOAT_OOB_FILL_NONE);
    }
    fused_decode_kernel<<<NCTA, NTHREADS, SMEM_BYTES>>>((const char*)d_in[9], maps, (const char*)d_in[7], (const char*)d_in[8],
                                                         (const __nv_bfloat16*)d_in[0], (const __nv_bfloat16*)d_in[6],
                                                         (__nv_bfloat16*)d_out, 0u);
}
```

```cpp
#include <cuda_runtime.h>
#include <cuda.h>
#include <cuda_bf16.h>
#include <stdint.h>

#define RING 7
#define WIN 4
#define WHI 5
#define THETA 64
#define END_V 40
#define GATE_W 64
#define PREWIN 2
#define TAILWIN 3
#define POLL_DELAY 2500
#define POLL_DELAY2 4000
#define ST_SPLIT 16
#define ST_GAP 300
#define G_SPLIT 8
#define G_GAP 500
#define BACKOFF 200
#define BACKOFF2 100

namespace {

constexpr int NCTA = 128;
constexpr int NTHREADS = 448;
constexpr uint32_t CH = 16384;
constexpr int NTILE = 32;
constexpr int RUN = 4;

constexpr uint32_t OFF_RING = 0;
constexpr uint32_t OFF_S0 = RING * CH;
constexpr uint32_t OFF_S1 = OFF_S0 + 2 * CH;
constexpr uint32_t OFF_S2 = OFF_S1 + 2 * CH;
constexpr uint32_t OFF_P = OFF_S2 + 2 * CH;
constexpr uint32_t OFF_SC = OFF_P + 4096;
constexpr uint32_t VROW = 272;
constexpr uint32_t OFF_XB = OFF_SC + 8704;
constexpr uint32_t OFF_XA = OFF_XB + 2 * VROW;
constexpr uint32_t OFF_QA = OFF_XA + 2 * VROW;
constexpr uint32_t OFF_QS = OFF_QA + 2 * VROW;
constexpr uint32_t OFF_CC = OFF_QS + 2 * VROW;
constexpr uint32_t OFF_CA = OFF_P;
constexpr uint32_t OFF_QB = OFF_CC + 4 * VROW;
constexpr uint32_t OFF_LSE = OFF_QB + 256;
constexpr uint32_t OFF_ML = OFF_LSE + 512;
constexpr uint32_t OFF_TAG = OFF_ML + 32;
constexpr uint32_t OFF_NOW = OFF_TAG + 4;
constexpr uint32_t OFF_WIN = OFF_TAG + 8;
constexpr uint32_t OFF_TWIN = OFF_TAG + 12;
constexpr uint32_t OFF_BAR = OFF_TAG + 16;
constexpr int B_EMPTY = RING;
constexpr int B_WQB = 2 * RING;
constexpr int B_WQA = B_WQB + 2;
constexpr int B_WUK = B_WQA + 2;
constexpr int B_WUV = B_WUK + 2;
constexpr int B_CKV = B_WUV + 2;
constexpr int B_WO = B_CKV + 4;
constexpr int B_FREE = B_WO + 8;
constexpr int B_GATH = B_FREE + 1;
constexpr int B_S2 = B_GATH + 1;
constexpr int NBAR = B_S2 + 1;
constexpr uint32_t TS_OFF = OFF_BAR + NBAR * 8;
constexpr uint32_t SMEM_USED = TS_OFF;
constexpr uint32_t SMEM_BYTES = SMEM_USED + 1024;
static_assert(SMEM_BYTES <= 232448, "smem");
static_assert(RING >= RUN && RING >= WHI && WHI >= WIN && WIN >= 3 && WIN <= 6, "windows");

constexpr float LOG2E = 1.4426950408889634f;
constexpr float SCALE = 0.08838834764831845f;
#define SPIN_LOG 22
constexpr uint32_t SPIN_MAX = 1u << SPIN_LOG;

struct Maps { CUtensorMap wqB, wqA, wuk, wuv, woB, woA, ckv, ctxp; };

__device__ __align__(256) unsigned g_cnt[32];
__device__ __align__(256) ulonglong2 g_e1[2][NCTA][128];
__device__ __align__(256) uint4 g_qabs[2 * 32 * 64];
__device__ __align__(256) uint4 g_ctxp[NCTA * 128 * 16];
__device__ __align__(256) float4 g_lse[32 * 32];
__device__ __align__(256) uint4 g_e4[NCTA][64];
__device__ __align__(256) uint4 g_e5[NCTA][16];
__device__ __align__(256) uint4 g_l5[32][8];
constexpr uint32_t EMPTY = 0xffffffffu;

#define TS(k) do {} while (0)

__device__ __forceinline__ void mbar_init(uint32_t b, int c) { asm volatile("mbarrier.init.shared::cta.b64 [%0], %1;" ::"r"(b), "r"(c) : "memory"); }
__device__ __forceinline__ void mbar_expect(uint32_t b, uint32_t bytes) { asm volatile("mbarrier.arrive.expect_tx.shared::cta.b64 _, [%0], %1;" ::"r"(b), "r"(bytes) : "memory"); }
__device__ __forceinline__ void mbar_arrive(uint32_t b) { asm volatile("mbarrier.arrive.shared::cta.b64 _, [%0];" ::"r"(b) : "memory"); }
__device__ __forceinline__ void mbar_wait(uint32_t b, uint32_t ph) {
    asm volatile("{\n.reg .pred p;\n.reg .u32 n;\nmov.u32 n, 0;\n"
                 "W:\nmbarrier.try_wait.parity.shared::cta.b64 p, [%0], %1;\n@p bra D;\n"
                 "add.u32 n, n, 1;\nsetp.le.u32 p, n, %2;\n@p bra W;\ntrap;\nD:\n}" ::"r"(b), "r"(ph), "n"(SPIN_MAX) : "memory");
}
__device__ __forceinline__ uint32_t mbar_test(uint32_t b, uint32_t ph) {
    uint32_t ok;
    asm volatile("{\n.reg .pred p;\nmbarrier.test_wait.parity.shared::cta.b64 p, [%1], %2;\nselp.u32 %0, 1, 0, p;\n}" : "=r"(ok) : "r"(b), "r"(ph) : "memory");
    return ok;
}
__device__ __forceinline__ void bulk1d(uint32_t dst, const void* src, uint32_t bar, uint64_t pol) {
    asm volatile("cp.async.bulk.shared::cluster.global.mbarrier::complete_tx::bytes.L2::cache_hint [%0], [%1], %2, [%3], %4;"
                 ::"r"(dst), "l"(src), "n"(CH), "r"(bar), "l"(pol) : "memory");
}
__device__ __forceinline__ void bulk1d_n(uint32_t dst, const void* src, uint32_t bytes, uint32_t bar) {
    asm volatile("cp.async.bulk.shared::cluster.global.mbarrier::complete_tx::bytes [%0], [%1], %2, [%3];"
                 ::"r"(dst), "l"(src), "r"(bytes), "r"(bar) : "memory");
}
__device__ __forceinline__ void tma3d(uint32_t dst, const CUtensorMap* map, int c1, int c2, uint32_t bar, uint64_t pol, int c0 = 0) {
    asm volatile("cp.async.bulk.tensor.3d.shared::cluster.global.mbarrier::complete_tx::bytes.L2::cache_hint [%0], [%1, {%3,%4,%5}], [%2], %6;"
                 ::"r"(dst), "l"(map), "r"(bar), "r"(c0), "r"(c1), "r"(c2), "l"(pol) : "memory");
}
__device__ __forceinline__ void bar_sync(int id, int n) { asm volatile("barrier.cta.sync %0, %1;" ::"r"(id), "r"(n) : "memory"); }
__device__ __forceinline__ void bar_arrive(int id, int n) { asm volatile("barrier.cta.arrive %0, %1;" ::"r"(id), "r"(n) : "memory"); }
__device__ __forceinline__ void ldsm4(uint32_t (&r)[4], uint32_t a) {
    asm volatile("ldmatrix.sync.aligned.m8n8.x4.shared.b16 {%0,%1,%2,%3}, [%4];" : "=r"(r[0]), "=r"(r[1]), "=r"(r[2]), "=r"(r[3]) : "r"(a) : "memory");
}
__device__ __forceinline__ void ldsm4t(uint32_t (&r)[4], uint32_t a) {
    asm volatile("ldmatrix.sync.aligned.m8n8.x4.trans.shared.b16 {%0,%1,%2,%3}, [%4];" : "=r"(r[0]), "=r"(r[1]), "=r"(r[2]), "=r"(r[3]) : "r"(a) : "memory");
}
__device__ __forceinline__ void mma(float (&c)[4], const uint32_t (&a)[4], uint32_t b0, uint32_t b1) {
    asm volatile("mma.sync.aligned.m16n8k16.row.col.f32.bf16.bf16.f32 {%0,%1,%2,%3}, {%4,%5,%6,%7}, {%8,%9}, {%0,%1,%2,%3};"
                 : "+f"(c[0]), "+f"(c[1]), "+f"(c[2]), "+f"(c[3]) : "r"(a[0]), "r"(a[1]), "r"(a[2]), "r"(a[3]), "r"(b0), "r"(b1));
}
__device__ __forceinline__ uint32_t lds32(uint32_t a) { uint32_t v; asm volatile("ld.shared.b32 %0, [%1];" : "=r"(v) : "r"(a) : "memory"); return v; }
__device__ __forceinline__ uint32_t ldsv(uint32_t a) { uint32_t v; asm volatile("ld.volatile.shared.b32 %0, [%1];" : "=r"(v) : "r"(a) : "memory"); return v; }
__device__ __forceinline__ void stsv(uint32_t a, uint32_t v) { asm volatile("st.volatile.shared.b32 [%0], %1;" ::"r"(a), "r"(v) : "memory"); }
__device__ __forceinline__ float ldsf(uint32_t a) { float v; asm volatile("ld.shared.f32 %0, [%1];" : "=f"(v) : "r"(a) : "memory"); return v; }
__device__ __forceinline__ uint4 lds128(uint32_t a) { uint4 v; asm volatile("ld.shared.v4.b32 {%0,%1,%2,%3}, [%4];" : "=r"(v.x), "=r"(v.y), "=r"(v.z), "=r"(v.w) : "r"(a) : "memory"); return v; }
__device__ __forceinline__ void sts16(uint32_t a, uint16_t v) { asm volatile("st.shared.b16 [%0], %1;" ::"r"(a), "h"(v) : "memory"); }
__device__ __forceinline__ void sts32(uint32_t a, uint32_t v) { asm volatile("st.shared.b32 [%0], %1;" ::"r"(a), "r"(v) : "memory"); }
__device__ __forceinline__ void stsf2(uint32_t a, float x, float y) { asm volatile("st.shared.v2.f32 [%0], {%1,%2};" ::"r"(a), "f"(x), "f"(y) : "memory"); }
__device__ __forceinline__ void sts128(uint32_t a, uint4 v) { asm volatile("st.shared.v4.b32 [%0], {%1,%2,%3,%4};" ::"r"(a), "r"(v.x), "r"(v.y), "r"(v.z), "r"(v.w) : "memory"); }
__device__ __forceinline__ uint16_t f2bf(float x) { return __bfloat16_as_ushort(__float2bfloat16_rn(x)); }
__device__ __forceinline__ float bfround(float x) { return __bfloat162float(__float2bfloat16_rn(x)); }
__device__ __forceinline__ uint32_t pack2(float lo, float hi) { uint32_t r; asm("cvt.rn.bf16x2.f32 %0, %1, %2;" : "=r"(r) : "f"(hi), "f"(lo)); return r; }
__device__ __forceinline__ float ex2(float x) { float r; asm("ex2.approx.ftz.f32 %0, %1;" : "=f"(r) : "f"(x)); return r; }
__device__ __forceinline__ float lg2(float x) { float r; asm("lg2.approx.ftz.f32 %0, %1;" : "=f"(r) : "f"(x)); return r; }

__device__ __forceinline__ float rcp(float x) { float r; asm("rcp.approx.ftz.f32 %0, %1;" : "=f"(r) : "f"(x)); return r; }
__device__ __forceinline__ void merge_weights(uint32_t l0, uint32_t l1, float& w0, float& w1) {
    const float a = __uint_as_float(l0), b = __uint_as_float(l1), mx = fmaxf(a, b), e0 = ex2(a - mx), e1 = ex2(b - mx), r = rcp(e0 + e1);
    w0 = e0 * r; w1 = e1 * r;
}

__device__ __forceinline__ void sleep_ns(uint32_t ns) {
    uint32_t t0, t;
    asm volatile("mov.u32 %0, %clock;" : "=r"(t0));
    do { __nanosleep(200); asm volatile("mov.u32 %0, %clock;" : "=r"(t)); } while (t - t0 < 2 * ns);
}

__device__ __forceinline__ void ll_store2(ulonglong2* p, float a, float b, uint32_t tag) {
    unsigned long long x = ((unsigned long long)tag << 32) | __float_as_uint(a);
    unsigned long long y = ((unsigned long long)tag << 32) | __float_as_uint(b);
    asm volatile("st.relaxed.gpu.global.v2.b64 [%0], {%1,%2};" ::"l"(p), "l"(x), "l"(y) : "memory");
}
__device__ __forceinline__ void ll_ld2(const void* p, unsigned long long& x, unsigned long long& y) {
    asm volatile("ld.relaxed.gpu.global.v2.b64 {%0,%1}, [%2];" : "=l"(x), "=l"(y) : "l"(p) : "memory");
}
__device__ __forceinline__ void ll_gather4(const ulonglong2* p, uint32_t tag, float& r0, float& r1) {
    unsigned long long x[4], y[4]; uint32_t it = 0;
    while (true) {
        bool ok = true;
#pragma unroll
        for (int k = 0; k < 4; k++) ll_ld2(p + k * 128, x[k], y[k]);
#pragma unroll
        for (int k = 0; k < 4; k++) ok = ok && (uint32_t)(x[k] >> 32) == tag && (uint32_t)(y[k] >> 32) == tag;
        if (ok) break;
        if (++it > SPIN_MAX) __trap();
        __nanosleep(BACKOFF);
    }
    r0 = (__uint_as_float((uint32_t)x[0]) + __uint_as_float((uint32_t)x[1])) + (__uint_as_float((uint32_t)x[2]) + __uint_as_float((uint32_t)x[3]));
    r1 = (__uint_as_float((uint32_t)y[0]) + __uint_as_float((uint32_t)y[1])) + (__uint_as_float((uint32_t)y[2]) + __uint_as_float((uint32_t)y[3]));
}
__device__ __forceinline__ void cnt_rendezvous(unsigned* c, uint32_t target, int tsk) {
    TS(tsk);
    asm volatile("red.release.gpu.global.add.u32 [%0], 1;" ::"l"(c) : "memory");
    if (tsk == 18) TS(tsk + 1);
    uint32_t v, it = 0;
    while (true) {
        asm volatile("ld.acquire.gpu.global.u32 %0, [%1];" : "=r"(v) : "l"(c) : "memory");
        if ((int)(v - target) >= 0) break;
        if (++it > SPIN_MAX) __trap();
        __nanosleep(BACKOFF);
    }
    asm volatile("fence.proxy.async.global;" ::: "memory");
}

__device__ __forceinline__ void matvec_loadA(uint32_t (&a)[8][4], uint32_t tile, uint32_t bar, int w, int lane) {
    const int i = lane >> 3, rr = lane & 7, chunk = 2 * w + (i & 1);
    const uint32_t a0 = tile + (chunk >> 3) * 8192 + (rr + 8 * (i >> 1)) * 128 + (((chunk & 7) ^ rr) << 4);
#pragma unroll
    for (int hh = 0; hh < 2; hh++) {
        mbar_wait(bar + hh * 8, 0);
#pragma unroll
        for (int k = 0; k < 4; k++) ldsm4t(a[hh * 4 + k], a0 + hh * CH + k * 2048);
    }
}
__device__ __forceinline__ void matvec_mma(float (&c)[4], const uint32_t (&a)[8][4], uint32_t vec, int nvec, int lane) {
    const uint32_t va = vec + (lane & (nvec - 1)) * VROW + (lane >> 3) * 16;
    float d[4][4];
#pragma unroll
    for (int q = 0; q < 4; q++) {
        uint32_t b[4];
        ldsm4(b, va + q * 64);
        d[q][0] = d[q][1] = d[q][2] = d[q][3] = 0.f;
        mma(d[q], a[2 * q], b[0], b[1]);
        mma(d[q], a[2 * q + 1], b[2], b[3]);
    }
#pragma unroll
    for (int k = 0; k < 4; k++) c[k] = (d[0][k] + d[1][k]) + (d[2][k] + d[3][k]);
}
__device__ __forceinline__ void matvecT(float (&c)[4], uint32_t tile, uint32_t vec, int nvec, uint32_t bar, int w, int lane) {
    uint32_t a[8][4];
    matvec_loadA(a, tile, bar, w, lane);
    matvec_mma(c, a, vec, nvec, lane);
}
template <class T> __device__ __forceinline__ T* pin(T* p) { asm volatile("" : "+l"(p)); return p; }
__device__ __forceinline__ void mail_put(void* p, uint32_t v) { asm volatile("st.relaxed.gpu.global.b32 [%0], %1;" ::"l"(p), "r"(v) : "memory"); }
__device__ __forceinline__ void mail_put(void* p, float v) { mail_put(p, __float_as_uint(v)); }
__device__ __forceinline__ void out_add(__nv_bfloat16* p, float x, float y) {
    asm volatile("red.relaxed.gpu.global.add.noftz.bf16x2 [%0], %1;" ::"l"(p), "r"(pack2(x, y)) : "memory");
}
__device__ __forceinline__ bool mail_missing(const uint4& v) { return v.x == EMPTY || v.y == EMPTY || v.z == EMPTY || v.w == EMPTY; }
__device__ __forceinline__ void mail_get(uint4& v, const uint4* p, bool need = true) {
    asm volatile("{\n.reg .pred q;\nsetp.ne.u32 q, %5, 0;\n@q ld.relaxed.gpu.global.v4.b32 {%0,%1,%2,%3}, [%4];\n}"
                 : "+r"(v.x), "+r"(v.y), "+r"(v.z), "+r"(v.w) : "l"(p), "r"((uint32_t)need) : "memory");
}
__device__ __forceinline__ void sts64(uint32_t a, uint32_t x, uint32_t y) { asm volatile("st.shared.v2.b32 [%0], {%1,%2};" ::"r"(a), "r"(x), "r"(y) : "memory"); }
__device__ __forceinline__ float2 ldsf2(uint32_t a) { float2 v; asm volatile("ld.shared.v2.f32 {%0,%1}, [%2];" : "=f"(v.x), "=f"(v.y) : "r"(a) : "memory"); return v; }

__global__ void __launch_bounds__(NTHREADS, 1)
fused_decode_kernel(const char* __restrict__ wqraw, const __grid_constant__ Maps maps, const char* __restrict__ Kc, const char* __restrict__ Vc,
                    const __nv_bfloat16* __restrict__ xA, const __nv_bfloat16* __restrict__ xB,
                    __nv_bfloat16* __restrict__ out, const uint32_t zero) {
    if (threadIdx.x == 0) asm volatile("cp.async.bulk.prefetch.L2.global [%0], 32768;" ::"l"(wqraw + (size_t)blockIdx.x * 32768u) : "memory");
    asm volatile("nanosleep.u32 60;" ::: "memory");
    asm volatile("barrier.cta.sync.aligned 7, %0;" ::"n"(NTHREADS) : "memory");
    asm volatile("{\n.reg .pred p;\n.reg .u32 s;\nmov.u32 s, %smid;\nsetp.eq.u32 p, s, 0xffff;\n@p exit;\n}" ::: "memory");
    extern __shared__ char smem_raw[];
    const uint32_t sm = ((uint32_t)__cvta_generic_to_shared(smem_raw) + 1023u) & ~1023u;
    const uint32_t bars = sm + OFF_BAR;
    const int cta = blockIdx.x, h = cta >> 2, j = cta & 3;
    uint64_t pol = 0;
    if (threadIdx.x == 0) {
        TS(0);
        asm volatile("createpolicy.fractional.L2::evict_first.b64 %0, 1.0;" : "=l"(pol));
#pragma unroll
        for (int i = 0; i < WIN; i++) mbar_init(bars + (B_WQB + i) * 8, 1);
        asm volatile("fence.mbarrier_init.release.cluster;" ::: "memory");
#pragma unroll
        for (int i = 0; i < WIN; i++) {
            mbar_expect(bars + (B_WQB + i) * 8, CH);
            tma3d(sm + OFF_S0 + i * CH, &maps.wqB + (i >> 1), j * 128 + (i & 1) * 64, h * 2, bars + (B_WQB + i) * 8, pol);
        }
    }
    const int tid = threadIdx.x < 64 ? threadIdx.x + 384 : threadIdx.x - 64, warp = tid >> 5, lane = tid & 31;

    if (warp == 12) {
        const size_t kvoff = ((size_t)(((j >> 1) * 32 + h) * 4096 + (j & 1) * 2048)) * 256;
        const char* kp = Kc + kvoff;
        const char* vp = Vc + kvoff;
        __syncwarp();
        bar_arrive(0, NTHREADS);
        bar_sync(3, 64);
        if (lane == 0) {
            uint32_t pb[WHI];
#pragma unroll
            for (int i = 0; i < WHI; i++) pb[i] = i < WHI - WIN ? (bars + B_WO * 8) | 1u : bars + (B_WQB + i - (WHI - WIN)) * 8;
            auto pace = [&](uint32_t bar, uint32_t par, uint32_t wina) {
                uint32_t it = 0;
                while (true) {
                    const uint32_t win = ldsv(wina);
                    uint32_t busy = 0;
#pragma unroll
                    for (int i = 0; i < WHI; i++) busy += mbar_test(pb[i] & ~1u, pb[i] & 1u) ^ 1u;
                    if (busy < win) break;
                    if (++it > SPIN_MAX) __trap();
                }
#pragma unroll
                for (int i = 0; i + 1 < WHI; i++) pb[i] = pb[i + 1];
                pb[WHI - 1] = bar | par;
            };
            auto side = [&](const CUtensorMap* m, uint32_t dst, int bidx, int c1, int c2, uint32_t wina) {
                const uint32_t bar = bars + bidx * 8;
                pace(bar, 0, wina);
                mbar_expect(bar, CH);
                tma3d(dst, m, c1, c2, bar, pol);
            };
#pragma unroll 1
            for (int i = WIN; i < 6; i++)
                side(&maps.wqB + (i >> 1), sm + OFF_S0 + i * CH, B_WQB + i, j * 128 + (i & 1) * 64, h * 2, sm + OFF_WIN);
            TS(1);
            uint32_t slot = 0, use = 0;
            int nuv = 0;
#pragma unroll 1
            for (int n = 0; n < 2 * NTILE; n++) {
                if (n == RING) {
                    mbar_wait(bars + B_FREE * 8, 0);
#pragma unroll 1
                    for (int q = 0; q < 4; q++) side(&maps.ckv, sm + OFF_S0 + q * CH, B_CKV + q, cta * 64 + q * 16, 0, sm + OFF_WIN);
                }
                if (nuv < 2 && n > RING && (n >= 2 * NTILE - 8 || mbar_test(bars + B_FREE * 8, 1))) {
                    mbar_wait(bars + B_FREE * 8, 1);
                    side(&maps.wuv, sm + OFF_S1 + nuv * CH, B_WUV + nuv, j * 128 + nuv * 64, h * 2, sm + OFF_WIN);
                    nuv++;
                }
                const uint32_t fb = bars + slot * 8;
                pace(fb, use & 1, sm + OFF_WIN);
                mbar_wait(fb + B_EMPTY * 8, (use & 1) ^ 1);
                mbar_expect(fb, CH);
                bulk1d(sm + OFF_RING + slot * CH, ((n & RUN) ? vp : kp) + (size_t)(n / (2 * RUN) * RUN + n % RUN) * CH, fb, pol);
                if (((n + cta) & 3) == 0) asm volatile("red.relaxed.gpu.global.add.u32 [%0], 4;" ::"l"(&g_cnt[2]) : "memory");
                stsv(sm + OFF_NOW, n + 1);
                if (++slot == RING) { slot = 0; use++; }
            }
            TS(2);
            mbar_wait(bars + B_FREE * 8, 0);
#pragma unroll 1
            for (int i = 0; i < 4; i++) {
                const uint32_t bar = bars + (B_WO + 2 * i) * 8;
                pace(bar + 8, 0, sm + OFF_TWIN);
                TS(32 + i);
#pragma unroll
                for (int k = 0; k < 2; k++) {
                    mbar_expect(bar + k * 8, CH / 2);
                    tma3d(sm + OFF_S0 + i * CH + k * (CH / 2), &maps.woB + (i >> 1), (i & 1) * 64 + k * 32, h & ~3, bar + k * 8, pol, (cta & 15) * 32);
                }
            }
            TS(3);
        }
    } else if (warp == 13) {
        if (lane == 0) {
#pragma unroll
            for (int i = 0; i < NBAR; i++)
                if (i < B_WQB || i >= B_WQB + WIN)
                    mbar_init(bars + i * 8, i == B_FREE ? 8 : (i >= B_EMPTY && i < B_EMPTY + RING) ? 4 : 1);
            asm volatile("fence.mbarrier_init.release.cluster;" ::: "memory");
#pragma unroll
            for (int i = 2; i < 8; i++) asm volatile("prefetch.tensormap [%0];" ::"l"(&maps.wqB + i) : "memory");
            stsv(sm + OFF_NOW, 0); stsv(sm + OFF_WIN, WIN); stsv(sm + OFF_TWIN, PREWIN);
        }
        __syncwarp();
        bar_arrive(3, 64);
        bar_sync(0, NTHREADS);
        if (lane == 0) {
            const uint32_t base = (lds32(sm + OFF_TAG) - 1u) * (NCTA * 2 * NTILE);
            mbar_wait(bars + (B_WUK + 1) * 8, 0);
            uint32_t it = 0;
            while (true) {
                const uint32_t n = ldsv(sm + OFF_NOW);
                uint32_t v;
                asm volatile("ld.relaxed.gpu.global.u32 %0, [%1];" : "=r"(v) : "l"(&g_cnt[2]) : "memory");
                v -= base;
                if (v >= NCTA * 2 * NTILE - GATE_W) break;
                const int diff = (int)(n * NCTA) - (int)v;
                stsv(sm + OFF_WIN, diff < -THETA ? WHI : WIN - (diff > THETA) - (v >= NCTA * END_V));
                if (++it > SPIN_MAX) __trap();
                __nanosleep(BACKOFF2);
            }
            stsv(sm + OFF_WIN, WHI); stsv(sm + OFF_TWIN, TAILWIN);
            TS(24);
        }
    } else if (warp < 4) {
        const int g = lane >> 2, t = lane & 3, i = lane >> 3, rr = lane & 7;
        if (tid == 0) {
            unsigned e;
            asm volatile("ld.relaxed.gpu.global.u32 %0, [%1];" : "=r"(e) : "l"(&g_cnt[1]) : "memory");
            sts32(sm + OFF_TAG, (e >> 7) + 1u);
        }
        bar_sync(0, NTHREADS);
        const uint32_t tag = lds32(sm + OFF_TAG);
        {
            mbar_wait(bars + 8, 0);
            float q0, q1;
            ll_gather4(&g_e1[0][h * 4][tid], tag, q0, q1);
            sts16(sm + OFF_QB + tid * 2, f2bf((j >> 1) ? q1 : q0));
        }
        bar_sync(1, 128);
        if (tid == 0) TS(4);
        uint32_t qf[8][2];
#pragma unroll
        for (int c = 0; c < 8; c++) {
            const uint32_t a = sm + OFF_QB + (((c + g) & 7) * 8 + 2 * t) * 2;
            qf[c][0] = lds32(a); qf[c][1] = lds32(a + 128);
        }
        float acc[8][4];
#pragma unroll
        for (int c = 0; c < 8; c++) { acc[c][0] = acc[c][1] = acc[c][2] = acc[c][3] = 0.f; }
        float m = -INFINITY, l = 0.f;
        const bool diag = (t == (g >> 1));
        const uint32_t krow = sm + OFF_RING + (warp * 16 + rr + 8 * (i & 1)) * 256 + (i >> 1) * 128;
        const uint32_t vrow = sm + OFF_RING + (warp * 16 + rr + 8 * (i >> 1)) * 256 + (i & 1) * 128;
        uint32_t slot = 0, ph = 0;
        uint32_t* const e5own = pin((uint32_t*)g_e5[cta] + tid);
        uint32_t a[8][4] = {}, b0[RUN], b1[RUN];
        auto release = [&]() {
            __syncwarp();
            if (lane == 0) mbar_arrive(bars + (B_EMPTY + slot) * 8 + ((a[0][0] | a[1][0] | a[2][0] | a[3][0] | a[4][0] | a[5][0] | a[6][0] | a[7][0]) & zero));
            if (++slot == RING) { slot = 0; ph ^= 1; }
        };
        auto load_v = [&]() {
            mbar_wait(bars + slot * 8, ph);
#pragma unroll
            for (int c = 0; c < 8; c++) ldsm4t(a[c], vrow + slot * CH + (((c + rr) & 7) << 4));
        };
#pragma unroll 1
        for (int run = 0;; run++) {
            float slo[RUN], shi[RUN], mx = -INFINITY;
#pragma unroll
            for (int u = 0; u < RUN; u++) {
                mbar_wait(bars + slot * 8, ph);
#pragma unroll
                for (int c = 0; c < 8; c++) ldsm4(a[c], krow + slot * CH + (((c + rr) & 7) << 4));
                release();
                float s0[4] = {0.f, 0.f, 0.f, 0.f}, s1[4] = {0.f, 0.f, 0.f, 0.f};
#pragma unroll
                for (int c = 0; c < 8; c += 2) { mma(s0, a[c], qf[c][0], qf[c][1]); mma(s1, a[c + 1], qf[c + 1][0], qf[c + 1][1]); }
                slo[u] = diag ? bfround(bfround((g & 1) ? s0[1] + s1[1] : s0[0] + s1[0]) * SCALE) : -INFINITY;
                shi[u] = diag ? bfround(bfround((g & 1) ? s0[3] + s1[3] : s0[2] + s1[2]) * SCALE) : -INFINITY;
                mx = fmaxf(mx, fmaxf(slo[u], shi[u]));
            }
            int key = __float_as_int(mx);
            key ^= (key >> 31) & 0x7fffffff;
            key = __reduce_max_sync(0xffffffffu, key);
            key ^= (key >> 31) & 0x7fffffff;
            const float mn = fmaxf(m, __int_as_float(key));
            const float alpha = ex2((m - mn) * LOG2E);
            m = mn;
            l *= alpha;
#pragma unroll
            for (int u = 0; u < RUN; u++) {
                const float plo = ex2((slo[u] - mn) * LOG2E), phi = ex2((shi[u] - mn) * LOG2E);
                l += plo + phi;
                b0[u] = (g & 1) ? pack2(0.f, plo) : pack2(plo, 0.f);
                b1[u] = (g & 1) ? pack2(0.f, phi) : pack2(phi, 0.f);
            }
#pragma unroll
            for (int c = 0; c < 8; c++) { acc[c][0] *= alpha; acc[c][1] *= alpha; acc[c][2] *= alpha; acc[c][3] *= alpha; }
            if (run == NTILE / RUN - 1) break;
#pragma unroll
            for (int u = 0; u < RUN; u++) {
                load_v();
                release();
#pragma unroll
                for (int c = 0; c < 8; c++) mma(acc[c], a[c], b0[u], b1[u]);
            }
        }
#pragma unroll
        for (int o = 16; o; o >>= 1) l += __shfl_xor_sync(0xffffffffu, l, o);
        if (lane == 0) stsf2(sm + OFF_ML + warp * 8, m, l);
        mbar_wait(bars + B_S2 * 8, 0);
        bar_sync(1, 128);
        {
            const uint4 ml0 = lds128(sm + OFF_ML), ml1 = lds128(sm + OFF_ML + 16);
            const float m0 = __uint_as_float(ml0.x), m1 = __uint_as_float(ml0.z), m2 = __uint_as_float(ml1.x), m3 = __uint_as_float(ml1.z);
            const float M = fmaxf(fmaxf(m0, m1), fmaxf(m2, m3));
            const float L = (ex2((m0 - M) * LOG2E) * __uint_as_float(ml0.y) + ex2((m1 - M) * LOG2E) * __uint_as_float(ml0.w))
                          + (ex2((m2 - M) * LOG2E) * __uint_as_float(ml1.y) + ex2((m3 - M) * LOG2E) * __uint_as_float(ml1.w));
            const float f = ex2((m - M) * LOG2E) * rcp(L);
            const float lse = M * LOG2E + lg2(L);
            float* const l5own = pin((float*)g_l5[h] + j);
            const uint32_t wa = sm + OFF_S2 + warp * 640 + (t * 16 + (t >> 1) * 8 + g) * 4;
            const uint32_t ra = sm + OFF_S2 + ((tid >> 4 & 1) * 40 + (tid & 2) * 40 + (tid >> 5) * 16 + (tid & 1) * 8 + (tid >> 2 & 3) * 2) * 4;
#pragma unroll
            for (int u = 0; u < RUN; u++) {
                load_v();
                if (++slot == RING) { slot = 0; ph ^= 1; }
                if (u == RUN - 1 && tid == 96) mail_put(l5own, lse);
#pragma unroll
                for (int c = 0; c < 8; c++) mma(acc[c], a[c], b0[u], b1[u]);
            }
            if (tid == 0) TS(5);
            float v[2][8];
#pragma unroll
            for (int c = 0; c < 8; c++) { v[0][c] = acc[c][0] + acc[(c + 7) & 7][1]; v[1][c] = acc[c][2] + acc[(c + 7) & 7][3]; }
#pragma unroll
            for (int c = 0; c < 4; c++) { v[0][c] += __shfl_xor_sync(0xffffffffu, v[0][c + 4], 2); v[1][c] += __shfl_xor_sync(0xffffffffu, v[1][c + 4], 2); }
            const int src = (lane & ~3) | ((lane + 3) & 3);
#pragma unroll
            for (int c = 0; c < 2; c++) { v[0][c] += __shfl_sync(0xffffffffu, v[0][c + 2], src); v[1][c] += __shfl_sync(0xffffffffu, v[1][c + 2], src); }
#pragma unroll
            for (int c = 0; c < 4; c++) sts32(wa + (c >> 1) * 320 + (c & 1) * 32, __float_as_uint(v[c >> 1][c & 1] * f));
            if (warp < 2) {
                bar_sync(1, 128);
                const float2 r0 = ldsf2(ra), r1 = ldsf2(ra + 640), r2 = ldsf2(ra + 1280), r3 = ldsf2(ra + 1920);
                mail_put(e5own, pack2((r0.x + r1.x) + (r2.x + r3.x), (r0.y + r1.y) + (r2.y + r3.y)));
            } else {
                bar_arrive(1, 128);
            }
        }
        if (tid == 0) TS(6);
        {
            uint32_t x[4][4][4];
            float d[4][4];
            bar_sync(4, 256 + 128);
#pragma unroll
            for (int k = 0; k < 16; k++) ldsm4(x[k >> 2][k & 3], sm + OFF_CA + ((k >> 2) * 2 + (lane & 1)) * VROW + (k & 3) * 64 + (i & 1) * 32 + (i >> 1) * 16);
#pragma unroll
            for (int k = 0; k < 4; k++) d[k][0] = d[k][1] = d[k][2] = d[k][3] = 0.f;
            const uint32_t wa = sm + OFF_S1 + lane * 64 + ((warp ^ (rr >> 1)) << 4);
            __nv_bfloat16* const outp = pin(out + (g & 1) * 1024 + (cta & 15) * 32 + warp * 8 + t * 2);
#pragma unroll
            for (int q = 0; q < 4; q += 2) {
#pragma unroll
                for (int k = 0; k < 8; k++) {
                    if (!(k & 3)) mbar_wait(bars + (B_WO + 4 + q + (k >> 2)) * 8, 0);
                    ldsm4t(a[k], wa + q * 8192 + k * 2048);
                }
#pragma unroll
                for (int k = 0; k < 16; k++) mma(d[k & 3], x[(k >> 1) & 3][q + (k >> 3)], a[k >> 1][(k & 1) * 2], a[k >> 1][(k & 1) * 2 + 1]);
            }
            if (lane < 8) out_add(outp, (d[0][0] + d[1][2]) + (d[2][0] + d[3][2]), (d[0][1] + d[1][3]) + (d[2][1] + d[3][3]));
            if (tid == 0) TS(15);
        }
    } else {
        const int st = tid - 128, w = warp - 4;
        const int g = lane >> 2, t = lane & 3, i = lane >> 3, rr = lane & 7;
        if (t == 0) {
#pragma unroll
            for (int k = 0; k < 4; k++) ll_store2(&g_e1[k >> 1][cta][w * 16 + g + (k & 1) * 8], 0.f, 0.f, 0u);
        }
        if (st < 64) {
            const int which = st >> 5, b = (st >> 4) & 1, c = st & 15;
            const uint4 v = __ldg((const uint4*)((which ? xA : xB) + b * 512 + j * 128) + c);
            sts128(sm + OFF_XB + (which * 2 + b) * VROW + c * 16, v);
        }
        bar_sync(0, NTHREADS);
        const uint32_t tag = lds32(sm + OFF_TAG);
        float c[4];
#pragma unroll 1
        for (int which = 0; which < 2; which++) {
            matvecT(c, sm + OFF_S0 + which * 2 * CH, sm + OFF_XB + which * 2 * VROW, 2, bars + (B_WQB + which * 2) * 8, w, lane);
            if (t == 0) {
                ll_store2(&g_e1[which][cta][w * 16 + g], c[0], c[1], tag);
                ll_store2(&g_e1[which][cta][w * 16 + g + 8], c[2], c[3], tag);
            }
        }
        __syncwarp();
        if (lane == 0) mbar_arrive(bars + B_FREE * 8);
        if (st == 0) TS(8);
        if (st < 128) {
            float q0, q1;
            sleep_ns(POLL_DELAY);
            ll_gather4(&g_e1[1][h * 4][st], tag, q0, q1);
            sts16(sm + OFF_QA + st * 2, f2bf(q0)); sts16(sm + OFF_QA + VROW + st * 2, f2bf(q1));
        }
        bar_sync(2, 256);
        if (st == 0) TS(9);
        {
            const int row = w * 16 + rr + 8 * (i & 1);
            const uint32_t a0 = sm + OFF_S2 + (row >> 6) * CH + (row & 63) * 128;
            const uint32_t va = sm + OFF_QA + g * VROW + t * 4;
            float d[4] = {0.f, 0.f, 0.f, 0.f};
            c[0] = c[1] = c[2] = c[3] = 0.f;
            mbar_wait(bars + (B_WUK + (w >> 2)) * 8, 0);
#pragma unroll
            for (int ks = 0; ks < 8; ks++) {
                const int chunk = 2 * ks + (i >> 1);
                uint32_t a[4];
                ldsm4(a, a0 + (chunk >> 3) * 8192 + (((chunk & 7) ^ rr) << 4));
                const uint32_t b0 = (g < 2) ? lds32(va + ks * 32) : 0u, b1 = (g < 2) ? lds32(va + ks * 32 + 16) : 0u;
                if (ks & 1) mma(d, a, b0, b1); else mma(c, a, b0, b1);
            }
            if (t == 0) {
                const uint32_t qs = sm + OFF_QS + (w * 16 + g) * 2;
                sts16(qs, f2bf(c[0] + d[0])); sts16(qs + VROW, f2bf(c[1] + d[1]));
                sts16(qs + 16, f2bf(c[2] + d[2])); sts16(qs + VROW + 16, f2bf(c[3] + d[3]));
            }
            bar_sync(2, 256);
            if (w == 0) {
                const int b = lane >> 4, cc = lane & 15;
                g_qabs[(b * 32 + h) * 64 + ((j * 16 + cc) ^ (h & 7))] = lds128(sm + OFF_QS + b * VROW + cc * 16);
                __syncwarp();
                if (lane == 0) {
                    cnt_rendezvous(&g_cnt[0], tag * 128u, 18);
                    TS(10);
                    mbar_expect(bars + B_GATH * 8, 2 * CH);
                    bulk1d_n(sm + OFF_S2, g_qabs + (cta >> 6) * 2048, 2 * CH, bars + B_GATH * 8);
                }
                __syncwarp();
            }
        }
        mbar_wait(bars + B_GATH * 8, 0);
        if (st == 0) TS(11);
        {
            const int mt = w & 1, kg = w >> 1;
            const uint32_t qa = sm + OFF_S2 + (mt * 16 + rr + 8 * (i & 1)) * 1024;
            const uint32_t ka = sm + OFF_S0 + kg * CH + (rr + 8 * (i >> 1)) * 128;
            float s0[4] = {0.f, 0.f, 0.f, 0.f}, s1[4] = {0.f, 0.f, 0.f, 0.f};
            mbar_wait(bars + (B_CKV + kg) * 8, 0);
#pragma unroll 2
            for (int gq = 0; gq < 8; gq++) {
#pragma unroll
                for (int k4 = 0; k4 < 4; k4++) {
                    uint32_t a[4], b[4];
                    ldsm4(a, qa + gq * 128 + (((2 * k4 + (i >> 1)) ^ rr) << 4));
                    ldsm4(b, ka + gq * 2048 + (((2 * k4 + (i & 1)) ^ rr) << 4));
                    mma(s0, a, b[0], b[1]);
                    mma(s1, a, b[2], b[3]);
                }
            }
            const uint32_t sa = sm + OFF_SC + ((mt * 16 + g) * 68 + kg * 16 + 2 * t) * 4;
            stsf2(sa, s0[0], s0[1]); stsf2(sa + 32, s1[0], s1[1]);
            stsf2(sa + 8 * 68 * 4, s0[2], s0[3]); stsf2(sa + 8 * 68 * 4 + 32, s1[2], s1[3]);
        }
        bar_sync(2, 256);
        {
            const int head = w * 4 + i;
            const uint32_t sa = sm + OFF_SC + (head * 68 + rr * 8) * 4;
            const uint4 u0 = lds128(sa), u1 = lds128(sa + 16);
            float s[8] = {__uint_as_float(u0.x), __uint_as_float(u0.y), __uint_as_float(u0.z), __uint_as_float(u0.w),
                          __uint_as_float(u1.x), __uint_as_float(u1.y), __uint_as_float(u1.z), __uint_as_float(u1.w)};
            float mx = s[0];
#pragma unroll
            for (int k = 1; k < 8; k++) mx = fmaxf(mx, s[k]);
#pragma unroll
            for (int o = 1; o < 8; o <<= 1) mx = fmaxf(mx, __shfl_xor_sync(0xffffffffu, mx, o));
            float sum = 0.f;
#pragma unroll
            for (int k = 0; k < 8; k++) { s[k] = ex2((s[k] - mx) * (SCALE * LOG2E)); sum += s[k]; }
#pragma unroll
            for (int o = 1; o < 8; o <<= 1) sum += __shfl_xor_sync(0xffffffffu, sum, o);
            const float inv = __fdividef(1.f, sum);
            uint4 p;
            p.x = pack2(s[0] * inv, s[1] * inv); p.y = pack2(s[2] * inv, s[3] * inv);
            p.z = pack2(s[4] * inv, s[5] * inv); p.w = pack2(s[6] * inv, s[7] * inv);
            sts128(sm + OFF_P + head * 128 + ((rr ^ (head & 7)) << 4), p);
            if (rr == 0) ((float*)g_lse)[head * 128 + cta] = mx * (SCALE * LOG2E) + lg2(sum);
        }
        bar_sync(2, 256);
        {
            float o[2][8][4];
#pragma unroll
            for (int mt = 0; mt < 2; mt++)
#pragma unroll
                for (int n = 0; n < 8; n++) { o[mt][n][0] = o[mt][n][1] = o[mt][n][2] = o[mt][n][3] = 0.f; }
            const uint32_t pa = sm + OFF_P + (rr + 8 * (i & 1)) * 128;
            const uint32_t va = sm + OFF_S0 + w * 2048 + (rr + 8 * (i & 1)) * 128;
#pragma unroll 1
            for (int kq = 0; kq < 4; kq++) {
                uint32_t a0[4], a1[4];
                ldsm4(a0, pa + (((2 * kq + (i >> 1)) ^ rr) << 4));
                ldsm4(a1, pa + 2048 + (((2 * kq + (i >> 1)) ^ rr) << 4));
#pragma unroll
                for (int n = 0; n < 8; n += 2) {
                    uint32_t b[4];
                    ldsm4t(b, va + kq * CH + (((n + (i >> 1)) ^ rr) << 4));
                    mma(o[0][n], a0, b[0], b[1]); mma(o[1][n], a1, b[0], b[1]);
                    mma(o[0][n + 1], a0, b[2], b[3]); mma(o[1][n + 1], a1, b[2], b[3]);
                }
            }
#pragma unroll
            for (int mt = 0; mt < 2; mt++)
#pragma unroll
                for (int hf = 0; hf < 2; hf++) {
                    const uint32_t dst = sm + OFF_S2 + (mt * 16 + hf * 8 + g) * 1024 + w * 128 + t * 16;
#pragma unroll
                    for (int nb = 0; nb < 2; nb++) {
                        uint4 v;
                        v.x = pack2(o[mt][nb * 4 + 0][hf * 2], o[mt][nb * 4 + 0][hf * 2 + 1]);
                        v.y = pack2(o[mt][nb * 4 + 1][hf * 2], o[mt][nb * 4 + 1][hf * 2 + 1]);
                        v.z = pack2(o[mt][nb * 4 + 2][hf * 2], o[mt][nb * 4 + 2][hf * 2 + 1]);
                        v.w = pack2(o[mt][nb * 4 + 3][hf * 2], o[mt][nb * 4 + 3][hf * 2 + 1]);
                        sts128(dst + nb * 64, v);
                    }
                }
            asm volatile("fence.proxy.async.shared::cta;" ::: "memory");
            __syncwarp();
            if (lane == 0) mbar_arrive(bars + B_FREE * 8);
            if (st < 82) *(st < 64 ? &g_e4[cta][st] : st < 80 ? &g_e5[cta][st - 64] : &g_l5[h][j * 2 + st - 80]) = make_uint4(EMPTY, EMPTY, EMPTY, EMPTY);
            else if (st < 84) ((uint4*)out)[cta * 2 + st - 82] = make_uint4(0u, 0u, 0u, 0u);
        }
        bar_sync(2, 256);
        if (st == 0) {
            TS(12);
#pragma unroll 1
            for (int k = 0; k < ST_SPLIT; k++) {
                asm volatile("cp.async.bulk.tensor.3d.global.shared::cta.bulk_group [%0, {%2,%3,%4}], [%1];"
                             ::"l"(&maps.ctxp), "r"(sm + OFF_S2 + k * (2 * CH / ST_SPLIT)), "r"(0), "r"(cta), "r"(k * (128 / ST_SPLIT)) : "memory");
                if (k + 1 < ST_SPLIT) __nanosleep(ST_GAP);
            }
            asm volatile("cp.async.bulk.commit_group;" ::: "memory");
            asm volatile("cp.async.bulk.wait_group 0;" ::: "memory");
            cnt_rendezvous(&g_cnt[1], tag * 128u, 20);
            TS(13);
            mbar_expect(bars + B_GATH * 8, 2 * CH + 512);
            bulk1d_n(sm + OFF_LSE, g_lse + h * 32, 512, bars + B_GATH * 8);
#pragma unroll 1
            for (int k = 0; k < G_SPLIT; k++) {
                bulk1d_n(sm + OFF_S2 + k * (2 * CH / G_SPLIT), g_ctxp + cta * 2048 + k * (2048 / G_SPLIT), 2 * CH / G_SPLIT, bars + B_GATH * 8);
                if (k + 1 < G_SPLIT) __nanosleep(G_GAP);
            }
        }
        __syncwarp();
        {
            mbar_wait(bars + B_GATH * 8, 1);
            if (st == 0) TS(22);
            uint4 v[8];
#pragma unroll
            for (int k = 0; k < 8; k++) v[k] = lds128(sm + OFF_S2 + (k * 256 + st) * 16);
            float ls[4];
#pragma unroll
            for (int k = 0; k < 4; k++) ls[k] = ldsf(sm + OFF_LSE + (k * 32 + lane) * 4);
            float m0 = fmaxf(ls[0], ls[1]), m1 = fmaxf(ls[2], ls[3]);
#pragma unroll
            for (int o = 16; o; o >>= 1) { m0 = fmaxf(m0, __shfl_xor_sync(0xffffffffu, m0, o)); m1 = fmaxf(m1, __shfl_xor_sync(0xffffffffu, m1, o)); }
            ls[0] = ex2(ls[0] - m0); ls[1] = ex2(ls[1] - m0); ls[2] = ex2(ls[2] - m1); ls[3] = ex2(ls[3] - m1);
            float z0 = ls[0] + ls[1], z1 = ls[2] + ls[3];
#pragma unroll
            for (int o = 16; o; o >>= 1) { z0 += __shfl_xor_sync(0xffffffffu, z0, o); z1 += __shfl_xor_sync(0xffffffffu, z1, o); }
            z0 = __fdividef(1.f, z0); z1 = __fdividef(1.f, z1);
            ls[0] *= z0; ls[1] *= z0; ls[2] *= z1; ls[3] *= z1;
            float a[2][8];
#pragma unroll
            for (int e = 0; e < 8; e++) a[0][e] = a[1][e] = 0.f;
            const int rg = st >> 4;
#pragma unroll
            for (int k = 0; k < 8; k++) {
                const float wt = __shfl_sync(0xffffffffu, ls[k >> 1], rg + 16 * (k & 1));
                const uint32_t u[4] = {v[k].x, v[k].y, v[k].z, v[k].w};
#pragma unroll
                for (int e = 0; e < 4; e++) {
                    a[k >> 2][2 * e] += wt * __uint_as_float(u[e] << 16);
                    a[k >> 2][2 * e + 1] += wt * __uint_as_float(u[e] & 0xffff0000u);
                }
            }
            const int b = lane >> 4, u16 = lane & 15;
            const uint32_t ra = sm + OFF_SC + (w * 256 + b * 128 + (u16 >> 3) * 64 + ((u16 >> 2) & 1) * 32 + (u16 & 3) * 2) * 4;
#pragma unroll
            for (int e = 0; e < 8; e += 2) {
                const float k0 = b ? a[1][e] : a[0][e], k1 = b ? a[1][e + 1] : a[0][e + 1];
                const float s0 = b ? a[0][e] : a[1][e], s1 = b ? a[0][e + 1] : a[1][e + 1];
                stsf2(ra + (e >> 1) * 32, k0 + __shfl_xor_sync(0xffffffffu, s0, 16), k1 + __shfl_xor_sync(0xffffffffu, s1, 16));
            }
            bar_sync(2, 256);
            if (st == 0) mbar_arrive(bars + B_S2 * 8);
            float s = 0.f;
#pragma unroll
            for (int k = 0; k < 8; k++) s += ldsf(sm + OFF_SC + (k * 256 + st) * 4);
            const float hi = bfround(s);
            const uint32_t ca = sm + OFF_CC + (st >> 7) * VROW + (st & 127) * 2;
            sts16(ca, f2bf(hi)); sts16(ca + 2 * VROW, f2bf(s - hi));
            bar_sync(2, 256);
        }
        matvecT(c, sm + OFF_S1, sm + OFF_CC, 4, bars + B_WUV * 8, w, lane);
#pragma unroll
        for (int k = 0; k < 4; k++) c[k] += __shfl_down_sync(0xffffffffu, c[k], 1);
        if (t == 0) {
            float* const e = (float*)g_e4[cta] + w * 16 + g;
            mail_put(e, c[0]); mail_put(e + 128, c[1]); mail_put(e + 8, c[2]); mail_put(e + 136, c[3]);
        }
        __syncwarp();
        if (lane == 0) mbar_arrive(bars + B_FREE * 8);
        if (st == 0) TS(23);
        {
            const uint4* const pv = &g_e4[(cta & ~15) + (w >> 1) * 4][(w & 1) * 32 + lane];
            uint4 x[4];
            uint32_t it = 0;
            sleep_ns(POLL_DELAY2);
            while (true) {
#pragma unroll
                for (int k = 0; k < 4; k++) { x[k].x = x[k].y = x[k].z = x[k].w = 0u; mail_get(x[k], pv + k * 64); }
                if (!__any_sync(0xffffffffu, mail_missing(x[0]) | mail_missing(x[1]) | mail_missing(x[2]) | mail_missing(x[3]))) break;
                if (++it > SPIN_MAX) __trap();
                __nanosleep(BACKOFF);
            }
#define SUM4(e) ((__uint_as_float(x[0].e) + __uint_as_float(x[1].e)) + (__uint_as_float(x[2].e) + __uint_as_float(x[3].e)))
            sts64(sm + OFF_CA + w * VROW + lane * 8, pack2(SUM4(x), SUM4(y)), pack2(SUM4(z), SUM4(w)));
#undef SUM4
        }
        if (st == 0) TS(14);
        bar_sync(4, 256 + 128);
        {
            const uint32_t a0 = sm + OFF_S0 + w * 1024 + (rr + 8 * (i >> 1)) * 64 + (((i & 1) ^ (rr >> 1)) << 4);
            const uint4* const pv = pin(&g_e5[(cta & ~15) + (w >> 1) * 4 + (g & 3)][(w & 1) * 8 + (g >> 2) * 4 + t]);
            const uint32_t* const pl = pin((const uint32_t*)g_l5[(h & ~3) + (w >> 1)] + t);
            const uint32_t wa = sm + OFF_SC + ((w * 2 + (t >> 1)) * 80 + (t & 1) * 40 + g) * 4;
            __nv_bfloat16* const outp = pin(out + (lane >> 4) * 1024 + 512 + (cta & 15) * 32 + (lane & 15) * 2);
            uint32_t a[4][2][4], xl = 0u, it = 0;
            uint4 x = make_uint4(0u, 0u, 0u, 0u);
            while (true) {
                if (lane < 4) asm volatile("atom.relaxed.gpu.global.or.b32 %0, [%1], 0;" : "=r"(xl) : "l"(pl) : "memory");
                if (!__any_sync(0xffffffffu, xl == EMPTY)) break;
                if (++it > SPIN_MAX) __trap();
            }
            if (st == 0) TS(25);
            mail_get(x, pv);
            float w0, w1;
            merge_weights(__shfl_sync(0xffffffffu, xl, (t & 1) * 2), __shfl_sync(0xffffffffu, xl, (t & 1) * 2 + 1), w0, w1);
#pragma unroll
            for (int q = 0; q < 4; q++) {
                mbar_wait(bars + (B_WO + q) * 8, 0);
                ldsm4t(a[q][0], a0 + q * 8192);
                ldsm4t(a[q][1], (a0 ^ 32) + q * 8192);
            }
            if (st == 0) TS(26);
            while (true) {
                const bool n = mail_missing(x);
                if (!__any_sync(0xffffffffu, n)) break;
                mail_get(x, pv, n);
                if (++it > SPIN_MAX) __trap();
            }
            if (st == 0) TS(16);
            float d[2][2][4];
#pragma unroll
            for (int k = 0; k < 4; k++) {
                float (&dk)[4] = d[k >> 1][k & 1];
                dk[0] = dk[1] = dk[2] = dk[3] = 0.f;
                mma(dk, a[k >> 1][k & 1], x.x, x.y);
            }
#pragma unroll
            for (int k = 0; k < 4; k++) mma(d[k >> 1][k & 1], a[2 + (k >> 1)][k & 1], x.z, x.w);
#pragma unroll
            for (int k = 0; k < 4; k++) {
                const float s0 = (t & 2) ? d[1][k >> 1][(k & 1) * 2] : d[0][k >> 1][(k & 1) * 2];
                const float s1 = (t & 2) ? d[1][k >> 1][(k & 1) * 2 + 1] : d[0][k >> 1][(k & 1) * 2 + 1];
                sts32(wa + k * 32, __float_as_uint(w0 * s0 + w1 * s1));
            }
            if (st == 0) TS(17);
            if (w == 0) {
                bar_sync(5, 256);
                const uint32_t ra = sm + OFF_SC + ((lane >> 4) * 40 + (lane & 15) * 2) * 4;
                float2 r[16];
#pragma unroll
                for (int k = 0; k < 16; k++) r[k] = ldsf2(ra + k * 320);
#pragma unroll
                for (int o = 1; o < 16; o <<= 1)
#pragma unroll
                    for (int k = 0; k < 16; k += 2 * o) { r[k].x += r[k + o].x; r[k].y += r[k + o].y; }
                out_add(outp, r[0].x, r[0].y);
            } else {
                bar_arrive(5, 256);
            }
        }
    }
}

typedef CUresult (*EncodeFn)(CUtensorMap*, CUtensorMapDataType, cuuint32_t, void*, const cuuint64_t*, const cuuint64_t*,
                             const cuuint32_t*, const cuuint32_t*, CUtensorMapInterleave, CUtensorMapSwizzle,
                             CUtensorMapL2promotion, CUtensorMapFloatOOBfill);

void make_map(EncodeFn enc, CUtensorMap* m, void* p, unsigned rows, unsigned cols, unsigned br, unsigned bg) {
    cuuint64_t gd[3] = {64, rows, cols / 64};
    cuuint64_t gs[2] = {(cuuint64_t)cols * 2, 128};
    cuuint32_t bx[3] = {64, br, bg};
    cuuint32_t es[3] = {1, 1, 1};
    enc(m, CU_TENSOR_MAP_DATA_TYPE_BFLOAT16, 3, p, gd, gs, bx, es, CU_TENSOR_MAP_INTERLEAVE_NONE,
        CU_TENSOR_MAP_SWIZZLE_128B, CU_TENSOR_MAP_L2_PROMOTION_L2_128B, CU_TENSOR_MAP_FLOAT_OOB_FILL_NONE);
}

}

extern "C" void kernel_launch(void* const* d_in, const int* in_sizes, int n_in, void* d_out, int out_size) {
    static EncodeFn enc = nullptr;
    if (!enc) {
        void* fn = nullptr;
        cudaDriverEntryPointQueryResult qr;
        cudaGetDriverEntryPoint("cuTensorMapEncodeTiled", &fn, cudaEnableDefault, &qr);
        enc = (EncodeFn)fn;
        cudaFuncSetAttribute(fused_decode_kernel, cudaFuncAttributeMaxDynamicSharedMemorySize, SMEM_BYTES);
    }
    Maps maps;
    make_map(enc, &maps.wqB, d_in[9], 512, 4096, 64, 2);
    make_map(enc, &maps.wqA, d_in[2], 512, 4096, 64, 2);
    make_map(enc, &maps.wuk, d_in[3], 512, 4096, 64, 2);
    make_map(enc, &maps.wuv, d_in[4], 512, 4096, 64, 2);
    for (int k = 0; k < 2; k++) {
        cuuint64_t gd[3] = {512, 128, 32};
        cuuint64_t gs[2] = {1024, 131072};
        cuuint32_t bx[3] = {32, 32, 4};
        cuuint32_t es[3] = {1, 1, 1};
        enc(&maps.woB + k, CU_TENSOR_MAP_DATA_TYPE_BFLOAT16, 3, d_in[k ? 5 : 10], gd, gs, bx, es, CU_TENSOR_MAP_INTERLEAVE_NONE,
            CU_TENSOR_MAP_SWIZZLE_64B, CU_TENSOR_MAP_L2_PROMOTION_L2_256B, CU_TENSOR_MAP_FLOAT_OOB_FILL_NONE);
    }
    make_map(enc, &maps.ckv, d_in[1], 8192, 512, 16, 8);
    {
        void* p = nullptr;
        cudaGetSymbolAddress(&p, g_ctxp);
        cuuint64_t gd[3] = {128, 128, 128};
        cuuint64_t gs[2] = {256, 32768};
        cuuint32_t bx[3] = {128, 1, 128 / ST_SPLIT};
        cuuint32_t es[3] = {1, 1, 1};
        enc(&maps.ctxp, CU_TENSOR_MAP_DATA_TYPE_BFLOAT16, 3, p, gd, gs, bx, es, CU_TENSOR_MAP_INTERLEAVE_NONE,
            CU_TENSOR_MAP_SWIZZLE_NONE, CU_TENSOR_MAP_L2_PROMOTION_NONE, CU_TENSOR_MAP_FLOAT_OOB_FILL_NONE);
    }
    fused_decode_kernel<<<NCTA, NTHREADS, SMEM_BYTES>>>((const char*)d_in[9], maps, (const char*)d_in[7], (const char*)d_in[8],
                                                         (const __nv_bfloat16*)d_in[0], (const __nv_bfloat16*)d_in[6],
                                                         (__nv_bfloat16*)d_out, 0u);
}
```

```cpp
#include <cuda_runtime.h>
#include <cuda.h>
#include <cuda_bf16.h>
#include <stdint.h>

#define RING 7
#define WIN 4
#define WHI 5
#define THETA 64
#define END_V 40
#define GATE_W 64
#define PREWIN 4
#define TAILWIN 6
#define BOXGAP 350
#define POLL_DELAY 2500
#define POLL_DELAY2 4000
#define ST_SPLIT 16
#define ST_GAP 300
#define G_SPLIT 8
#define G_GAP 500
#define BACKOFF 200
#define BACKOFF2 100

namespace {

constexpr int NCTA = 128;
constexpr int NTHREADS = 448;
constexpr uint32_t CH = 16384;
constexpr int NTILE = 32;
constexpr int RUN = 4;

constexpr uint32_t OFF_RING = 0;
constexpr uint32_t OFF_S0 = RING * CH;
constexpr uint32_t OFF_S1 = OFF_S0 + 2 * CH;
constexpr uint32_t OFF_S2 = OFF_S1 + 2 * CH;
constexpr uint32_t OFF_P = OFF_S2 + 2 * CH;
constexpr uint32_t OFF_SC = OFF_P + 4096;
constexpr uint32_t VROW = 272;
constexpr uint32_t OFF_XB = OFF_SC + 8704;
constexpr uint32_t OFF_XA = OFF_XB + 2 * VROW;
constexpr uint32_t OFF_QA = OFF_XA + 2 * VROW;
constexpr uint32_t OFF_QS = OFF_QA + 2 * VROW;
constexpr uint32_t OFF_CC = OFF_QS + 2 * VROW;
constexpr uint32_t OFF_CA = OFF_P;
constexpr uint32_t OFF_QB = OFF_CC + 4 * VROW;
constexpr uint32_t OFF_LSE = OFF_QB + 256;
constexpr uint32_t OFF_ML = OFF_LSE + 512;
constexpr uint32_t OFF_TAG = OFF_ML + 32;
constexpr uint32_t OFF_NOW = OFF_TAG + 4;
constexpr uint32_t OFF_WIN = OFF_TAG + 8;
constexpr uint32_t OFF_TWIN = OFF_TAG + 12;
constexpr uint32_t OFF_BAR = OFF_TAG + 16;
constexpr int B_EMPTY = RING;
constexpr int B_WQB = 2 * RING;
constexpr int B_WQA = B_WQB + 2;
constexpr int B_WUK = B_WQA + 2;
constexpr int B_WUV = B_WUK + 2;
constexpr int B_CKV = B_WUV + 2;
constexpr int B_WO = B_CKV + 4;
constexpr int B_FREE = B_WO + 8;
constexpr int B_GATH = B_FREE + 1;
constexpr int B_S2 = B_GATH + 1;
constexpr int NBAR = B_S2 + 1;
constexpr uint32_t TS_OFF = OFF_BAR + NBAR * 8;
constexpr uint32_t SMEM_USED = TS_OFF;
constexpr uint32_t SMEM_BYTES = SMEM_USED + 1024;
static_assert(SMEM_BYTES <= 232448, "smem");
static_assert(RING >= RUN && RING >= WHI && WHI >= WIN && WHI >= 4 && WIN >= 3 && WIN <= 6 && TAILWIN >= 4, "windows");

constexpr float LOG2E = 1.4426950408889634f;
constexpr float SCALE = 0.08838834764831845f;
#define SPIN_LOG 22
constexpr uint32_t SPIN_MAX = 1u << SPIN_LOG;

struct Maps { CUtensorMap wqB, wqA, wuk, wuv, woB, woA, ckv, ctxp; };

__device__ __align__(256) unsigned g_cnt[32];
__device__ __align__(256) ulonglong2 g_e1[2][NCTA][128];
__device__ __align__(256) uint4 g_qabs[2 * 32 * 64];
__device__ __align__(256) uint4 g_ctxp[NCTA * 128 * 16];
__device__ __align__(256) float4 g_lse[32 * 32];
__device__ __align__(256) uint4 g_e4[NCTA][64];
__device__ __align__(256) uint4 g_e5[NCTA][16];
__device__ __align__(256) uint4 g_l5[32][8];
constexpr uint32_t EMPTY = 0xffffffffu;

#define TS(k) do {} while (0)

__device__ __forceinline__ void mbar_init(uint32_t b, int c) { asm volatile("mbarrier.init.shared::cta.b64 [%0], %1;" ::"r"(b), "r"(c) : "memory"); }
__device__ __forceinline__ void mbar_expect(uint32_t b, uint32_t bytes) { asm volatile("mbarrier.arrive.expect_tx.shared::cta.b64 _, [%0], %1;" ::"r"(b), "r"(bytes) : "memory"); }
__device__ __forceinline__ void mbar_arrive(uint32_t b) { asm volatile("mbarrier.arrive.shared::cta.b64 _, [%0];" ::"r"(b) : "memory"); }
__device__ __forceinline__ void mbar_wait(uint32_t b, uint32_t ph) {
    asm volatile("{\n.reg .pred p;\n.reg .u32 n;\nmov.u32 n, 0;\n"
                 "W:\nmbarrier.try_wait.parity.shared::cta.b64 p, [%0], %1;\n@p bra D;\n"
                 "add.u32 n, n, 1;\nsetp.le.u32 p, n, %2;\n@p bra W;\ntrap;\nD:\n}" ::"r"(b), "r"(ph), "n"(SPIN_MAX) : "memory");
}
__device__ __forceinline__ uint32_t mbar_test(uint32_t b, uint32_t ph) {
    uint32_t ok;
    asm volatile("{\n.reg .pred p;\nmbarrier.test_wait.parity.shared::cta.b64 p, [%1], %2;\nselp.u32 %0, 1, 0, p;\n}" : "=r"(ok) : "r"(b), "r"(ph) : "memory");
    return ok;
}
__device__ __forceinline__ void bulk1d(uint32_t dst, const void* src, uint32_t bar, uint64_t pol) {
    asm volatile("cp.async.bulk.shared::cluster.global.mbarrier::complete_tx::bytes.L2::cache_hint [%0], [%1], %2, [%3], %4;"
                 ::"r"(dst), "l"(src), "n"(CH), "r"(bar), "l"(pol) : "memory");
}
__device__ __forceinline__ void bulk1d_n(uint32_t dst, const void* src, uint32_t bytes, uint32_t bar) {
    asm volatile("cp.async.bulk.shared::cluster.global.mbarrier::complete_tx::bytes [%0], [%1], %2, [%3];"
                 ::"r"(dst), "l"(src), "r"(bytes), "r"(bar) : "memory");
}
__device__ __forceinline__ void tma3d(uint32_t dst, const CUtensorMap* map, int c1, int c2, uint32_t bar, uint64_t pol, int c0 = 0) {
    asm volatile("cp.async.bulk.tensor.3d.shared::cluster.global.mbarrier::complete_tx::bytes.L2::cache_hint [%0], [%1, {%3,%4,%5}], [%2], %6;"
                 ::"r"(dst), "l"(map), "r"(bar), "r"(c0), "r"(c1), "r"(c2), "l"(pol) : "memory");
}
__device__ __forceinline__ void bar_sync(int id, int n) { asm volatile("barrier.cta.sync %0, %1;" ::"r"(id), "r"(n) : "memory"); }
__device__ __forceinline__ void bar_arrive(int id, int n) { asm volatile("barrier.cta.arrive %0, %1;" ::"r"(id), "r"(n) : "memory"); }
__device__ __forceinline__ void ldsm4(uint32_t (&r)[4], uint32_t a) {
    asm volatile("ldmatrix.sync.aligned.m8n8.x4.shared.b16 {%0,%1,%2,%3}, [%4];" : "=r"(r[0]), "=r"(r[1]), "=r"(r[2]), "=r"(r[3]) : "r"(a) : "memory");
}
__device__ __forceinline__ void ldsm4t(uint32_t (&r)[4], uint32_t a) {
    asm volatile("ldmatrix.sync.aligned.m8n8.x4.trans.shared.b16 {%0,%1,%2,%3}, [%4];" : "=r"(r[0]), "=r"(r[1]), "=r"(r[2]), "=r"(r[3]) : "r"(a) : "memory");
}
__device__ __forceinline__ void mma(float (&c)[4], const uint32_t (&a)[4], uint32_t b0, uint32_t b1) {
    asm volatile("mma.sync.aligned.m16n8k16.row.col.f32.bf16.bf16.f32 {%0,%1,%2,%3}, {%4,%5,%6,%7}, {%8,%9}, {%0,%1,%2,%3};"
                 : "+f"(c[0]), "+f"(c[1]), "+f"(c[2]), "+f"(c[3]) : "r"(a[0]), "r"(a[1]), "r"(a[2]), "r"(a[3]), "r"(b0), "r"(b1));
}
__device__ __forceinline__ uint32_t lds32(uint32_t a) { uint32_t v; asm volatile("ld.shared.b32 %0, [%1];" : "=r"(v) : "r"(a) : "memory"); return v; }
__device__ __forceinline__ uint32_t ldsv(uint32_t a) { uint32_t v; asm volatile("ld.volatile.shared.b32 %0, [%1];" : "=r"(v) : "r"(a) : "memory"); return v; }
__device__ __forceinline__ void stsv(uint32_t a, uint32_t v) { asm volatile("st.volatile.shared.b32 [%0], %1;" ::"r"(a), "r"(v) : "memory"); }
__device__ __forceinline__ float ldsf(uint32_t a) { float v; asm volatile("ld.shared.f32 %0, [%1];" : "=f"(v) : "r"(a) : "memory"); return v; }
__device__ __forceinline__ uint4 lds128(uint32_t a) { uint4 v; asm volatile("ld.shared.v4.b32 {%0,%1,%2,%3}, [%4];" : "=r"(v.x), "=r"(v.y), "=r"(v.z), "=r"(v.w) : "r"(a) : "memory"); return v; }
__device__ __forceinline__ void sts16(uint32_t a, uint16_t v) { asm volatile("st.shared.b16 [%0], %1;" ::"r"(a), "h"(v) : "memory"); }
__device__ __forceinline__ void sts32(uint32_t a, uint32_t v) { asm volatile("st.shared.b32 [%0], %1;" ::"r"(a), "r"(v) : "memory"); }
__device__ __forceinline__ void stsf2(uint32_t a, float x, float y) { asm volatile("st.shared.v2.f32 [%0], {%1,%2};" ::"r"(a), "f"(x), "f"(y) : "memory"); }
__device__ __forceinline__ void sts128(uint32_t a, uint4 v) { asm volatile("st.shared.v4.b32 [%0], {%1,%2,%3,%4};" ::"r"(a), "r"(v.x), "r"(v.y), "r"(v.z), "r"(v.w) : "memory"); }
__device__ __forceinline__ uint16_t f2bf(float x) { return __bfloat16_as_ushort(__float2bfloat16_rn(x)); }
__device__ __forceinline__ float bfround(float x) { return __bfloat162float(__float2bfloat16_rn(x)); }
__device__ __forceinline__ uint32_t pack2(float lo, float hi) { uint32_t r; asm("cvt.rn.bf16x2.f32 %0, %1, %2;" : "=r"(r) : "f"(hi), "f"(lo)); return r; }
__device__ __forceinline__ float ex2(float x) { float r; asm("ex2.approx.ftz.f32 %0, %1;" : "=f"(r) : "f"(x)); return r; }
__device__ __forceinline__ float lg2(float x) { float r; asm("lg2.approx.ftz.f32 %0, %1;" : "=f"(r) : "f"(x)); return r; }

__device__ __forceinline__ float rcp(float x) { float r; asm("rcp.approx.ftz.f32 %0, %1;" : "=f"(r) : "f"(x)); return r; }
__device__ __forceinline__ void merge_weights(uint32_t l0, uint32_t l1, float& w0, float& w1) {
    const float a = __uint_as_float(l0), b = __uint_as_float(l1), mx = fmaxf(a, b), e0 = ex2(a - mx), e1 = ex2(b - mx), r = rcp(e0 + e1);
    w0 = e0 * r; w1 = e1 * r;
}

__device__ __forceinline__ uint32_t clock_lo() { uint32_t t; asm volatile("mov.u32 %0, %clock;" : "=r"(t) :: "memory"); return t; }
__device__ __forceinline__ void sleep_ns(uint32_t ns) {
    const uint32_t t0 = clock_lo();
    do { __nanosleep(200); } while (clock_lo() - t0 < 2 * ns);
}

__device__ __forceinline__ void ll_store2(ulonglong2* p, float a, float b, uint32_t tag) {
    unsigned long long x = ((unsigned long long)tag << 32) | __float_as_uint(a);
    unsigned long long y = ((unsigned long long)tag << 32) | __float_as_uint(b);
    asm volatile("st.relaxed.gpu.global.v2.b64 [%0], {%1,%2};" ::"l"(p), "l"(x), "l"(y) : "memory");
}
__device__ __forceinline__ void ll_ld2(const void* p, unsigned long long& x, unsigned long long& y) {
    asm volatile("ld.relaxed.gpu.global.v2.b64 {%0,%1}, [%2];" : "=l"(x), "=l"(y) : "l"(p) : "memory");
}
__device__ __forceinline__ void ll_gather4(const ulonglong2* p, uint32_t tag, float& r0, float& r1) {
    unsigned long long x[4], y[4]; uint32_t it = 0;
    while (true) {
        bool ok = true;
#pragma unroll
        for (int k = 0; k < 4; k++) ll_ld2(p + k * 128, x[k], y[k]);
#pragma unroll
        for (int k = 0; k < 4; k++) ok = ok && (uint32_t)(x[k] >> 32) == tag && (uint32_t)(y[k] >> 32) == tag;
        if (ok) break;
        if (++it > SPIN_MAX) __trap();
        __nanosleep(BACKOFF);
    }
    r0 = (__uint_as_float((uint32_t)x[0]) + __uint_as_float((uint32_t)x[1])) + (__uint_as_float((uint32_t)x[2]) + __uint_as_float((uint32_t)x[3]));
    r1 = (__uint_as_float((uint32_t)y[0]) + __uint_as_float((uint32_t)y[1])) + (__uint_as_float((uint32_t)y[2]) + __uint_as_float((uint32_t)y[3]));
}
__device__ __forceinline__ void cnt_rendezvous(unsigned* c, uint32_t target, int tsk) {
    TS(tsk);
    asm volatile("red.release.gpu.global.add.u32 [%0], 1;" ::"l"(c) : "memory");
    if (tsk == 18) TS(tsk + 1);
    uint32_t v, it = 0;
    while (true) {
        asm volatile("ld.acquire.gpu.global.u32 %0, [%1];" : "=r"(v) : "l"(c) : "memory");
        if ((int)(v - target) >= 0) break;
        if (++it > SPIN_MAX) __trap();
        __nanosleep(BACKOFF);
    }
    asm volatile("fence.proxy.async.global;" ::: "memory");
}

__device__ __forceinline__ void matvec_loadA(uint32_t (&a)[8][4], uint32_t tile, uint32_t bar, int w, int lane) {
    const int i = lane >> 3, rr = lane & 7, chunk = 2 * w + (i & 1);
    const uint32_t a0 = tile + (chunk >> 3) * 8192 + (rr + 8 * (i >> 1)) * 128 + (((chunk & 7) ^ rr) << 4);
#pragma unroll
    for (int hh = 0; hh < 2; hh++) {
        mbar_wait(bar + hh * 8, 0);
#pragma unroll
        for (int k = 0; k < 4; k++) ldsm4t(a[hh * 4 + k], a0 + hh * CH + k * 2048);
    }
}
__device__ __forceinline__ void matvec_mma(float (&c)[4], const uint32_t (&a)[8][4], uint32_t vec, int nvec, int lane) {
    const uint32_t va = vec + (lane & (nvec - 1)) * VROW + (lane >> 3) * 16;
    float d[4][4];
#pragma unroll
    for (int q = 0; q < 4; q++) {
        uint32_t b[4];
        ldsm4(b, va + q * 64);
        d[q][0] = d[q][1] = d[q][2] = d[q][3] = 0.f;
        mma(d[q], a[2 * q], b[0], b[1]);
        mma(d[q], a[2 * q + 1], b[2], b[3]);
    }
#pragma unroll
    for (int k = 0; k < 4; k++) c[k] = (d[0][k] + d[1][k]) + (d[2][k] + d[3][k]);
}
__device__ __forceinline__ void matvecT(float (&c)[4], uint32_t tile, uint32_t vec, int nvec, uint32_t bar, int w, int lane) {
    uint32_t a[8][4];
    matvec_loadA(a, tile, bar, w, lane);
    matvec_mma(c, a, vec, nvec, lane);
}
template <class T> __device__ __forceinline__ T* pin(T* p) { asm volatile("" : "+l"(p)); return p; }
__device__ __forceinline__ void mail_put(void* p, uint32_t v) { asm volatile("st.relaxed.gpu.global.b32 [%0], %1;" ::"l"(p), "r"(v) : "memory"); }
__device__ __forceinline__ void mail_put(void* p, float v) { mail_put(p, __float_as_uint(v)); }
__device__ __forceinline__ void out_add(__nv_bfloat16* p, float x, float y) {
    asm volatile("red.relaxed.gpu.global.add.noftz.bf16x2 [%0], %1;" ::"l"(p), "r"(pack2(x, y)) : "memory");
}
__device__ __forceinline__ bool mail_missing(const uint4& v) { return v.x == EMPTY || v.y == EMPTY || v.z == EMPTY || v.w == EMPTY; }
__device__ __forceinline__ void mail_get(uint4& v, const uint4* p, bool need = true) {
    asm volatile("{\n.reg .pred q;\nsetp.ne.u32 q, %5, 0;\n@q ld.relaxed.gpu.global.v4.b32 {%0,%1,%2,%3}, [%4];\n}"
                 : "+r"(v.x), "+r"(v.y), "+r"(v.z), "+r"(v.w) : "l"(p), "r"((uint32_t)need) : "memory");
}
__device__ __forceinline__ void sts64(uint32_t a, uint32_t x, uint32_t y) { asm volatile("st.shared.v2.b32 [%0], {%1,%2};" ::"r"(a), "r"(x), "r"(y) : "memory"); }
__device__ __forceinline__ float2 ldsf2(uint32_t a) { float2 v; asm volatile("ld.shared.v2.f32 {%0,%1}, [%2];" : "=f"(v.x), "=f"(v.y) : "r"(a) : "memory"); return v; }

__global__ void __launch_bounds__(NTHREADS, 1)
fused_decode_kernel(const char* __restrict__ wqraw, const __grid_constant__ Maps maps, const char* __restrict__ Kc, const char* __restrict__ Vc,
                    const __nv_bfloat16* __restrict__ xA, const __nv_bfloat16* __restrict__ xB,
                    __nv_bfloat16* __restrict__ out, const uint32_t zero) {
    if (threadIdx.x == 0) asm volatile("cp.async.bulk.prefetch.L2.global [%0], 32768;" ::"l"(wqraw + (size_t)blockIdx.x * 32768u) : "memory");
    asm volatile("nanosleep.u32 60;" ::: "memory");
    asm volatile("barrier.cta.sync.aligned 7, %0;" ::"n"(NTHREADS) : "memory");
    asm volatile("{\n.reg .pred p;\n.reg .u32 s;\nmov.u32 s, %smid;\nsetp.eq.u32 p, s, 0xffff;\n@p exit;\n}" ::: "memory");
    extern __shared__ char smem_raw[];
    const uint32_t sm = ((uint32_t)__cvta_generic_to_shared(smem_raw) + 1023u) & ~1023u;
    const uint32_t bars = sm + OFF_BAR;
    const int cta = blockIdx.x, h = cta >> 2, j = cta & 3;
    uint64_t pol = 0;
    if (threadIdx.x == 0) {
        TS(0);
        asm volatile("createpolicy.fractional.L2::evict_first.b64 %0, 1.0;" : "=l"(pol));
#pragma unroll
        for (int i = 0; i < WIN; i++) mbar_init(bars + (B_WQB + i) * 8, 1);
        asm volatile("fence.mbarrier_init.release.cluster;" ::: "memory");
#pragma unroll
        for (int i = 0; i < WIN; i++) {
            mbar_expect(bars + (B_WQB + i) * 8, CH);
            tma3d(sm + OFF_S0 + i * CH, &maps.wqB + (i >> 1), j * 128 + (i & 1) * 64, h * 2, bars + (B_WQB + i) * 8, pol);
        }
    }
    const int tid = threadIdx.x < 64 ? threadIdx.x + 384 : threadIdx.x - 64, warp = tid >> 5, lane = tid & 31;

    if (warp == 12) {
        const size_t kvoff = ((size_t)(((j >> 1) * 32 + h) * 4096 + (j & 1) * 2048)) * 256;
        const char* kp = Kc + kvoff;
        const char* vp = Vc + kvoff;
        __syncwarp();
        bar_arrive(0, NTHREADS);
        bar_sync(3, 64);
        if (lane == 0) {
            uint32_t pb[WHI];
#pragma unroll
            for (int i = 0; i < WHI; i++) pb[i] = i < WHI - WIN ? (bars + B_WO * 8) | 1u : bars + (B_WQB + i - (WHI - WIN)) * 8;
            auto pace = [&](uint32_t bar, uint32_t par) {
                uint32_t it = 0;
                while (true) {
                    const uint32_t win = ldsv(sm + OFF_WIN);
                    uint32_t busy = 0;
#pragma unroll
                    for (int i = 0; i < WHI; i++) busy += mbar_test(pb[i] & ~1u, pb[i] & 1u) ^ 1u;
                    if (busy < win) break;
                    if (++it > SPIN_MAX) __trap();
                }
#pragma unroll
                for (int i = 0; i + 1 < WHI; i++) pb[i] = pb[i + 1];
                pb[WHI - 1] = bar | par;
            };
            auto side = [&](const CUtensorMap* m, uint32_t dst, int bidx, int c1, int c2) {
                const uint32_t bar = bars + bidx * 8;
                pace(bar, 0);
                mbar_expect(bar, CH);
                tma3d(dst, m, c1, c2, bar, pol);
            };
#pragma unroll 1
            for (int i = WIN; i < 6; i++)
                side(&maps.wqB + (i >> 1), sm + OFF_S0 + i * CH, B_WQB + i, j * 128 + (i & 1) * 64, h * 2);
            TS(1);
            uint32_t slot = 0, use = 0;
            int nuv = 0;
#pragma unroll 1
            for (int n = 0; n < 2 * NTILE; n++) {
                if (n == RING) {
                    mbar_wait(bars + B_FREE * 8, 0);
#pragma unroll 1
                    for (int q = 0; q < 4; q++) side(&maps.ckv, sm + OFF_S0 + q * CH, B_CKV + q, cta * 64 + q * 16, 0);
                }
                if (nuv < 2 && n > RING && (n >= 2 * NTILE - 8 || mbar_test(bars + B_FREE * 8, 1))) {
                    mbar_wait(bars + B_FREE * 8, 1);
                    side(&maps.wuv, sm + OFF_S1 + nuv * CH, B_WUV + nuv, j * 128 + nuv * 64, h * 2);
                    nuv++;
                }
                const uint32_t fb = bars + slot * 8;
                pace(fb, use & 1);
                mbar_wait(fb + B_EMPTY * 8, (use & 1) ^ 1);
                mbar_expect(fb, CH);
                bulk1d(sm + OFF_RING + slot * CH, ((n & RUN) ? vp : kp) + (size_t)(n / (2 * RUN) * RUN + n % RUN) * CH, fb, pol);
                if (((n + cta) & 3) == 0) asm volatile("red.relaxed.gpu.global.add.u32 [%0], 4;" ::"l"(&g_cnt[2]) : "memory");
                stsv(sm + OFF_NOW, n + 1);
                if (++slot == RING) { slot = 0; use++; }
            }
            TS(2);
            mbar_wait(bars + B_FREE * 8, 0);
            uint32_t tlast = clock_lo();
#pragma unroll 1
            for (int i = 0; i < 8; i++) {
                uint32_t it = 0;
                while (true) {
                    const uint32_t win = ldsv(sm + OFF_TWIN);
                    uint32_t busy = i;
#pragma unroll
                    for (int k = 0; k < 4; k++) busy += 2 * (mbar_test(pb[WHI - 4 + k] & ~1u, pb[WHI - 4 + k] & 1u) ^ 1u) - mbar_test(bars + (B_WO + k) * 8, 0);
                    if (busy < win) break;
                    if (++it > SPIN_MAX) __trap();
                }
                while (clock_lo() - tlast < BOXGAP) {}
                tlast = clock_lo();
                if (i & 1) TS(32 + (i >> 1));
                mbar_expect(bars + (B_WO + i) * 8, CH / 2);
                tma3d(sm + OFF_S0 + i * (CH / 2), &maps.woB + (i >> 2), (i & 3) * 32, h & ~3, bars + (B_WO + i) * 8, pol, (cta & 15) * 32);
            }
            TS(3);
        }
    } else if (warp == 13) {
        if (lane == 0) {
#pragma unroll
            for (int i = 0; i < NBAR; i++)
                if (i < B_WQB || i >= B_WQB + WIN)
                    mbar_init(bars + i * 8, i == B_FREE ? 8 : (i >= B_EMPTY && i < B_EMPTY + RING) ? 4 : 1);
            asm volatile("fence.mbarrier_init.release.cluster;" ::: "memory");
#pragma unroll
            for (int i = 2; i < 8; i++) asm volatile("prefetch.tensormap [%0];" ::"l"(&maps.wqB + i) : "memory");
            stsv(sm + OFF_NOW, 0); stsv(sm + OFF_WIN, WIN); stsv(sm + OFF_TWIN, PREWIN);
        }
        __syncwarp();
        bar_arrive(3, 64);
        bar_sync(0, NTHREADS);
        if (lane == 0) {
            const uint32_t base = (lds32(sm + OFF_TAG) - 1u) * (NCTA * 2 * NTILE);
            mbar_wait(bars + (B_WUK + 1) * 8, 0);
            uint32_t it = 0;
            while (true) {
                const uint32_t n = ldsv(sm + OFF_NOW);
                uint32_t v;
                asm volatile("ld.relaxed.gpu.global.u32 %0, [%1];" : "=r"(v) : "l"(&g_cnt[2]) : "memory");
                v -= base;
                if (v >= NCTA * 2 * NTILE - GATE_W) break;
                const int diff = (int)(n * NCTA) - (int)v;
                stsv(sm + OFF_WIN, diff < -THETA ? WHI : WIN - (diff > THETA) - (v >= NCTA * END_V));
                if (++it > SPIN_MAX) __trap();
                __nanosleep(BACKOFF2);
            }
            stsv(sm + OFF_WIN, WHI); stsv(sm + OFF_TWIN, TAILWIN);
            TS(24);
        }
    } else if (warp < 4) {
        const int g = lane >> 2, t = lane & 3, i = lane >> 3, rr = lane & 7;
        if (tid == 0) {
            unsigned e;
            asm volatile("ld.relaxed.gpu.global.u32 %0, [%1];" : "=r"(e) : "l"(&g_cnt[1]) : "memory");
            sts32(sm + OFF_TAG, (e >> 7) + 1u);
        }
        bar_sync(0, NTHREADS);
        const uint32_t tag = lds32(sm + OFF_TAG);
        {
            mbar_wait(bars + 8, 0);
            float q0, q1;
            ll_gather4(&g_e1[0][h * 4][tid], tag, q0, q1);
            sts16(sm + OFF_QB + tid * 2, f2bf((j >> 1) ? q1 : q0));
        }
        bar_sync(1, 128);
        if (tid == 0) TS(4);
        uint32_t qf[8][2];
#pragma unroll
        for (int c = 0; c < 8; c++) {
            const uint32_t a = sm + OFF_QB + (((c + g) & 7) * 8 + 2 * t) * 2;
            qf[c][0] = lds32(a); qf[c][1] = lds32(a + 128);
        }
        float acc[8][4];
#pragma unroll
        for (int c = 0; c < 8; c++) { acc[c][0] = acc[c][1] = acc[c][2] = acc[c][3] = 0.f; }
        float m = -INFINITY, l = 0.f;
        const bool diag = (t == (g >> 1));
        const uint32_t krow = sm + OFF_RING + (warp * 16 + rr + 8 * (i & 1)) * 256 + (i >> 1) * 128;
        const uint32_t vrow = sm + OFF_RING + (warp * 16 + rr + 8 * (i >> 1)) * 256 + (i & 1) * 128;
        uint32_t slot = 0, ph = 0;
        uint32_t* const e5own = pin((uint32_t*)g_e5[cta] + tid);
        uint32_t a[8][4] = {}, b0[RUN], b1[RUN];
        auto release = [&]() {
            __syncwarp();
            if (lane == 0) mbar_arrive(bars + (B_EMPTY + slot) * 8 + ((a[0][0] | a[1][0] | a[2][0] | a[3][0] | a[4][0] | a[5][0] | a[6][0] | a[7][0]) & zero));
            if (++slot == RING) { slot = 0; ph ^= 1; }
        };
        auto load_v = [&]() {
            mbar_wait(bars + slot * 8, ph);
#pragma unroll
            for (int c = 0; c < 8; c++) ldsm4t(a[c], vrow + slot * CH + (((c + rr) & 7) << 4));
        };
#pragma unroll 1
        for (int run = 0;; run++) {
            float slo[RUN], shi[RUN], mx = -INFINITY;
#pragma unroll
            for (int u = 0; u < RUN; u++) {
                mbar_wait(bars + slot * 8, ph);
#pragma unroll
                for (int c = 0; c < 8; c++) ldsm4(a[c], krow + slot * CH + (((c + rr) & 7) << 4));
                release();
                float s0[4] = {0.f, 0.f, 0.f, 0.f}, s1[4] = {0.f, 0.f, 0.f, 0.f};
#pragma unroll
                for (int c = 0; c < 8; c += 2) { mma(s0, a[c], qf[c][0], qf[c][1]); mma(s1, a[c + 1], qf[c + 1][0], qf[c + 1][1]); }
                slo[u] = diag ? bfround(bfround((g & 1) ? s0[1] + s1[1] : s0[0] + s1[0]) * SCALE) : -INFINITY;
                shi[u] = diag ? bfround(bfround((g & 1) ? s0[3] + s1[3] : s0[2] + s1[2]) * SCALE) : -INFINITY;
                mx = fmaxf(mx, fmaxf(slo[u], shi[u]));
            }
            int key = __float_as_int(mx);
            key ^= (key >> 31) & 0x7fffffff;
            key = __reduce_max_sync(0xffffffffu, key);
            key ^= (key >> 31) & 0x7fffffff;
            const float mn = fmaxf(m, __int_as_float(key));
            const float alpha = ex2((m - mn) * LOG2E);
            m = mn;
            l *= alpha;
#pragma unroll
            for (int u = 0; u < RUN; u++) {
                const float plo = ex2((slo[u] - mn) * LOG2E), phi = ex2((shi[u] - mn) * LOG2E);
                l += plo + phi;
                b0[u] = (g & 1) ? pack2(0.f, plo) : pack2(plo, 0.f);
                b1[u] = (g & 1) ? pack2(0.f, phi) : pack2(phi, 0.f);
            }
#pragma unroll
            for (int c = 0; c < 8; c++) { acc[c][0] *= alpha; acc[c][1] *= alpha; acc[c][2] *= alpha; acc[c][3] *= alpha; }
            if (run == NTILE / RUN - 1) break;
#pragma unroll
            for (int u = 0; u < RUN; u++) {
                load_v();
                release();
#pragma unroll
                for (int c = 0; c < 8; c++) mma(acc[c], a[c], b0[u], b1[u]);
            }
        }
#pragma unroll
        for (int o = 16; o; o >>= 1) l += __shfl_xor_sync(0xffffffffu, l, o);
        if (lane == 0) stsf2(sm + OFF_ML + warp * 8, m, l);
        mbar_wait(bars + B_S2 * 8, 0);
        bar_sync(1, 128);
        {
            const uint4 ml0 = lds128(sm + OFF_ML), ml1 = lds128(sm + OFF_ML + 16);
            const float m0 = __uint_as_float(ml0.x), m1 = __uint_as_float(ml0.z), m2 = __uint_as_float(ml1.x), m3 = __uint_as_float(ml1.z);
            const float M = fmaxf(fmaxf(m0, m1), fmaxf(m2, m3));
            const float L = (ex2((m0 - M) * LOG2E) * __uint_as_float(ml0.y) + ex2((m1 - M) * LOG2E) * __uint_as_float(ml0.w))
                          + (ex2((m2 - M) * LOG2E) * __uint_as_float(ml1.y) + ex2((m3 - M) * LOG2E) * __uint_as_float(ml1.w));
            const float f = ex2((m - M) * LOG2E) * rcp(L);
            const float lse = M * LOG2E + lg2(L);
            float* const l5own = pin((float*)g_l5[h] + j);
            const uint32_t wa = sm + OFF_S2 + warp * 640 + (t * 16 + (t >> 1) * 8 + g) * 4;
            const uint32_t ra = sm + OFF_S2 + ((tid >> 4 & 1) * 40 + (tid & 2) * 40 + (tid >> 5) * 16 + (tid & 1) * 8 + (tid >> 2 & 3) * 2) * 4;
#pragma unroll
            for (int u = 0; u < RUN; u++) {
                load_v();
                if (++slot == RING) { slot = 0; ph ^= 1; }
                if (u == RUN - 1 && tid == 96) mail_put(l5own, lse);
#pragma unroll
                for (int c = 0; c < 8; c++) mma(acc[c], a[c], b0[u], b1[u]);
            }
            if (tid == 0) TS(5);
            float v[2][8];
#pragma unroll
            for (int c = 0; c < 8; c++) { v[0][c] = acc[c][0] + acc[(c + 7) & 7][1]; v[1][c] = acc[c][2] + acc[(c + 7) & 7][3]; }
#pragma unroll
            for (int c = 0; c < 4; c++) { v[0][c] += __shfl_xor_sync(0xffffffffu, v[0][c + 4], 2); v[1][c] += __shfl_xor_sync(0xffffffffu, v[1][c + 4], 2); }
            const int src = (lane & ~3) | ((lane + 3) & 3);
#pragma unroll
            for (int c = 0; c < 2; c++) { v[0][c] += __shfl_sync(0xffffffffu, v[0][c + 2], src); v[1][c] += __shfl_sync(0xffffffffu, v[1][c + 2], src); }
#pragma unroll
            for (int c = 0; c < 4; c++) sts32(wa + (c >> 1) * 320 + (c & 1) * 32, __float_as_uint(v[c >> 1][c & 1] * f));
            if (warp < 2) {
                bar_sync(1, 128);
                const float2 r0 = ldsf2(ra), r1 = ldsf2(ra + 640), r2 = ldsf2(ra + 1280), r3 = ldsf2(ra + 1920);
                mail_put(e5own, pack2((r0.x + r1.x) + (r2.x + r3.x), (r0.y + r1.y) + (r2.y + r3.y)));
            } else {
                bar_arrive(1, 128);
            }
        }
        if (tid == 0) TS(6);
        {
            uint32_t x[4][4][4];
            float d[4][4];
            bar_sync(4, 256 + 128);
#pragma unroll
            for (int k = 0; k < 16; k++) ldsm4(x[k >> 2][k & 3], sm + OFF_CA + ((k >> 2) * 2 + (lane & 1)) * VROW + (k & 3) * 64 + (i & 1) * 32 + (i >> 1) * 16);
#pragma unroll
            for (int k = 0; k < 4; k++) d[k][0] = d[k][1] = d[k][2] = d[k][3] = 0.f;
            const uint32_t wa = sm + OFF_S1 + lane * 64 + ((warp ^ (rr >> 1)) << 4);
            __nv_bfloat16* const outp = pin(out + (g & 1) * 1024 + (cta & 15) * 32 + warp * 8 + t * 2);
#pragma unroll
            for (int q = 0; q < 4; q += 2) {
#pragma unroll
                for (int k = 0; k < 8; k++) {
                    if (!(k & 3)) mbar_wait(bars + (B_WO + 4 + q + (k >> 2)) * 8, 0);
                    ldsm4t(a[k], wa + q * 8192 + k * 2048);
                }
#pragma unroll
                for (int k = 0; k < 16; k++) mma(d[k & 3], x[(k >> 1) & 3][q + (k >> 3)], a[k >> 1][(k & 1) * 2], a[k >> 1][(k & 1) * 2 + 1]);
            }
            if (lane < 8) out_add(outp, (d[0][0] + d[1][2]) + (d[2][0] + d[3][2]), (d[0][1] + d[1][3]) + (d[2][1] + d[3][3]));
            if (tid == 0) TS(15);
        }
    } else {
        const int st = tid - 128, w = warp - 4;
        const int g = lane >> 2, t = lane & 3, i = lane >> 3, rr = lane & 7;
        if (t == 0) {
#pragma unroll
            for (int k = 0; k < 4; k++) ll_store2(&g_e1[k >> 1][cta][w * 16 + g + (k & 1) * 8], 0.f, 0.f, 0u);
        }
        if (st < 64) {
            const int which = st >> 5, b = (st >> 4) & 1, c = st & 15;
            const uint4 v = __ldg((const uint4*)((which ? xA : xB) + b * 512 + j * 128) + c);
            sts128(sm + OFF_XB + (which * 2 + b) * VROW + c * 16, v);
        }
        bar_sync(0, NTHREADS);
        const uint32_t tag = lds32(sm + OFF_TAG);
        float c[4];
#pragma unroll 1
        for (int which = 0; which < 2; which++) {
            matvecT(c, sm + OFF_S0 + which * 2 * CH, sm + OFF_XB + which * 2 * VROW, 2, bars + (B_WQB + which * 2) * 8, w, lane);
            if (t == 0) {
                ll_store2(&g_e1[which][cta][w * 16 + g], c[0], c[1], tag);
                ll_store2(&g_e1[which][cta][w * 16 + g + 8], c[2], c[3], tag);
            }
        }
        __syncwarp();
        if (lane == 0) mbar_arrive(bars + B_FREE * 8);
        if (st == 0) TS(8);
        if (st < 128) {
            float q0, q1;
            sleep_ns(POLL_DELAY);
            ll_gather4(&g_e1[1][h * 4][st], tag, q0, q1);
            sts16(sm + OFF_QA + st * 2, f2bf(q0)); sts16(sm + OFF_QA + VROW + st * 2, f2bf(q1));
        }
        bar_sync(2, 256);
        if (st == 0) TS(9);
        {
            const int row = w * 16 + rr + 8 * (i & 1);
            const uint32_t a0 = sm + OFF_S2 + (row >> 6) * CH + (row & 63) * 128;
            const uint32_t va = sm + OFF_QA + g * VROW + t * 4;
            float d[4] = {0.f, 0.f, 0.f, 0.f};
            c[0] = c[1] = c[2] = c[3] = 0.f;
            mbar_wait(bars + (B_WUK + (w >> 2)) * 8, 0);
#pragma unroll
            for (int ks = 0; ks < 8; ks++) {
                const int chunk = 2 * ks + (i >> 1);
                uint32_t a[4];
                ldsm4(a, a0 + (chunk >> 3) * 8192 + (((chunk & 7) ^ rr) << 4));
                const uint32_t b0 = (g < 2) ? lds32(va + ks * 32) : 0u, b1 = (g < 2) ? lds32(va + ks * 32 + 16) : 0u;
                if (ks & 1) mma(d, a, b0, b1); else mma(c, a, b0, b1);
            }
            if (t == 0) {
                const uint32_t qs = sm + OFF_QS + (w * 16 + g) * 2;
                sts16(qs, f2bf(c[0] + d[0])); sts16(qs + VROW, f2bf(c[1] + d[1]));
                sts16(qs + 16, f2bf(c[2] + d[2])); sts16(qs + VROW + 16, f2bf(c[3] + d[3]));
            }
            bar_sync(2, 256);
            if (w == 0) {
                const int b = lane >> 4, cc = lane & 15;
                g_qabs[(b * 32 + h) * 64 + ((j * 16 + cc) ^ (h & 7))] = lds128(sm + OFF_QS + b * VROW + cc * 16);
                __syncwarp();
                if (lane == 0) {
                    cnt_rendezvous(&g_cnt[0], tag * 128u, 18);
                    TS(10);
                    mbar_expect(bars + B_GATH * 8, 2 * CH);
                    bulk1d_n(sm + OFF_S2, g_qabs + (cta >> 6) * 2048, 2 * CH, bars + B_GATH * 8);
                }
                __syncwarp();
            }
        }
        mbar_wait(bars + B_GATH * 8, 0);
        if (st == 0) TS(11);
        {
            const int mt = w & 1, kg = w >> 1;
            const uint32_t qa = sm + OFF_S2 + (mt * 16 + rr + 8 * (i & 1)) * 1024;
            const uint32_t ka = sm + OFF_S0 + kg * CH + (rr + 8 * (i >> 1)) * 128;
            float s0[4] = {0.f, 0.f, 0.f, 0.f}, s1[4] = {0.f, 0.f, 0.f, 0.f};
            mbar_wait(bars + (B_CKV + kg) * 8, 0);
#pragma unroll 2
            for (int gq = 0; gq < 8; gq++) {
#pragma unroll
                for (int k4 = 0; k4 < 4; k4++) {
                    uint32_t a[4], b[4];
                    ldsm4(a, qa + gq * 128 + (((2 * k4 + (i >> 1)) ^ rr) << 4));
                    ldsm4(b, ka + gq * 2048 + (((2 * k4 + (i & 1)) ^ rr) << 4));
                    mma(s0, a, b[0], b[1]);
                    mma(s1, a, b[2], b[3]);
                }
            }
            const uint32_t sa = sm + OFF_SC + ((mt * 16 + g) * 68 + kg * 16 + 2 * t) * 4;
            stsf2(sa, s0[0], s0[1]); stsf2(sa + 32, s1[0], s1[1]);
            stsf2(sa + 8 * 68 * 4, s0[2], s0[3]); stsf2(sa + 8 * 68 * 4 + 32, s1[2], s1[3]);
        }
        bar_sync(2, 256);
        {
            const int head = w * 4 + i;
            const uint32_t sa = sm + OFF_SC + (head * 68 + rr * 8) * 4;
            const uint4 u0 = lds128(sa), u1 = lds128(sa + 16);
            float s[8] = {__uint_as_float(u0.x), __uint_as_float(u0.y), __uint_as_float(u0.z), __uint_as_float(u0.w),
                          __uint_as_float(u1.x), __uint_as_float(u1.y), __uint_as_float(u1.z), __uint_as_float(u1.w)};
            float mx = s[0];
#pragma unroll
            for (int k = 1; k < 8; k++) mx = fmaxf(mx, s[k]);
#pragma unroll
            for (int o = 1; o < 8; o <<= 1) mx = fmaxf(mx, __shfl_xor_sync(0xffffffffu, mx, o));
            float sum = 0.f;
#pragma unroll
            for (int k = 0; k < 8; k++) { s[k] = ex2((s[k] - mx) * (SCALE * LOG2E)); sum += s[k]; }
#pragma unroll
            for (int o = 1; o < 8; o <<= 1) sum += __shfl_xor_sync(0xffffffffu, sum, o);
            const float inv = __fdividef(1.f, sum);
            uint4 p;
            p.x = pack2(s[0] * inv, s[1] * inv); p.y = pack2(s[2] * inv, s[3] * inv);
            p.z = pack2(s[4] * inv, s[5] * inv); p.w = pack2(s[6] * inv, s[7] * inv);
            sts128(sm + OFF_P + head * 128 + ((rr ^ (head & 7)) << 4), p);
            if (rr == 0) ((float*)g_lse)[head * 128 + cta] = mx * (SCALE * LOG2E) + lg2(sum);
        }
        bar_sync(2, 256);
        {
            float o[2][8][4];
#pragma unroll
            for (int mt = 0; mt < 2; mt++)
#pragma unroll
                for (int n = 0; n < 8; n++) { o[mt][n][0] = o[mt][n][1] = o[mt][n][2] = o[mt][n][3] = 0.f; }
            const uint32_t pa = sm + OFF_P + (rr + 8 * (i & 1)) * 128;
            const uint32_t va = sm + OFF_S0 + w * 2048 + (rr + 8 * (i & 1)) * 128;
#pragma unroll 1
            for (int kq = 0; kq < 4; kq++) {
                uint32_t a0[4], a1[4];
                ldsm4(a0, pa + (((2 * kq + (i >> 1)) ^ rr) << 4));
                ldsm4(a1, pa + 2048 + (((2 * kq + (i >> 1)) ^ rr) << 4));
#pragma unroll
                for (int n = 0; n < 8; n += 2) {
                    uint32_t b[4];
                    ldsm4t(b, va + kq * CH + (((n + (i >> 1)) ^ rr) << 4));
                    mma(o[0][n], a0, b[0], b[1]); mma(o[1][n], a1, b[0], b[1]);
                    mma(o[0][n + 1], a0, b[2], b[3]); mma(o[1][n + 1], a1, b[2], b[3]);
                }
            }
#pragma unroll
            for (int mt = 0; mt < 2; mt++)
#pragma unroll
                for (int hf = 0; hf < 2; hf++) {
                    const uint32_t dst = sm + OFF_S2 + (mt * 16 + hf * 8 + g) * 1024 + w * 128 + t * 16;
#pragma unroll
                    for (int nb = 0; nb < 2; nb++) {
                        uint4 v;
                        v.x = pack2(o[mt][nb * 4 + 0][hf * 2], o[mt][nb * 4 + 0][hf * 2 + 1]);
                        v.y = pack2(o[mt][nb * 4 + 1][hf * 2], o[mt][nb * 4 + 1][hf * 2 + 1]);
                        v.z = pack2(o[mt][nb * 4 + 2][hf * 2], o[mt][nb * 4 + 2][hf * 2 + 1]);
                        v.w = pack2(o[mt][nb * 4 + 3][hf * 2], o[mt][nb * 4 + 3][hf * 2 + 1]);
                        sts128(dst + nb * 64, v);
                    }
                }
            asm volatile("fence.proxy.async.shared::cta;" ::: "memory");
            __syncwarp();
            if (lane == 0) mbar_arrive(bars + B_FREE * 8);
            if (st < 82) *(st < 64 ? &g_e4[cta][st] : st < 80 ? &g_e5[cta][st - 64] : &g_l5[h][j * 2 + st - 80]) = make_uint4(EMPTY, EMPTY, EMPTY, EMPTY);
            else if (st < 84) ((uint4*)out)[cta * 2 + st - 82] = make_uint4(0u, 0u, 0u, 0u);
        }
        bar_sync(2, 256);
        if (st == 0) {
            TS(12);
#pragma unroll 1
            for (int k = 0; k < ST_SPLIT; k++) {
                asm volatile("cp.async.bulk.tensor.3d.global.shared::cta.bulk_group [%0, {%2,%3,%4}], [%1];"
                             ::"l"(&maps.ctxp), "r"(sm + OFF_S2 + k * (2 * CH / ST_SPLIT)), "r"(0), "r"(cta), "r"(k * (128 / ST_SPLIT)) : "memory");
                if (k + 1 < ST_SPLIT) __nanosleep(ST_GAP);
            }
            asm volatile("cp.async.bulk.commit_group;" ::: "memory");
            asm volatile("cp.async.bulk.wait_group 0;" ::: "memory");
            cnt_rendezvous(&g_cnt[1], tag * 128u, 20);
            TS(13);
            mbar_expect(bars + B_GATH * 8, 2 * CH + 512);
            bulk1d_n(sm + OFF_LSE, g_lse + h * 32, 512, bars + B_GATH * 8);
#pragma unroll 1
            for (int k = 0; k < G_SPLIT; k++) {
                bulk1d_n(sm + OFF_S2 + k * (2 * CH / G_SPLIT), g_ctxp + cta * 2048 + k * (2048 / G_SPLIT), 2 * CH / G_SPLIT, bars + B_GATH * 8);
                if (k + 1 < G_SPLIT) __nanosleep(G_GAP);
            }
        }
        __syncwarp();
        {
            mbar_wait(bars + B_GATH * 8, 1);
            if (st == 0) TS(22);
            uint4 v[8];
#pragma unroll
            for (int k = 0; k < 8; k++) v[k] = lds128(sm + OFF_S2 + (k * 256 + st) * 16);
            float ls[4];
#pragma unroll
            for (int k = 0; k < 4; k++) ls[k] = ldsf(sm + OFF_LSE + (k * 32 + lane) * 4);
            float m0 = fmaxf(ls[0], ls[1]), m1 = fmaxf(ls[2], ls[3]);
#pragma unroll
            for (int o = 16; o; o >>= 1) { m0 = fmaxf(m0, __shfl_xor_sync(0xffffffffu, m0, o)); m1 = fmaxf(m1, __shfl_xor_sync(0xffffffffu, m1, o)); }
            ls[0] = ex2(ls[0] - m0); ls[1] = ex2(ls[1] - m0); ls[2] = ex2(ls[2] - m1); ls[3] = ex2(ls[3] - m1);
            float z0 = ls[0] + ls[1], z1 = ls[2] + ls[3];
#pragma unroll
            for (int o = 16; o; o >>= 1) { z0 += __shfl_xor_sync(0xffffffffu, z0, o); z1 += __shfl_xor_sync(0xffffffffu, z1, o); }
            z0 = __fdividef(1.f, z0); z1 = __fdividef(1.f, z1);
            ls[0] *= z0; ls[1] *= z0; ls[2] *= z1; ls[3] *= z1;
            float a[2][8];
#pragma unroll
            for (int e = 0; e < 8; e++) a[0][e] = a[1][e] = 0.f;
            const int rg = st >> 4;
#pragma unroll
            for (int k = 0; k < 8; k++) {
                const float wt = __shfl_sync(0xffffffffu, ls[k >> 1], rg + 16 * (k & 1));
                const uint32_t u[4] = {v[k].x, v[k].y, v[k].z, v[k].w};
#pragma unroll
                for (int e = 0; e < 4; e++) {
                    a[k >> 2][2 * e] += wt * __uint_as_float(u[e] << 16);
                    a[k >> 2][2 * e + 1] += wt * __uint_as_float(u[e] & 0xffff0000u);
                }
            }
            const int b = lane >> 4, u16 = lane & 15;
            const uint32_t ra = sm + OFF_SC + (w * 256 + b * 128 + (u16 >> 3) * 64 + ((u16 >> 2) & 1) * 32 + (u16 & 3) * 2) * 4;
#pragma unroll
            for (int e = 0; e < 8; e += 2) {
                const float k0 = b ? a[1][e] : a[0][e], k1 = b ? a[1][e + 1] : a[0][e + 1];
                const float s0 = b ? a[0][e] : a[1][e], s1 = b ? a[0][e + 1] : a[1][e + 1];
                stsf2(ra + (e >> 1) * 32, k0 + __shfl_xor_sync(0xffffffffu, s0, 16), k1 + __shfl_xor_sync(0xffffffffu, s1, 16));
            }
            bar_sync(2, 256);
            if (st == 0) mbar_arrive(bars + B_S2 * 8);
            float s = 0.f;
#pragma unroll
            for (int k = 0; k < 8; k++) s += ldsf(sm + OFF_SC + (k * 256 + st) * 4);
            const float hi = bfround(s);
            const uint32_t ca = sm + OFF_CC + (st >> 7) * VROW + (st & 127) * 2;
            sts16(ca, f2bf(hi)); sts16(ca + 2 * VROW, f2bf(s - hi));
            bar_sync(2, 256);
        }
        matvecT(c, sm + OFF_S1, sm + OFF_CC, 4, bars + B_WUV * 8, w, lane);
#pragma unroll
        for (int k = 0; k < 4; k++) c[k] += __shfl_down_sync(0xffffffffu, c[k], 1);
        if (t == 0) {
            float* const e = (float*)g_e4[cta] + w * 16 + g;
            mail_put(e, c[0]); mail_put(e + 128, c[1]); mail_put(e + 8, c[2]); mail_put(e + 136, c[3]);
        }
        __syncwarp();
        if (lane == 0) mbar_arrive(bars + B_FREE * 8);
        if (st == 0) TS(23);
        {
            const uint4* const pv = &g_e4[(cta & ~15) + (w >> 1) * 4][(w & 1) * 32 + lane];
            uint4 x[4];
            uint32_t it = 0;
            sleep_ns(POLL_DELAY2);
            while (true) {
#pragma unroll
                for (int k = 0; k < 4; k++) { x[k].x = x[k].y = x[k].z = x[k].w = 0u; mail_get(x[k], pv + k * 64); }
                if (!__any_sync(0xffffffffu, mail_missing(x[0]) | mail_missing(x[1]) | mail_missing(x[2]) | mail_missing(x[3]))) break;
                if (++it > SPIN_MAX) __trap();
                __nanosleep(BACKOFF);
            }
#define SUM4(e) ((__uint_as_float(x[0].e) + __uint_as_float(x[1].e)) + (__uint_as_float(x[2].e) + __uint_as_float(x[3].e)))
            sts64(sm + OFF_CA + w * VROW + lane * 8, pack2(SUM4(x), SUM4(y)), pack2(SUM4(z), SUM4(w)));
#undef SUM4
        }
        if (st == 0) TS(14);
        bar_sync(4, 256 + 128);
        {
            const uint32_t a0 = sm + OFF_S0 + w * 1024 + (rr + 8 * (i >> 1)) * 64 + (((i & 1) ^ (rr >> 1)) << 4);
            const uint4* const pv = pin(&g_e5[(cta & ~15) + (w >> 1) * 4 + (g & 3)][(w & 1) * 8 + (g >> 2) * 4 + t]);
            const uint32_t* const pl = pin((const uint32_t*)g_l5[(h & ~3) + (w >> 1)] + t);
            const uint32_t wa = sm + OFF_SC + ((w * 2 + (t >> 1)) * 80 + (t & 1) * 40 + g) * 4;
            __nv_bfloat16* const outp = pin(out + (lane >> 4) * 1024 + 512 + (cta & 15) * 32 + (lane & 15) * 2);
            uint32_t a[4][2][4], xl = 0u, it = 0;
            uint4 x = make_uint4(0u, 0u, 0u, 0u);
            while (true) {
                if (lane < 4) asm volatile("atom.relaxed.gpu.global.or.b32 %0, [%1], 0;" : "=r"(xl) : "l"(pl) : "memory");
                if (!__any_sync(0xffffffffu, xl == EMPTY)) break;
                if (++it > SPIN_MAX) __trap();
            }
            if (st == 0) TS(25);
            mail_get(x, pv);
            float w0, w1;
            merge_weights(__shfl_sync(0xffffffffu, xl, (t & 1) * 2), __shfl_sync(0xffffffffu, xl, (t & 1) * 2 + 1), w0, w1);
#pragma unroll
            for (int q = 0; q < 4; q++) {
                mbar_wait(bars + (B_WO + q) * 8, 0);
                ldsm4t(a[q][0], a0 + q * 8192);
                ldsm4t(a[q][1], (a0 ^ 32) + q * 8192);
            }
            if (st == 0) TS(26);
            while (true) {
                const bool n = mail_missing(x);
                if (!__any_sync(0xffffffffu, n)) break;
                mail_get(x, pv, n);
                if (++it > SPIN_MAX) __trap();
            }
            if (st == 0) TS(16);
            float d[2][2][4];
#pragma unroll
            for (int k = 0; k < 4; k++) {
                float (&dk)[4] = d[k >> 1][k & 1];
                dk[0] = dk[1] = dk[2] = dk[3] = 0.f;
                mma(dk, a[k >> 1][k & 1], x.x, x.y);
            }
#pragma unroll
            for (int k = 0; k < 4; k++) mma(d[k >> 1][k & 1], a[2 + (k >> 1)][k & 1], x.z, x.w);
#pragma unroll
            for (int k = 0; k < 4; k++) {
                const float s0 = (t & 2) ? d[1][k >> 1][(k & 1) * 2] : d[0][k >> 1][(k & 1) * 2];
                const float s1 = (t & 2) ? d[1][k >> 1][(k & 1) * 2 + 1] : d[0][k >> 1][(k & 1) * 2 + 1];
                sts32(wa + k * 32, __float_as_uint(w0 * s0 + w1 * s1));
            }
            if (st == 0) TS(17);
            if (w == 0) {
                bar_sync(5, 256);
                const uint32_t ra = sm + OFF_SC + ((lane >> 4) * 40 + (lane & 15) * 2) * 4;
                float2 r[16];
#pragma unroll
                for (int k = 0; k < 16; k++) r[k] = ldsf2(ra + k * 320);
#pragma unroll
                for (int o = 1; o < 16; o <<= 1)
#pragma unroll
                    for (int k = 0; k < 16; k += 2 * o) { r[k].x += r[k + o].x; r[k].y += r[k + o].y; }
                out_add(outp, r[0].x, r[0].y);
            } else {
                bar_arrive(5, 256);
            }
        }
    }
}

typedef CUresult (*EncodeFn)(CUtensorMap*, CUtensorMapDataType, cuuint32_t, void*, const cuuint64_t*, const cuuint64_t*,
                             const cuuint32_t*, const cuuint32_t*, CUtensorMapInterleave, CUtensorMapSwizzle,
                             CUtensorMapL2promotion, CUtensorMapFloatOOBfill);

void make_map(EncodeFn enc, CUtensorMap* m, void* p, unsigned rows, unsigned cols, unsigned br, unsigned bg) {
    cuuint64_t gd[3] = {64, rows, cols / 64};
    cuuint64_t gs[2] = {(cuuint64_t)cols * 2, 128};
    cuuint32_t bx[3] = {64, br, bg};
    cuuint32_t es[3] = {1, 1, 1};
    enc(m, CU_TENSOR_MAP_DATA_TYPE_BFLOAT16, 3, p, gd, gs, bx, es, CU_TENSOR_MAP_INTERLEAVE_NONE,
        CU_TENSOR_MAP_SWIZZLE_128B, CU_TENSOR_MAP_L2_PROMOTION_L2_128B, CU_TENSOR_MAP_FLOAT_OOB_FILL_NONE);
}

}

extern "C" void kernel_launch(void* const* d_in, const int* in_sizes, int n_in, void* d_out, int out_size) {
    static EncodeFn enc = nullptr;
    if (!enc) {
        void* fn = nullptr;
        cudaDriverEntryPointQueryResult qr;
        cudaGetDriverEntryPoint("cuTensorMapEncodeTiled", &fn, cudaEnableDefault, &qr);
        enc = (EncodeFn)fn;
        cudaFuncSetAttribute(fused_decode_kernel, cudaFuncAttributeMaxDynamicSharedMemorySize, SMEM_BYTES);
    }
    Maps maps;
    make_map(enc, &maps.wqB, d_in[9], 512, 4096, 64, 2);
    make_map(enc, &maps.wqA, d_in[2], 512, 4096, 64, 2);
    make_map(enc, &maps.wuk, d_in[3], 512, 4096, 64, 2);
    make_map(enc, &maps.wuv, d_in[4], 512, 4096, 64, 2);
    for (int k = 0; k < 2; k++) {
        cuuint64_t gd[3] = {512, 128, 32};
        cuuint64_t gs[2] = {1024, 131072};
        cuuint32_t bx[3] = {32, 32, 4};
        cuuint32_t es[3] = {1, 1, 1};
        enc(&maps.woB + k, CU_TENSOR_MAP_DATA_TYPE_BFLOAT16, 3, d_in[k ? 5 : 10], gd, gs, bx, es, CU_TENSOR_MAP_INTERLEAVE_NONE,
            CU_TENSOR_MAP_SWIZZLE_64B, CU_TENSOR_MAP_L2_PROMOTION_L2_256B, CU_TENSOR_MAP_FLOAT_OOB_FILL_NONE);
    }
    make_map(enc, &maps.ckv, d_in[1], 8192, 512, 16, 8);
    {
        void* p = nullptr;
        cudaGetSymbolAddress(&p, g_ctxp);
        cuuint64_t gd[3] = {128, 128, 128};
        cuuint64_t gs[2] = {256, 32768};
        cuuint32_t bx[3] = {128, 1, 128 / ST_SPLIT};
        cuuint32_t es[3] = {1, 1, 1};
        enc(&maps.ctxp, CU_TENSOR_MAP_DATA_TYPE_BFLOAT16, 3, p, gd, gs, bx, es, CU_TENSOR_MAP_INTERLEAVE_NONE,
            CU_TENSOR_MAP_SWIZZLE_NONE, CU_TENSOR_MAP_L2_PROMOTION_NONE, CU_TENSOR_MAP_FLOAT_OOB_FILL_NONE);
    }
    fused_decode_kernel<<<NCTA, NTHREADS, SMEM_BYTES>>>((const char*)d_in[9], maps, (const char*)d_in[7], (const char*)d_in[8],
                                                         (const __nv_bfloat16*)d_in[0], (const __nv_bfloat16*)d_in[6],
                                                         (__nv_bfloat16*)d_out, 0u);
}
```

```cpp
#include <cuda_runtime.h>
#include <cuda.h>
#include <cuda_bf16.h>
#include <stdint.h>

#define RING 7
#define WIN 4
#define WHI 5
#define THETA 64
#define END_V 40
#define GATE_W 64
#define PREWIN 4
#define TAILWIN 6
#define BOXGAP 350
#define POLL_DELAY 2500
#define POLL_DELAY2 3000
#define ST_SPLIT 32
#define ST_GAP 200
#define G_SPLIT 8
#define G_GAP 250
#define BACKOFF 200
#define BACKOFF2 100

namespace {

constexpr int NCTA = 128;
constexpr int NTHREADS = 448;
constexpr uint32_t CH = 16384;
constexpr int NTILE = 32;
constexpr int RUN = 4;

constexpr uint32_t OFF_RING = 0;
constexpr uint32_t OFF_S0 = RING * CH;
constexpr uint32_t OFF_S1 = OFF_S0 + 2 * CH;
constexpr uint32_t OFF_S2 = OFF_S1 + 2 * CH;
constexpr uint32_t OFF_P = OFF_S2 + 2 * CH;
constexpr uint32_t OFF_SC = OFF_P + 4096;
constexpr uint32_t VROW = 272;
constexpr uint32_t OFF_XB = OFF_SC + 8704;
constexpr uint32_t OFF_XA = OFF_XB + 2 * VROW;
constexpr uint32_t OFF_QA = OFF_XA + 2 * VROW;
constexpr uint32_t OFF_QS = OFF_QA + 2 * VROW;
constexpr uint32_t OFF_CC = OFF_QS + 2 * VROW;
constexpr uint32_t OFF_CA = OFF_P;
constexpr uint32_t OFF_QB = OFF_CC + 4 * VROW;
constexpr uint32_t OFF_LSE = OFF_QB + 256;
constexpr uint32_t OFF_ML = OFF_LSE + 512;
constexpr uint32_t OFF_TAG = OFF_ML + 32;
constexpr uint32_t OFF_NOW = OFF_TAG + 4;
constexpr uint32_t OFF_WIN = OFF_TAG + 8;
constexpr uint32_t OFF_TWIN = OFF_TAG + 12;
constexpr uint32_t OFF_BAR = OFF_TAG + 16;
constexpr int B_EMPTY = RING;
constexpr int B_WQB = 2 * RING;
constexpr int B_WQA = B_WQB + 2;
constexpr int B_WUK = B_WQA + 2;
constexpr int B_WUV = B_WUK + 2;
constexpr int B_CKV = B_WUV + 2;
constexpr int B_WO = B_CKV + 4;
constexpr int B_FREE = B_WO + 8;
constexpr int B_GATH = B_FREE + 1;
constexpr int B_S2 = B_GATH + 1;
constexpr int NBAR = B_S2 + 1;
constexpr uint32_t TS_OFF = OFF_BAR + NBAR * 8;
constexpr uint32_t SMEM_USED = TS_OFF;
constexpr uint32_t SMEM_BYTES = SMEM_USED + 1024;
static_assert(SMEM_BYTES <= 232448, "smem");
static_assert(RING >= RUN && RING >= WHI && WHI >= WIN && WHI >= 4 && WIN >= 3 && WIN <= 6 && TAILWIN >= 4, "windows");

constexpr float LOG2E = 1.4426950408889634f;
constexpr float SCALE = 0.08838834764831845f;
#define SPIN_LOG 22
constexpr uint32_t SPIN_MAX = 1u << SPIN_LOG;

struct Maps { CUtensorMap wqB, wqA, wuk, wuv, woB, woA, ckv, ctxp; };

__device__ __align__(256) unsigned g_cnt[32];
__device__ __align__(256) ulonglong2 g_e1[2][NCTA][128];
__device__ __align__(256) uint4 g_qabs[2 * 32 * 64];
__device__ __align__(256) uint4 g_ctxp[NCTA * 128 * 16];
__device__ __align__(256) float4 g_lse[32 * 32];
__device__ __align__(256) uint4 g_e4[NCTA][64];
__device__ __align__(256) uint4 g_e5[NCTA][16];
__device__ __align__(256) uint4 g_l5[32][8];
constexpr uint32_t EMPTY = 0xffffffffu;

#define TS(k) do {} while (0)

__device__ __forceinline__ void mbar_init(uint32_t b, int c) { asm volatile("mbarrier.init.shared::cta.b64 [%0], %1;" ::"r"(b), "r"(c) : "memory"); }
__device__ __forceinline__ void mbar_expect(uint32_t b, uint32_t bytes) { asm volatile("mbarrier.arrive.expect_tx.shared::cta.b64 _, [%0], %1;" ::"r"(b), "r"(bytes) : "memory"); }
__device__ __forceinline__ void mbar_arrive(uint32_t b) { asm volatile("mbarrier.arrive.shared::cta.b64 _, [%0];" ::"r"(b) : "memory"); }
__device__ __forceinline__ void mbar_wait(uint32_t b, uint32_t ph) {
    asm volatile("{\n.reg .pred p;\n.reg .u32 n;\nmov.u32 n, 0;\n"
                 "W:\nmbarrier.try_wait.parity.shared::cta.b64 p, [%0], %1;\n@p bra D;\n"
                 "add.u32 n, n, 1;\nsetp.le.u32 p, n, %2;\n@p bra W;\ntrap;\nD:\n}" ::"r"(b), "r"(ph), "n"(SPIN_MAX) : "memory");
}
__device__ __forceinline__ uint32_t mbar_test(uint32_t b, uint32_t ph) {
    uint32_t ok;
    asm volatile("{\n.reg .pred p;\nmbarrier.test_wait.parity.shared::cta.b64 p, [%1], %2;\nselp.u32 %0, 1, 0, p;\n}" : "=r"(ok) : "r"(b), "r"(ph) : "memory");
    return ok;
}
__device__ __forceinline__ void bulk1d(uint32_t dst, const void* src, uint32_t bar, uint64_t pol) {
    asm volatile("cp.async.bulk.shared::cluster.global.mbarrier::complete_tx::bytes.L2::cache_hint [%0], [%1], %2, [%3], %4;"
                 ::"r"(dst), "l"(src), "n"(CH), "r"(bar), "l"(pol) : "memory");
}
__device__ __forceinline__ void bulk1d_n(uint32_t dst, const void* src, uint32_t bytes, uint32_t bar) {
    asm volatile("cp.async.bulk.shared::cluster.global.mbarrier::complete_tx::bytes [%0], [%1], %2, [%3];"
                 ::"r"(dst), "l"(src), "r"(bytes), "r"(bar) : "memory");
}
__device__ __forceinline__ void tma3d(uint32_t dst, const CUtensorMap* map, int c1, int c2, uint32_t bar, uint64_t pol, int c0 = 0) {
    asm volatile("cp.async.bulk.tensor.3d.shared::cluster.global.mbarrier::complete_tx::bytes.L2::cache_hint [%0], [%1, {%3,%4,%5}], [%2], %6;"
                 ::"r"(dst), "l"(map), "r"(bar), "r"(c0), "r"(c1), "r"(c2), "l"(pol) : "memory");
}
__device__ __forceinline__ void bar_sync(int id, int n) { asm volatile("barrier.cta.sync %0, %1;" ::"r"(id), "r"(n) : "memory"); }
__device__ __forceinline__ void bar_arrive(int id, int n) { asm volatile("barrier.cta.arrive %0, %1;" ::"r"(id), "r"(n) : "memory"); }
__device__ __forceinline__ void ldsm4(uint32_t (&r)[4], uint32_t a) {
    asm volatile("ldmatrix.sync.aligned.m8n8.x4.shared.b16 {%0,%1,%2,%3}, [%4];" : "=r"(r[0]), "=r"(r[1]), "=r"(r[2]), "=r"(r[3]) : "r"(a) : "memory");
}
__device__ __forceinline__ void ldsm4t(uint32_t (&r)[4], uint32_t a) {
    asm volatile("ldmatrix.sync.aligned.m8n8.x4.trans.shared.b16 {%0,%1,%2,%3}, [%4];" : "=r"(r[0]), "=r"(r[1]), "=r"(r[2]), "=r"(r[3]) : "r"(a) : "memory");
}
__device__ __forceinline__ bool box_load(uint32_t (&r)[4], uint32_t (&s)[4], uint32_t (&u)[4], uint32_t (&v)[4], uint32_t bar, uint32_t a) {
    uint32_t ok;
    asm volatile("{\n.reg .pred p;\nmbarrier.try_wait.parity.shared::cta.b64 p, [%17], 0;\n"
                 "@p ldmatrix.sync.aligned.m8n8.x4.trans.shared.b16 {%0,%1,%2,%3}, [%18];\n"
                 "@p ldmatrix.sync.aligned.m8n8.x4.trans.shared.b16 {%4,%5,%6,%7}, [%18 + 2048];\n"
                 "@p ldmatrix.sync.aligned.m8n8.x4.trans.shared.b16 {%8,%9,%10,%11}, [%18 + 4096];\n"
                 "@p ldmatrix.sync.aligned.m8n8.x4.trans.shared.b16 {%12,%13,%14,%15}, [%18 + 6144];\n"
                 "selp.u32 %16, 1, 0, p;\n}"
                 : "+r"(r[0]), "+r"(r[1]), "+r"(r[2]), "+r"(r[3]), "+r"(s[0]), "+r"(s[1]), "+r"(s[2]), "+r"(s[3]),
                   "+r"(u[0]), "+r"(u[1]), "+r"(u[2]), "+r"(u[3]), "+r"(v[0]), "+r"(v[1]), "+r"(v[2]), "+r"(v[3]), "=r"(ok)
                 : "r"(bar), "r"(a) : "memory");
    return ok != 0;
}
__device__ __forceinline__ void mma(float (&c)[4], const uint32_t (&a)[4], uint32_t b0, uint32_t b1) {
    asm volatile("mma.sync.aligned.m16n8k16.row.col.f32.bf16.bf16.f32 {%0,%1,%2,%3}, {%4,%5,%6,%7}, {%8,%9}, {%0,%1,%2,%3};"
                 : "+f"(c[0]), "+f"(c[1]), "+f"(c[2]), "+f"(c[3]) : "r"(a[0]), "r"(a[1]), "r"(a[2]), "r"(a[3]), "r"(b0), "r"(b1));
}
__device__ __forceinline__ uint32_t lds32(uint32_t a) { uint32_t v; asm volatile("ld.shared.b32 %0, [%1];" : "=r"(v) : "r"(a) : "memory"); return v; }
__device__ __forceinline__ uint32_t ldsv(uint32_t a) { uint32_t v; asm volatile("ld.volatile.shared.b32 %0, [%1];" : "=r"(v) : "r"(a) : "memory"); return v; }
__device__ __forceinline__ void stsv(uint32_t a, uint32_t v) { asm volatile("st.volatile.shared.b32 [%0], %1;" ::"r"(a), "r"(v) : "memory"); }
__device__ __forceinline__ float ldsf(uint32_t a) { float v; asm volatile("ld.shared.f32 %0, [%1];" : "=f"(v) : "r"(a) : "memory"); return v; }
__device__ __forceinline__ uint4 lds128(uint32_t a) { uint4 v; asm volatile("ld.shared.v4.b32 {%0,%1,%2,%3}, [%4];" : "=r"(v.x), "=r"(v.y), "=r"(v.z), "=r"(v.w) : "r"(a) : "memory"); return v; }
__device__ __forceinline__ void sts16(uint32_t a, uint16_t v) { asm volatile("st.shared.b16 [%0], %1;" ::"r"(a), "h"(v) : "memory"); }
__device__ __forceinline__ void sts32(uint32_t a, uint32_t v) { asm volatile("st.shared.b32 [%0], %1;" ::"r"(a), "r"(v) : "memory"); }
__device__ __forceinline__ void stsf2(uint32_t a, float x, float y) { asm volatile("st.shared.v2.f32 [%0], {%1,%2};" ::"r"(a), "f"(x), "f"(y) : "memory"); }
__device__ __forceinline__ void sts128(uint32_t a, uint4 v) { asm volatile("st.shared.v4.b32 [%0], {%1,%2,%3,%4};" ::"r"(a), "r"(v.x), "r"(v.y), "r"(v.z), "r"(v.w) : "memory"); }
__device__ __forceinline__ uint16_t f2bf(float x) { return __bfloat16_as_ushort(__float2bfloat16_rn(x)); }
__device__ __forceinline__ float bfround(float x) { return __bfloat162float(__float2bfloat16_rn(x)); }
__device__ __forceinline__ uint32_t pack2(float lo, float hi) { uint32_t r; asm("cvt.rn.bf16x2.f32 %0, %1, %2;" : "=r"(r) : "f"(hi), "f"(lo)); return r; }
__device__ __forceinline__ float ex2(float x) { float r; asm("ex2.approx.ftz.f32 %0, %1;" : "=f"(r) : "f"(x)); return r; }
__device__ __forceinline__ float lg2(float x) { float r; asm("lg2.approx.ftz.f32 %0, %1;" : "=f"(r) : "f"(x)); return r; }

__device__ __forceinline__ float rcp(float x) { float r; asm("rcp.approx.ftz.f32 %0, %1;" : "=f"(r) : "f"(x)); return r; }
__device__ __forceinline__ void merge_weights(uint32_t l0, uint32_t l1, float& w0, float& w1) {
    const float a = __uint_as_float(l0), b = __uint_as_float(l1), mx = fmaxf(a, b), e0 = ex2(a - mx), e1 = ex2(b - mx), r = rcp(e0 + e1);
    w0 = e0 * r; w1 = e1 * r;
}

__device__ __forceinline__ uint32_t clock_lo() { uint32_t t; asm volatile("mov.u32 %0, %clock;" : "=r"(t) :: "memory"); return t; }
__device__ __forceinline__ void sleep_ns(uint32_t ns) {
    const uint32_t t0 = clock_lo();
    do { __nanosleep(200); } while (clock_lo() - t0 < 2 * ns);
}

__device__ __forceinline__ void ll_store2(ulonglong2* p, float a, float b, uint32_t tag) {
    unsigned long long x = ((unsigned long long)tag << 32) | __float_as_uint(a);
    unsigned long long y = ((unsigned long long)tag << 32) | __float_as_uint(b);
    asm volatile("st.relaxed.gpu.global.v2.b64 [%0], {%1,%2};" ::"l"(p), "l"(x), "l"(y) : "memory");
}
__device__ __forceinline__ void ll_ld2(const void* p, unsigned long long& x, unsigned long long& y) {
    asm volatile("ld.relaxed.gpu.global.v2.b64 {%0,%1}, [%2];" : "=l"(x), "=l"(y) : "l"(p) : "memory");
}
__device__ __forceinline__ void ll_gather4(const ulonglong2* p, uint32_t tag, float& r0, float& r1) {
    unsigned long long x[4], y[4]; uint32_t it = 0;
    while (true) {
        bool ok = true;
#pragma unroll
        for (int k = 0; k < 4; k++) ll_ld2(p + k * 128, x[k], y[k]);
#pragma unroll
        for (int k = 0; k < 4; k++) ok = ok && (uint32_t)(x[k] >> 32) == tag && (uint32_t)(y[k] >> 32) == tag;
        if (ok) break;
        if (++it > SPIN_MAX) __trap();
        __nanosleep(BACKOFF);
    }
    r0 = (__uint_as_float((uint32_t)x[0]) + __uint_as_float((uint32_t)x[1])) + (__uint_as_float((uint32_t)x[2]) + __uint_as_float((uint32_t)x[3]));
    r1 = (__uint_as_float((uint32_t)y[0]) + __uint_as_float((uint32_t)y[1])) + (__uint_as_float((uint32_t)y[2]) + __uint_as_float((uint32_t)y[3]));
}
__device__ __forceinline__ void cnt_rendezvous(unsigned* c, uint32_t target, int tsk) {
    TS(tsk);
    asm volatile("red.release.gpu.global.add.u32 [%0], 1;" ::"l"(c) : "memory");
    if (tsk == 18) TS(tsk + 1);
    uint32_t v, it = 0;
    while (true) {
        asm volatile("ld.acquire.gpu.global.u32 %0, [%1];" : "=r"(v) : "l"(c) : "memory");
        if ((int)(v - target) >= 0) break;
        if (++it > SPIN_MAX) __trap();
        __nanosleep(BACKOFF);
    }
    asm volatile("fence.proxy.async.global;" ::: "memory");
}

__device__ __forceinline__ void matvec_loadA(uint32_t (&a)[8][4], uint32_t tile, uint32_t bar, int w, int lane) {
    const int i = lane >> 3, rr = lane & 7, chunk = 2 * w + (i & 1);
    const uint32_t a0 = tile + (chunk >> 3) * 8192 + (rr + 8 * (i >> 1)) * 128 + (((chunk & 7) ^ rr) << 4);
#pragma unroll
    for (int hh = 0; hh < 2; hh++) {
        mbar_wait(bar + hh * 8, 0);
#pragma unroll
        for (int k = 0; k < 4; k++) ldsm4t(a[hh * 4 + k], a0 + hh * CH + k * 2048);
    }
}
__device__ __forceinline__ void matvec_mma(float (&c)[4], const uint32_t (&a)[8][4], uint32_t vec, int nvec, int lane) {
    const uint32_t va = vec + (lane & (nvec - 1)) * VROW + (lane >> 3) * 16;
    float d[4][4];
#pragma unroll
    for (int q = 0; q < 4; q++) {
        uint32_t b[4];
        ldsm4(b, va + q * 64);
        d[q][0] = d[q][1] = d[q][2] = d[q][3] = 0.f;
        mma(d[q], a[2 * q], b[0], b[1]);
        mma(d[q], a[2 * q + 1], b[2], b[3]);
    }
#pragma unroll
    for (int k = 0; k < 4; k++) c[k] = (d[0][k] + d[1][k]) + (d[2][k] + d[3][k]);
}
__device__ __forceinline__ void matvecT(float (&c)[4], uint32_t tile, uint32_t vec, int nvec, uint32_t bar, int w, int lane) {
    uint32_t a[8][4];
    matvec_loadA(a, tile, bar, w, lane);
    matvec_mma(c, a, vec, nvec, lane);
}
template <class T> __device__ __forceinline__ T* pin(T* p) { asm volatile("" : "+l"(p)); return p; }
__device__ __forceinline__ void mail_put(void* p, uint32_t v) { asm volatile("st.relaxed.gpu.global.b32 [%0], %1;" ::"l"(p), "r"(v) : "memory"); }
__device__ __forceinline__ void mail_put(void* p, float v) { mail_put(p, __float_as_uint(v)); }
__device__ __forceinline__ void out_add(__nv_bfloat16* p, float x, float y) {
    asm volatile("red.relaxed.gpu.global.add.noftz.bf16x2 [%0], %1;" ::"l"(p), "r"(pack2(x, y)) : "memory");
}
__device__ __forceinline__ bool mail_missing(const uint4& v) { return v.x == EMPTY || v.y == EMPTY || v.z == EMPTY || v.w == EMPTY; }
__device__ __forceinline__ void mail_get(uint4& v, const uint4* p, bool need = true) {
    asm volatile("{\n.reg .pred q;\nsetp.ne.u32 q, %5, 0;\n@q ld.relaxed.gpu.global.v4.b32 {%0,%1,%2,%3}, [%4];\n}"
                 : "+r"(v.x), "+r"(v.y), "+r"(v.z), "+r"(v.w) : "l"(p), "r"((uint32_t)need) : "memory");
}
__device__ __forceinline__ void sts64(uint32_t a, uint32_t x, uint32_t y) { asm volatile("st.shared.v2.b32 [%0], {%1,%2};" ::"r"(a), "r"(x), "r"(y) : "memory"); }
__device__ __forceinline__ float2 ldsf2(uint32_t a) { float2 v; asm volatile("ld.shared.v2.f32 {%0,%1}, [%2];" : "=f"(v.x), "=f"(v.y) : "r"(a) : "memory"); return v; }

__global__ void __launch_bounds__(NTHREADS, 1)
fused_decode_kernel(const char* __restrict__ wqraw, const __grid_constant__ Maps maps, const char* __restrict__ Kc, const char* __restrict__ Vc,
                    const __nv_bfloat16* __restrict__ xA, const __nv_bfloat16* __restrict__ xB,
                    __nv_bfloat16* __restrict__ out, const uint32_t zero) {
    if (threadIdx.x == 0) asm volatile("cp.async.bulk.prefetch.L2.global [%0], 32768;" ::"l"(wqraw + (size_t)blockIdx.x * 32768u) : "memory");
    asm volatile("nanosleep.u32 60;" ::: "memory");
    asm volatile("barrier.cta.sync.aligned 7, %0;" ::"n"(NTHREADS) : "memory");
    asm volatile("{\n.reg .pred p;\n.reg .u32 s;\nmov.u32 s, %smid;\nsetp.eq.u32 p, s, 0xffff;\n@p exit;\n}" ::: "memory");
    extern __shared__ char smem_raw[];
    const uint32_t sm = ((uint32_t)__cvta_generic_to_shared(smem_raw) + 1023u) & ~1023u;
    const uint32_t bars = sm + OFF_BAR;
    const int cta = blockIdx.x, h = cta >> 2, j = cta & 3;
    uint64_t pol = 0;
    if (threadIdx.x == 0) {
        TS(0);
        asm volatile("createpolicy.fractional.L2::evict_first.b64 %0, 1.0;" : "=l"(pol));
#pragma unroll
        for (int i = 0; i < WIN; i++) mbar_init(bars + (B_WQB + i) * 8, 1);
        asm volatile("fence.mbarrier_init.release.cluster;" ::: "memory");
#pragma unroll
        for (int i = 0; i < WIN; i++) {
            mbar_expect(bars + (B_WQB + i) * 8, CH);
            tma3d(sm + OFF_S0 + i * CH, &maps.wqB + (i >> 1), j * 128 + (i & 1) * 64, h * 2, bars + (B_WQB + i) * 8, pol);
        }
    }
    const int tid = threadIdx.x < 64 ? threadIdx.x + 384 : threadIdx.x - 64, warp = tid >> 5, lane = tid & 31;

    if (warp == 12) {
        const size_t kvoff = ((size_t)(((j >> 1) * 32 + h) * 4096 + (j & 1) * 2048)) * 256;
        const char* kp = Kc + kvoff;
        const char* vp = Vc + kvoff;
        __syncwarp();
        bar_arrive(0, NTHREADS);
        bar_sync(3, 64);
        if (lane == 0) {
            uint32_t pb[WHI];
#pragma unroll
            for (int i = 0; i < WHI; i++) pb[i] = i < WHI - WIN ? (bars + B_WO * 8) | 1u : bars + (B_WQB + i - (WHI - WIN)) * 8;
            auto pace = [&](uint32_t bar, uint32_t par) {
                uint32_t it = 0;
                while (true) {
                    const uint32_t win = ldsv(sm + OFF_WIN);
                    uint32_t busy = 0;
#pragma unroll
                    for (int i = 0; i < WHI; i++) busy += mbar_test(pb[i] & ~1u, pb[i] & 1u) ^ 1u;
                    if (busy < win) break;
                    if (++it > SPIN_MAX) __trap();
                }
#pragma unroll
                for (int i = 0; i + 1 < WHI; i++) pb[i] = pb[i + 1];
                pb[WHI - 1] = bar | par;
            };
            auto side = [&](const CUtensorMap* m, uint32_t dst, int bidx, int c1, int c2) {
                const uint32_t bar = bars + bidx * 8;
                pace(bar, 0);
                mbar_expect(bar, CH);
                tma3d(dst, m, c1, c2, bar, pol);
            };
#pragma unroll 1
            for (int i = WIN; i < 6; i++)
                side(&maps.wqB + (i >> 1), sm + OFF_S0 + i * CH, B_WQB + i, j * 128 + (i & 1) * 64, h * 2);
            TS(1);
            uint32_t slot = 0, use = 0;
            int nuv = 0;
#pragma unroll 1
            for (int n = 0; n < 2 * NTILE; n++) {
                if (n == RING) {
                    mbar_wait(bars + B_FREE * 8, 0);
#pragma unroll 1
                    for (int q = 0; q < 4; q++) side(&maps.ckv, sm + OFF_S0 + q * CH, B_CKV + q, cta * 64 + q * 16, 0);
                }
                if (nuv < 2 && n > RING && (n >= 2 * NTILE - 8 || mbar_test(bars + B_FREE * 8, 1))) {
                    mbar_wait(bars + B_FREE * 8, 1);
                    side(&maps.wuv, sm + OFF_S1 + nuv * CH, B_WUV + nuv, j * 128 + nuv * 64, h * 2);
                    nuv++;
                }
                const uint32_t fb = bars + slot * 8;
                pace(fb, use & 1);
                mbar_wait(fb + B_EMPTY * 8, (use & 1) ^ 1);
                mbar_expect(fb, CH);
                bulk1d(sm + OFF_RING + slot * CH, ((n & RUN) ? vp : kp) + (size_t)(n / (2 * RUN) * RUN + n % RUN) * CH, fb, pol);
                if (((n + cta) & 3) == 0) asm volatile("red.relaxed.gpu.global.add.u32 [%0], 4;" ::"l"(&g_cnt[2]) : "memory");
                stsv(sm + OFF_NOW, n + 1);
                if (++slot == RING) { slot = 0; use++; }
            }
            TS(2);
            mbar_wait(bars + B_FREE * 8, 0);
            uint32_t tlast = clock_lo();
#pragma unroll 1
            for (int i = 0; i < 8; i++) {
                uint32_t it = 0;
                while (true) {
                    const uint32_t win = ldsv(sm + OFF_TWIN);
                    uint32_t busy = i;
#pragma unroll
                    for (int k = 0; k < 4; k++) busy += 2 * (mbar_test(pb[WHI - 4 + k] & ~1u, pb[WHI - 4 + k] & 1u) ^ 1u) - mbar_test(bars + (B_WO + k) * 8, 0);
                    if (busy < win) break;
                    if (++it > SPIN_MAX) __trap();
                }
                while (clock_lo() - tlast < BOXGAP) {}
                tlast = clock_lo();
                if (i & 1) TS(32 + (i >> 1));
                mbar_expect(bars + (B_WO + i) * 8, CH / 2);
                tma3d(sm + OFF_S0 + i * (CH / 2), &maps.woB + (i >> 2), (i & 3) * 32, h & ~3, bars + (B_WO + i) * 8, pol, (cta & 15) * 32);
            }
            TS(3);
        }
    } else if (warp == 13) {
        if (lane == 0) {
#pragma unroll
            for (int i = 0; i < NBAR; i++)
                if (i < B_WQB || i >= B_WQB + WIN)
                    mbar_init(bars + i * 8, i == B_FREE ? 8 : (i >= B_EMPTY && i < B_EMPTY + RING) ? 4 : 1);
            asm volatile("fence.mbarrier_init.release.cluster;" ::: "memory");
#pragma unroll
            for (int i = 2; i < 8; i++) asm volatile("prefetch.tensormap [%0];" ::"l"(&maps.wqB + i) : "memory");
            stsv(sm + OFF_NOW, 0); stsv(sm + OFF_WIN, WIN); stsv(sm + OFF_TWIN, PREWIN);
        }
        __syncwarp();
        bar_arrive(3, 64);
        bar_sync(0, NTHREADS);
        if (lane == 0) {
            const uint32_t base = (lds32(sm + OFF_TAG) - 1u) * (NCTA * 2 * NTILE);
            mbar_wait(bars + (B_WUK + 1) * 8, 0);
            uint32_t it = 0;
            while (true) {
                const uint32_t n = ldsv(sm + OFF_NOW);
                uint32_t v;
                asm volatile("ld.relaxed.gpu.global.u32 %0, [%1];" : "=r"(v) : "l"(&g_cnt[2]) : "memory");
                v -= base;
                if (v >= NCTA * 2 * NTILE - GATE_W) break;
                const int diff = (int)(n * NCTA) - (int)v;
                stsv(sm + OFF_WIN, diff < -THETA ? WHI : WIN - (diff > THETA) - (v >= NCTA * END_V));
                if (++it > SPIN_MAX) __trap();
                __nanosleep(BACKOFF2);
            }
            stsv(sm + OFF_WIN, WHI); stsv(sm + OFF_TWIN, TAILWIN);
            TS(24);
        }
    } else if (warp < 4) {
        const int g = lane >> 2, t = lane & 3, i = lane >> 3, rr = lane & 7;
        if (tid == 0) {
            unsigned e;
            asm volatile("ld.relaxed.gpu.global.u32 %0, [%1];" : "=r"(e) : "l"(&g_cnt[1]) : "memory");
            sts32(sm + OFF_TAG, (e >> 7) + 1u);
        }
        bar_sync(0, NTHREADS);
        const uint32_t tag = lds32(sm + OFF_TAG);
        {
            mbar_wait(bars + 8, 0);
            float q0, q1;
            ll_gather4(&g_e1[0][h * 4][tid], tag, q0, q1);
            sts16(sm + OFF_QB + tid * 2, f2bf((j >> 1) ? q1 : q0));
        }
        bar_sync(1, 128);
        if (tid == 0) TS(4);
        uint32_t qf[8][2];
#pragma unroll
        for (int c = 0; c < 8; c++) {
            const uint32_t a = sm + OFF_QB + (((c + g) & 7) * 8 + 2 * t) * 2;
            qf[c][0] = lds32(a); qf[c][1] = lds32(a + 128);
        }
        float acc[8][4];
#pragma unroll
        for (int c = 0; c < 8; c++) { acc[c][0] = acc[c][1] = acc[c][2] = acc[c][3] = 0.f; }
        float m = -INFINITY, l = 0.f;
        const bool diag = (t == (g >> 1));
        const uint32_t krow = sm + OFF_RING + (warp * 16 + rr + 8 * (i & 1)) * 256 + (i >> 1) * 128;
        const uint32_t vrow = sm + OFF_RING + (warp * 16 + rr + 8 * (i >> 1)) * 256 + (i & 1) * 128;
        uint32_t slot = 0, ph = 0;
        uint32_t* const e5own = pin((uint32_t*)g_e5[cta] + tid);
        uint32_t a[8][4] = {}, b0[RUN], b1[RUN];
        auto release = [&]() {
            __syncwarp();
            if (lane == 0) mbar_arrive(bars + (B_EMPTY + slot) * 8 + ((a[0][0] | a[1][0] | a[2][0] | a[3][0] | a[4][0] | a[5][0] | a[6][0] | a[7][0]) & zero));
            if (++slot == RING) { slot = 0; ph ^= 1; }
        };
        auto load_v = [&]() {
            mbar_wait(bars + slot * 8, ph);
#pragma unroll
            for (int c = 0; c < 8; c++) ldsm4t(a[c], vrow + slot * CH + (((c + rr) & 7) << 4));
        };
#pragma unroll 1
        for (int run = 0;; run++) {
            float slo[RUN], shi[RUN], mx = -INFINITY;
#pragma unroll
            for (int u = 0; u < RUN; u++) {
                mbar_wait(bars + slot * 8, ph);
#pragma unroll
                for (int c = 0; c < 8; c++) ldsm4(a[c], krow + slot * CH + (((c + rr) & 7) << 4));
                release();
                float s0[4] = {0.f, 0.f, 0.f, 0.f}, s1[4] = {0.f, 0.f, 0.f, 0.f};
#pragma unroll
                for (int c = 0; c < 8; c += 2) { mma(s0, a[c], qf[c][0], qf[c][1]); mma(s1, a[c + 1], qf[c + 1][0], qf[c + 1][1]); }
                slo[u] = diag ? bfround(bfround((g & 1) ? s0[1] + s1[1] : s0[0] + s1[0]) * SCALE) : -INFINITY;
                shi[u] = diag ? bfround(bfround((g & 1) ? s0[3] + s1[3] : s0[2] + s1[2]) * SCALE) : -INFINITY;
                mx = fmaxf(mx, fmaxf(slo[u], shi[u]));
            }
            int key = __float_as_int(mx);
            key ^= (key >> 31) & 0x7fffffff;
            key = __reduce_max_sync(0xffffffffu, key);
            key ^= (key >> 31) & 0x7fffffff;
            const float mn = fmaxf(m, __int_as_float(key));
            const float alpha = ex2((m - mn) * LOG2E);
            m = mn;
            l *= alpha;
#pragma unroll
            for (int u = 0; u < RUN; u++) {
                const float plo = ex2((slo[u] - mn) * LOG2E), phi = ex2((shi[u] - mn) * LOG2E);
                l += plo + phi;
                b0[u] = (g & 1) ? pack2(0.f, plo) : pack2(plo, 0.f);
                b1[u] = (g & 1) ? pack2(0.f, phi) : pack2(phi, 0.f);
            }
#pragma unroll
            for (int c = 0; c < 8; c++) { acc[c][0] *= alpha; acc[c][1] *= alpha; acc[c][2] *= alpha; acc[c][3] *= alpha; }
            if (run == NTILE / RUN - 1) break;
#pragma unroll
            for (int u = 0; u < RUN; u++) {
                load_v();
                release();
#pragma unroll
                for (int c = 0; c < 8; c++) mma(acc[c], a[c], b0[u], b1[u]);
            }
        }
#pragma unroll
        for (int o = 16; o; o >>= 1) l += __shfl_xor_sync(0xffffffffu, l, o);
        if (lane == 0) stsf2(sm + OFF_ML + warp * 8, m, l);
        mbar_wait(bars + B_S2 * 8, 0);
        bar_sync(1, 128);
        {
            const uint4 ml0 = lds128(sm + OFF_ML), ml1 = lds128(sm + OFF_ML + 16);
            const float m0 = __uint_as_float(ml0.x), m1 = __uint_as_float(ml0.z), m2 = __uint_as_float(ml1.x), m3 = __uint_as_float(ml1.z);
            const float M = fmaxf(fmaxf(m0, m1), fmaxf(m2, m3));
            const float L = (ex2((m0 - M) * LOG2E) * __uint_as_float(ml0.y) + ex2((m1 - M) * LOG2E) * __uint_as_float(ml0.w))
                          + (ex2((m2 - M) * LOG2E) * __uint_as_float(ml1.y) + ex2((m3 - M) * LOG2E) * __uint_as_float(ml1.w));
            const float f = ex2((m - M) * LOG2E) * rcp(L);
            const float lse = M * LOG2E + lg2(L);
            float* const l5own = pin((float*)g_l5[h] + j);
            const uint32_t wa = sm + OFF_S2 + warp * 640 + (t * 16 + (t >> 1) * 8 + g) * 4;
            const uint32_t ra = sm + OFF_S2 + ((tid >> 4 & 1) * 40 + (tid & 2) * 40 + (tid >> 5) * 16 + (tid & 1) * 8 + (tid >> 2 & 3) * 2) * 4;
#pragma unroll
            for (int u = 0; u < RUN; u++) {
                load_v();
                if (++slot == RING) { slot = 0; ph ^= 1; }
                if (u == RUN - 1 && tid == 96) mail_put(l5own, lse);
#pragma unroll
                for (int c = 0; c < 8; c++) mma(acc[c], a[c], b0[u], b1[u]);
            }
            if (tid == 0) TS(5);
            float v[2][8];
#pragma unroll
            for (int c = 0; c < 8; c++) { v[0][c] = acc[c][0] + acc[(c + 7) & 7][1]; v[1][c] = acc[c][2] + acc[(c + 7) & 7][3]; }
#pragma unroll
            for (int c = 0; c < 4; c++) { v[0][c] += __shfl_xor_sync(0xffffffffu, v[0][c + 4], 2); v[1][c] += __shfl_xor_sync(0xffffffffu, v[1][c + 4], 2); }
            const int src = (lane & ~3) | ((lane + 3) & 3);
#pragma unroll
            for (int c = 0; c < 2; c++) { v[0][c] += __shfl_sync(0xffffffffu, v[0][c + 2], src); v[1][c] += __shfl_sync(0xffffffffu, v[1][c + 2], src); }
#pragma unroll
            for (int c = 0; c < 4; c++) sts32(wa + (c >> 1) * 320 + (c & 1) * 32, __float_as_uint(v[c >> 1][c & 1] * f));
            if (warp < 2) {
                bar_sync(1, 128);
                const float2 r0 = ldsf2(ra), r1 = ldsf2(ra + 640), r2 = ldsf2(ra + 1280), r3 = ldsf2(ra + 1920);
                mail_put(e5own, pack2((r0.x + r1.x) + (r2.x + r3.x), (r0.y + r1.y) + (r2.y + r3.y)));
            } else {
                bar_arrive(1, 128);
            }
        }
        if (tid == 0) TS(6);
        {
            uint32_t x[4][4][4];
            float d[4][4];
            bar_sync(4, 256 + 128);
#pragma unroll
            for (int k = 0; k < 16; k++) ldsm4(x[k >> 2][k & 3], sm + OFF_CA + ((k >> 2) * 2 + (lane & 1)) * VROW + (k & 3) * 64 + (i & 1) * 32 + (i >> 1) * 16);
            const uint32_t wa = sm + OFF_S1 + lane * 64 + ((warp ^ (rr >> 1)) << 4);
            __nv_bfloat16* const outp = pin(out + (g & 1) * 1024 + (cta & 15) * 32 + warp * 8 + t * 2);
            mbar_wait(bars + (B_WO + 4) * 8, 0);
            uint32_t it = 0;
            while (true) {
                bool ok = true;
#pragma unroll
                for (int k = 0; k < 4; k++) d[k][0] = d[k][1] = d[k][2] = d[k][3] = 0.f;
#pragma unroll
                for (int q = 0; q < 5; q++) {
                    if (q < 4) ok &= box_load(a[(q & 1) * 4], a[(q & 1) * 4 + 1], a[(q & 1) * 4 + 2], a[(q & 1) * 4 + 3], bars + (B_WO + 4 + q) * 8, wa + q * 8192);
#pragma unroll
                    for (int k = 0; k < (q ? 8 : 0); k++) {
                        const uint32_t (&u)[4] = a[(~q & 1) * 4 + (k >> 1)];
                        mma(d[k & 3], x[k >> 1][q - 1], u[(k & 1) * 2], u[(k & 1) * 2 + 1]);
                    }
                }
                asm volatile("{\n.reg .pred p;\nsetp.ne.u32 p, %0, 0;\n@p exit;\n}" ::"r"((uint32_t)(ok && lane >= 8)) : "memory");
                if (ok) break;
                if (++it > SPIN_MAX) __trap();
            }
            out_add(outp, (d[0][0] + d[1][2]) + (d[2][0] + d[3][2]), (d[0][1] + d[1][3]) + (d[2][1] + d[3][3]));
            if (tid == 0) TS(15);
        }
    } else {
        const int st = tid - 128, w = warp - 4;
        const int g = lane >> 2, t = lane & 3, i = lane >> 3, rr = lane & 7;
        if (t == 0) {
#pragma unroll
            for (int k = 0; k < 4; k++) ll_store2(&g_e1[k >> 1][cta][w * 16 + g + (k & 1) * 8], 0.f, 0.f, 0u);
        }
        if (st < 64) {
            const int which = st >> 5, b = (st >> 4) & 1, c = st & 15;
            const uint4 v = __ldg((const uint4*)((which ? xA : xB) + b * 512 + j * 128) + c);
            sts128(sm + OFF_XB + (which * 2 + b) * VROW + c * 16, v);
        }
        bar_sync(0, NTHREADS);
        const uint32_t tag = lds32(sm + OFF_TAG);
        float c[4];
#pragma unroll 1
        for (int which = 0; which < 2; which++) {
            matvecT(c, sm + OFF_S0 + which * 2 * CH, sm + OFF_XB + which * 2 * VROW, 2, bars + (B_WQB + which * 2) * 8, w, lane);
            if (t == 0) {
                ll_store2(&g_e1[which][cta][w * 16 + g], c[0], c[1], tag);
                ll_store2(&g_e1[which][cta][w * 16 + g + 8], c[2], c[3], tag);
            }
        }
        __syncwarp();
        if (lane == 0) mbar_arrive(bars + B_FREE * 8);
        if (st == 0) TS(8);
        if (st < 128) {
            float q0, q1;
            sleep_ns(POLL_DELAY);
            ll_gather4(&g_e1[1][h * 4][st], tag, q0, q1);
            sts16(sm + OFF_QA + st * 2, f2bf(q0)); sts16(sm + OFF_QA + VROW + st * 2, f2bf(q1));
        }
        bar_sync(2, 256);
        if (st == 0) TS(9);
        {
            const int row = w * 16 + rr + 8 * (i & 1);
            const uint32_t a0 = sm + OFF_S2 + (row >> 6) * CH + (row & 63) * 128;
            const uint32_t va = sm + OFF_QA + g * VROW + t * 4;
            float d[4] = {0.f, 0.f, 0.f, 0.f};
            c[0] = c[1] = c[2] = c[3] = 0.f;
            mbar_wait(bars + (B_WUK + (w >> 2)) * 8, 0);
#pragma unroll
            for (int ks = 0; ks < 8; ks++) {
                const int chunk = 2 * ks + (i >> 1);
                uint32_t a[4];
                ldsm4(a, a0 + (chunk >> 3) * 8192 + (((chunk & 7) ^ rr) << 4));
                const uint32_t b0 = (g < 2) ? lds32(va + ks * 32) : 0u, b1 = (g < 2) ? lds32(va + ks * 32 + 16) : 0u;
                if (ks & 1) mma(d, a, b0, b1); else mma(c, a, b0, b1);
            }
            if (t == 0) {
                const uint32_t qs = sm + OFF_QS + (w * 16 + g) * 2;
                sts16(qs, f2bf(c[0] + d[0])); sts16(qs + VROW, f2bf(c[1] + d[1]));
                sts16(qs + 16, f2bf(c[2] + d[2])); sts16(qs + VROW + 16, f2bf(c[3] + d[3]));
            }
            bar_sync(2, 256);
            if (w == 0) {
                const int b = lane >> 4, cc = lane & 15;
                g_qabs[(b * 32 + h) * 64 + ((j * 16 + cc) ^ (h & 7))] = lds128(sm + OFF_QS + b * VROW + cc * 16);
                __syncwarp();
                if (lane == 0) {
                    cnt_rendezvous(&g_cnt[0], tag * 128u, 18);
                    TS(10);
                    mbar_expect(bars + B_GATH * 8, 2 * CH);
                    bulk1d_n(sm + OFF_S2, g_qabs + (cta >> 6) * 2048, 2 * CH, bars + B_GATH * 8);
                }
                __syncwarp();
            }
        }
        mbar_wait(bars + B_GATH * 8, 0);
        if (st == 0) TS(11);
        {
            const int mt = w & 1, kg = w >> 1;
            const uint32_t qa = sm + OFF_S2 + (mt * 16 + rr + 8 * (i & 1)) * 1024;
            const uint32_t ka = sm + OFF_S0 + kg * CH + (rr + 8 * (i >> 1)) * 128;
            float s0[4] = {0.f, 0.f, 0.f, 0.f}, s1[4] = {0.f, 0.f, 0.f, 0.f};
            mbar_wait(bars + (B_CKV + kg) * 8, 0);
#pragma unroll 2
            for (int gq = 0; gq < 8; gq++) {
#pragma unroll
                for (int k4 = 0; k4 < 4; k4++) {
                    uint32_t a[4], b[4];
                    ldsm4(a, qa + gq * 128 + (((2 * k4 + (i >> 1)) ^ rr) << 4));
                    ldsm4(b, ka + gq * 2048 + (((2 * k4 + (i & 1)) ^ rr) << 4));
                    mma(s0, a, b[0], b[1]);
                    mma(s1, a, b[2], b[3]);
                }
            }
            const uint32_t sa = sm + OFF_SC + ((mt * 16 + g) * 68 + kg * 16 + 2 * t) * 4;
            stsf2(sa, s0[0], s0[1]); stsf2(sa + 32, s1[0], s1[1]);
            stsf2(sa + 8 * 68 * 4, s0[2], s0[3]); stsf2(sa + 8 * 68 * 4 + 32, s1[2], s1[3]);
        }
        bar_sync(2, 256);
        {
            const int head = w * 4 + i;
            const uint32_t sa = sm + OFF_SC + (head * 68 + rr * 8) * 4;
            const uint4 u0 = lds128(sa), u1 = lds128(sa + 16);
            float s[8] = {__uint_as_float(u0.x), __uint_as_float(u0.y), __uint_as_float(u0.z), __uint_as_float(u0.w),
                          __uint_as_float(u1.x), __uint_as_float(u1.y), __uint_as_float(u1.z), __uint_as_float(u1.w)};
            float mx = s[0];
#pragma unroll
            for (int k = 1; k < 8; k++) mx = fmaxf(mx, s[k]);
#pragma unroll
            for (int o = 1; o < 8; o <<= 1) mx = fmaxf(mx, __shfl_xor_sync(0xffffffffu, mx, o));
            float sum = 0.f;
#pragma unroll
            for (int k = 0; k < 8; k++) { s[k] = ex2((s[k] - mx) * (SCALE * LOG2E)); sum += s[k]; }
#pragma unroll
            for (int o = 1; o < 8; o <<= 1) sum += __shfl_xor_sync(0xffffffffu, sum, o);
            const float inv = __fdividef(1.f, sum);
            uint4 p;
            p.x = pack2(s[0] * inv, s[1] * inv); p.y = pack2(s[2] * inv, s[3] * inv);
            p.z = pack2(s[4] * inv, s[5] * inv); p.w = pack2(s[6] * inv, s[7] * inv);
            sts128(sm + OFF_P + head * 128 + ((rr ^ (head & 7)) << 4), p);
            if (rr == 0) ((float*)g_lse)[head * 128 + cta] = mx * (SCALE * LOG2E) + lg2(sum);
        }
        bar_sync(2, 256);
        {
            float o[2][8][4];
#pragma unroll
            for (int mt = 0; mt < 2; mt++)
#pragma unroll
                for (int n = 0; n < 8; n++) { o[mt][n][0] = o[mt][n][1] = o[mt][n][2] = o[mt][n][3] = 0.f; }
            const uint32_t pa = sm + OFF_P + (rr + 8 * (i & 1)) * 128;
            const uint32_t va = sm + OFF_S0 + w * 2048 + (rr + 8 * (i & 1)) * 128;
#pragma unroll 1
            for (int kq = 0; kq < 4; kq++) {
                uint32_t a0[4], a1[4];
                ldsm4(a0, pa + (((2 * kq + (i >> 1)) ^ rr) << 4));
                ldsm4(a1, pa + 2048 + (((2 * kq + (i >> 1)) ^ rr) << 4));
#pragma unroll
                for (int n = 0; n < 8; n += 2) {
                    uint32_t b[4];
                    ldsm4t(b, va + kq * CH + (((n + (i >> 1)) ^ rr) << 4));
                    mma(o[0][n], a0, b[0], b[1]); mma(o[1][n], a1, b[0], b[1]);
                    mma(o[0][n + 1], a0, b[2], b[3]); mma(o[1][n + 1], a1, b[2], b[3]);
                }
            }
#pragma unroll
            for (int mt = 0; mt < 2; mt++)
#pragma unroll
                for (int hf = 0; hf < 2; hf++) {
                    const uint32_t dst = sm + OFF_S2 + (mt * 16 + hf * 8 + g) * 1024 + w * 128 + t * 16;
#pragma unroll
                    for (int nb = 0; nb < 2; nb++) {
                        uint4 v;
                        v.x = pack2(o[mt][nb * 4 + 0][hf * 2], o[mt][nb * 4 + 0][hf * 2 + 1]);
                        v.y = pack2(o[mt][nb * 4 + 1][hf * 2], o[mt][nb * 4 + 1][hf * 2 + 1]);
                        v.z = pack2(o[mt][nb * 4 + 2][hf * 2], o[mt][nb * 4 + 2][hf * 2 + 1]);
                        v.w = pack2(o[mt][nb * 4 + 3][hf * 2], o[mt][nb * 4 + 3][hf * 2 + 1]);
                        sts128(dst + nb * 64, v);
                    }
                }
            asm volatile("fence.proxy.async.shared::cta;" ::: "memory");
            __syncwarp();
            if (lane == 0) mbar_arrive(bars + B_FREE * 8);
            if (st < 82) *(st < 64 ? &g_e4[cta][st] : st < 80 ? &g_e5[cta][st - 64] : &g_l5[h][j * 2 + st - 80]) = make_uint4(EMPTY, EMPTY, EMPTY, EMPTY);
            else if (st < 84) ((uint4*)out)[cta * 2 + st - 82] = make_uint4(0u, 0u, 0u, 0u);
        }
        bar_sync(2, 256);
        if (st == 0) {
            TS(12);
#pragma unroll 1
            for (int k = 0; k < ST_SPLIT; k++) {
                asm volatile("cp.async.bulk.tensor.3d.global.shared::cta.bulk_group [%0, {%2,%3,%4}], [%1];"
                             ::"l"(&maps.ctxp), "r"(sm + OFF_S2 + k * (2 * CH / ST_SPLIT)), "r"(0), "r"(cta), "r"(k * (128 / ST_SPLIT)) : "memory");
                if (k + 1 < ST_SPLIT) __nanosleep(ST_GAP);
            }
            asm volatile("cp.async.bulk.commit_group;" ::: "memory");
            asm volatile("cp.async.bulk.wait_group 0;" ::: "memory");
            cnt_rendezvous(&g_cnt[1], tag * 128u, 20);
            TS(13);
            mbar_expect(bars + B_GATH * 8, 2 * CH + 512);
            bulk1d_n(sm + OFF_LSE, g_lse + h * 32, 512, bars + B_GATH * 8);
#pragma unroll 1
            for (int k = 0; k < G_SPLIT; k++) {
                bulk1d_n(sm + OFF_S2 + k * (2 * CH / G_SPLIT), g_ctxp + cta * 2048 + k * (2048 / G_SPLIT), 2 * CH / G_SPLIT, bars + B_GATH * 8);
                if (k + 1 < G_SPLIT) __nanosleep(G_GAP);
            }
        }
        __syncwarp();
        {
            mbar_wait(bars + B_GATH * 8, 1);
            if (st == 0) TS(22);
            uint4 v[8];
#pragma unroll
            for (int k = 0; k < 8; k++) v[k] = lds128(sm + OFF_S2 + (k * 256 + st) * 16);
            float ls[4];
#pragma unroll
            for (int k = 0; k < 4; k++) ls[k] = ldsf(sm + OFF_LSE + (k * 32 + lane) * 4);
            float m0 = fmaxf(ls[0], ls[1]), m1 = fmaxf(ls[2], ls[3]);
#pragma unroll
            for (int o = 16; o; o >>= 1) { m0 = fmaxf(m0, __shfl_xor_sync(0xffffffffu, m0, o)); m1 = fmaxf(m1, __shfl_xor_sync(0xffffffffu, m1, o)); }
            ls[0] = ex2(ls[0] - m0); ls[1] = ex2(ls[1] - m0); ls[2] = ex2(ls[2] - m1); ls[3] = ex2(ls[3] - m1);
            float z0 = ls[0] + ls[1], z1 = ls[2] + ls[3];
#pragma unroll
            for (int o = 16; o; o >>= 1) { z0 += __shfl_xor_sync(0xffffffffu, z0, o); z1 += __shfl_xor_sync(0xffffffffu, z1, o); }
            z0 = __fdividef(1.f, z0); z1 = __fdividef(1.f, z1);
            ls[0] *= z0; ls[1] *= z0; ls[2] *= z1; ls[3] *= z1;
            float a[2][8];
#pragma unroll
            for (int e = 0; e < 8; e++) a[0][e] = a[1][e] = 0.f;
            const int rg = st >> 4;
#pragma unroll
            for (int k = 0; k < 8; k++) {
                const float wt = __shfl_sync(0xffffffffu, ls[k >> 1], rg + 16 * (k & 1));
                const uint32_t u[4] = {v[k].x, v[k].y, v[k].z, v[k].w};
#pragma unroll
                for (int e = 0; e < 4; e++) {
                    a[k >> 2][2 * e] += wt * __uint_as_float(u[e] << 16);
                    a[k >> 2][2 * e + 1] += wt * __uint_as_float(u[e] & 0xffff0000u);
                }
            }
            const int b = lane >> 4, u16 = lane & 15;
            const uint32_t ra = sm + OFF_SC + (w * 256 + b * 128 + (u16 >> 3) * 64 + ((u16 >> 2) & 1) * 32 + (u16 & 3) * 2) * 4;
#pragma unroll
            for (int e = 0; e < 8; e += 2) {
                const float k0 = b ? a[1][e] : a[0][e], k1 = b ? a[1][e + 1] : a[0][e + 1];
                const float s0 = b ? a[0][e] : a[1][e], s1 = b ? a[0][e + 1] : a[1][e + 1];
                stsf2(ra + (e >> 1) * 32, k0 + __shfl_xor_sync(0xffffffffu, s0, 16), k1 + __shfl_xor_sync(0xffffffffu, s1, 16));
            }
            bar_sync(2, 256);
            if (st == 0) mbar_arrive(bars + B_S2 * 8);
            float s = 0.f;
#pragma unroll
            for (int k = 0; k < 8; k++) s += ldsf(sm + OFF_SC + (k * 256 + st) * 4);
            const float hi = bfround(s);
            const uint32_t ca = sm + OFF_CC + (st >> 7) * VROW + (st & 127) * 2;
            sts16(ca, f2bf(hi)); sts16(ca + 2 * VROW, f2bf(s - hi));
            bar_sync(2, 256);
        }
        matvecT(c, sm + OFF_S1, sm + OFF_CC, 4, bars + B_WUV * 8, w, lane);
#pragma unroll
        for (int k = 0; k < 4; k++) c[k] += __shfl_down_sync(0xffffffffu, c[k], 1);
        if (t == 0) {
            float* const e = (float*)g_e4[cta] + w * 16 + g;
            mail_put(e, c[0]); mail_put(e + 128, c[1]); mail_put(e + 8, c[2]); mail_put(e + 136, c[3]);
        }
        __syncwarp();
        if (lane == 0) mbar_arrive(bars + B_FREE * 8);
        if (st == 0) TS(23);
        {
            const uint4* const pv = &g_e4[(cta & ~15) + (w >> 1) * 4][(w & 1) * 32 + lane];
            uint4 x[4];
            uint32_t it = 0;
            sleep_ns(POLL_DELAY2);
            while (true) {
#pragma unroll
                for (int k = 0; k < 4; k++) { x[k].x = x[k].y = x[k].z = x[k].w = 0u; mail_get(x[k], pv + k * 64); }
                if (!__any_sync(0xffffffffu, mail_missing(x[0]) | mail_missing(x[1]) | mail_missing(x[2]) | mail_missing(x[3]))) break;
                if (++it > SPIN_MAX) __trap();
                __nanosleep(BACKOFF);
            }
#define SUM4(e) ((__uint_as_float(x[0].e) + __uint_as_float(x[1].e)) + (__uint_as_float(x[2].e) + __uint_as_float(x[3].e)))
            sts64(sm + OFF_CA + w * VROW + lane * 8, pack2(SUM4(x), SUM4(y)), pack2(SUM4(z), SUM4(w)));
#undef SUM4
        }
        if (st == 0) TS(14);
        bar_sync(4, 256 + 128);
        {
            const uint32_t a0 = sm + OFF_S0 + w * 1024 + (rr + 8 * (i >> 1)) * 64 + (((i & 1) ^ (rr >> 1)) << 4);
            const uint4* const pv = pin(&g_e5[(cta & ~15) + (w >> 1) * 4 + (g & 3)][(w & 1) * 8 + (g >> 2) * 4 + t]);
            const uint32_t* const pl = pin((const uint32_t*)g_l5[(h & ~3) + (w >> 1)] + t);
            const uint32_t wa = sm + OFF_SC + ((w * 2 + (t >> 1)) * 80 + (t & 1) * 40 + g) * 4;
            __nv_bfloat16* const outp = pin(out + (lane >> 4) * 1024 + 512 + (cta & 15) * 32 + (lane & 15) * 2);
            uint32_t a[4][2][4], xl = 0u, it = 0;
            uint4 x = make_uint4(0u, 0u, 0u, 0u);
            while (true) {
                if (lane < 4) asm volatile("atom.relaxed.gpu.global.or.b32 %0, [%1], 0;" : "=r"(xl) : "l"(pl) : "memory");
                if (!__any_sync(0xffffffffu, xl == EMPTY)) break;
                if (++it > SPIN_MAX) __trap();
            }
            if (st == 0) TS(25);
            mail_get(x, pv);
            float w0, w1;
            merge_weights(__shfl_sync(0xffffffffu, xl, (t & 1) * 2), __shfl_sync(0xffffffffu, xl, (t & 1) * 2 + 1), w0, w1);
#pragma unroll
            for (int q = 0; q < 4; q++) {
                mbar_wait(bars + (B_WO + q) * 8, 0);
                ldsm4t(a[q][0], a0 + q * 8192);
                ldsm4t(a[q][1], (a0 ^ 32) + q * 8192);
            }
            if (st == 0) TS(26);
            while (true) {
                const bool n = mail_missing(x);
                if (!__any_sync(0xffffffffu, n)) break;
                mail_get(x, pv, n);
                if (++it > SPIN_MAX) __trap();
            }
            if (st == 0) TS(16);
            float d[2][2][4];
#pragma unroll
            for (int k = 0; k < 4; k++) {
                float (&dk)[4] = d[k >> 1][k & 1];
                dk[0] = dk[1] = dk[2] = dk[3] = 0.f;
                mma(dk, a[k >> 1][k & 1], x.x, x.y);
            }
#pragma unroll
            for (int k = 0; k < 4; k++) mma(d[k >> 1][k & 1], a[2 + (k >> 1)][k & 1], x.z, x.w);
#pragma unroll
            for (int k = 0; k < 4; k++) {
                const float s0 = (t & 2) ? d[1][k >> 1][(k & 1) * 2] : d[0][k >> 1][(k & 1) * 2];
                const float s1 = (t & 2) ? d[1][k >> 1][(k & 1) * 2 + 1] : d[0][k >> 1][(k & 1) * 2 + 1];
                sts32(wa + k * 32, __float_as_uint(w0 * s0 + w1 * s1));
            }
            if (st == 0) TS(17);
            if (w == 0) {
                bar_sync(5, 256);
                const uint32_t ra = sm + OFF_SC + ((lane >> 4) * 40 + (lane & 15) * 2) * 4;
                float2 r[16];
#pragma unroll
                for (int k = 0; k < 16; k++) r[k] = ldsf2(ra + k * 320);
#pragma unroll
                for (int o = 1; o < 16; o <<= 1)
#pragma unroll
                    for (int k = 0; k < 16; k += 2 * o) { r[k].x += r[k + o].x; r[k].y += r[k + o].y; }
                out_add(outp, r[0].x, r[0].y);
            } else {
                bar_arrive(5, 256);
            }
        }
    }
}

typedef CUresult (*EncodeFn)(CUtensorMap*, CUtensorMapDataType, cuuint32_t, void*, const cuuint64_t*, const cuuint64_t*,
                             const cuuint32_t*, const cuuint32_t*, CUtensorMapInterleave, CUtensorMapSwizzle,
                             CUtensorMapL2promotion, CUtensorMapFloatOOBfill);

void make_map(EncodeFn enc, CUtensorMap* m, void* p, unsigned rows, unsigned cols, unsigned br, unsigned bg) {
    cuuint64_t gd[3] = {64, rows, cols / 64};
    cuuint64_t gs[2] = {(cuuint64_t)cols * 2, 128};
    cuuint32_t bx[3] = {64, br, bg};
    cuuint32_t es[3] = {1, 1, 1};
    enc(m, CU_TENSOR_MAP_DATA_TYPE_BFLOAT16, 3, p, gd, gs, bx, es, CU_TENSOR_MAP_INTERLEAVE_NONE,
        CU_TENSOR_MAP_SWIZZLE_128B, CU_TENSOR_MAP_L2_PROMOTION_L2_128B, CU_TENSOR_MAP_FLOAT_OOB_FILL_NONE);
}

}

extern "C" void kernel_launch(void* const* d_in, const int* in_sizes, int n_in, void* d_out, int out_size) {
    static EncodeFn enc = nullptr;
    if (!enc) {
        void* fn = nullptr;
        cudaDriverEntryPointQueryResult qr;
        cudaGetDriverEntryPoint("cuTensorMapEncodeTiled", &fn, cudaEnableDefault, &qr);
        enc = (EncodeFn)fn;
        cudaFuncSetAttribute(fused_decode_kernel, cudaFuncAttributeMaxDynamicSharedMemorySize, SMEM_BYTES);
    }
    Maps maps;
    make_map(enc, &maps.wqB, d_in[9], 512, 4096, 64, 2);
    make_map(enc, &maps.wqA, d_in[2], 512, 4096, 64, 2);
    make_map(enc, &maps.wuk, d_in[3], 512, 4096, 64, 2);
    make_map(enc, &maps.wuv, d_in[4], 512, 4096, 64, 2);
    for (int k = 0; k < 2; k++) {
        cuuint64_t gd[3] = {512, 128, 32};
        cuuint64_t gs[2] = {1024, 131072};
        cuuint32_t bx[3] = {32, 32, 4};
        cuuint32_t es[3] = {1, 1, 1};
        enc(&maps.woB + k, CU_TENSOR_MAP_DATA_TYPE_BFLOAT16, 3, d_in[k ? 5 : 10], gd, gs, bx, es, CU_TENSOR_MAP_INTERLEAVE_NONE,
            CU_TENSOR_MAP_SWIZZLE_64B, CU_TENSOR_MAP_L2_PROMOTION_L2_256B, CU_TENSOR_MAP_FLOAT_OOB_FILL_NONE);
    }
    make_map(enc, &maps.ckv, d_in[1], 8192, 512, 16, 8);
    {
        void* p = nullptr;
        cudaGetSymbolAddress(&p, g_ctxp);
        cuuint64_t gd[3] = {128, 128, 128};
        cuuint64_t gs[2] = {256, 32768};
        cuuint32_t bx[3] = {128, 1, 128 / ST_SPLIT};
        cuuint32_t es[3] = {1, 1, 1};
        enc(&maps.ctxp, CU_TENSOR_MAP_DATA_TYPE_BFLOAT16, 3, p, gd, gs, bx, es, CU_TENSOR_MAP_INTERLEAVE_NONE,
            CU_TENSOR_MAP_SWIZZLE_NONE, CU_TENSOR_MAP_L2_PROMOTION_NONE, CU_TENSOR_MAP_FLOAT_OOB_FILL_NONE);
    }
    fused_decode_kernel<<<NCTA, NTHREADS, SMEM_BYTES>>>((const char*)d_in[9], maps, (const char*)d_in[7], (const char*)d_in[8],
                                                         (const __nv_bfloat16*)d_in[0], (const __nv_bfloat16*)d_in[6],
                                                         (__nv_bfloat16*)d_out, 0u);
}
```

```cpp
#include <cuda_runtime.h>
#include <cuda.h>
#include <cuda_bf16.h>
#include <stdint.h>

#define RING 7
#define WIN 4
#define WHI 5
#define THETA 64
#define END_V 40
#define GATE_W 64
#define PREWIN 4
#define TAILWIN 6
#define BOXGAP 350
#define POLL_DELAY 2500
#define POLL_DELAY2 3000
#define ST_SPLIT 32
#define ST_GAP 200
#define G_SPLIT 8
#define G_GAP 250
#define BACKOFF 200
#define BACKOFF2 100

namespace {

constexpr int NCTA = 128;
constexpr int NTHREADS = 448;
constexpr uint32_t CH = 16384;
constexpr int NTILE = 32;
constexpr int RUN = 4;

constexpr uint32_t OFF_RING = 0;
constexpr uint32_t OFF_S0 = RING * CH;
constexpr uint32_t OFF_S1 = OFF_S0 + 2 * CH;
constexpr uint32_t OFF_S2 = OFF_S1 + 2 * CH;
constexpr uint32_t OFF_P = OFF_S2 + 2 * CH;
constexpr uint32_t OFF_SC = OFF_P + 4096;
constexpr uint32_t VROW = 272;
constexpr uint32_t OFF_XB = OFF_SC + 8704;
constexpr uint32_t OFF_XA = OFF_XB + 2 * VROW;
constexpr uint32_t OFF_QA = OFF_XA + 2 * VROW;
constexpr uint32_t OFF_QS = OFF_QA + 2 * VROW;
constexpr uint32_t OFF_CC = OFF_QS + 2 * VROW;
constexpr uint32_t OFF_CA = OFF_P;
constexpr uint32_t OFF_QB = OFF_CC + 4 * VROW;
constexpr uint32_t OFF_LSE = OFF_QB + 512;
constexpr uint32_t OFF_ML = OFF_LSE + 512;
constexpr uint32_t OFF_TAG = OFF_ML + 64;
constexpr uint32_t OFF_NOW = OFF_TAG + 4;
constexpr uint32_t OFF_WIN = OFF_TAG + 8;
constexpr uint32_t OFF_TWIN = OFF_TAG + 12;
constexpr uint32_t OFF_BAR = OFF_TAG + 16;
constexpr int B_EMPTY = RING;
constexpr int B_WQB = 2 * RING;
constexpr int B_WQA = B_WQB + 2;
constexpr int B_WUK = B_WQA + 2;
constexpr int B_WUV = B_WUK + 2;
constexpr int B_CKV = B_WUV + 2;
constexpr int B_WO = B_CKV + 4;
constexpr int B_FREE = B_WO + 8;
constexpr int B_GATH = B_FREE + 1;
constexpr int B_S2 = B_GATH + 1;
constexpr int NBAR = B_S2 + 1;
constexpr uint32_t TS_OFF = OFF_BAR + NBAR * 8;
constexpr uint32_t SMEM_USED = TS_OFF;
constexpr uint32_t SMEM_BYTES = SMEM_USED + 1024;
static_assert(SMEM_BYTES <= 232448, "smem");
static_assert(RING >= RUN && RING >= WHI && WHI >= WIN && WHI >= 4 && WIN >= 3 && WIN <= 6 && TAILWIN >= 4, "windows");

constexpr float LOG2E = 1.4426950408889634f;
constexpr float SCALE = 0.08838834764831845f;
#define SPIN_LOG 22
constexpr uint32_t SPIN_MAX = 1u << SPIN_LOG;

struct Maps { CUtensorMap wqB, wqA, wuk, wuv, woB, woA, ckv, ctxp; };

__device__ __align__(256) unsigned g_cnt[32];
__device__ __align__(256) ulonglong2 g_e1[2][NCTA][128];
__device__ __align__(256) uint4 g_qabs[2 * 32 * 64];
__device__ __align__(256) uint4 g_ctxp[NCTA * 128 * 16];
__device__ __align__(256) float4 g_lse[32 * 32];
__device__ __align__(256) uint4 g_e4[NCTA][64];
__device__ __align__(256) uint4 g_e5[NCTA][32];
__device__ __align__(256) uint4 g_l5[32][8];
constexpr uint32_t EMPTY = 0xffffffffu;

#define TS(k) do {} while (0)

__device__ __forceinline__ void mbar_init(uint32_t b, int c) { asm volatile("mbarrier.init.shared::cta.b64 [%0], %1;" ::"r"(b), "r"(c) : "memory"); }
__device__ __forceinline__ void mbar_expect(uint32_t b, uint32_t bytes) { asm volatile("mbarrier.arrive.expect_tx.shared::cta.b64 _, [%0], %1;" ::"r"(b), "r"(bytes) : "memory"); }
__device__ __forceinline__ void mbar_arrive(uint32_t b) { asm volatile("mbarrier.arrive.shared::cta.b64 _, [%0];" ::"r"(b) : "memory"); }
__device__ __forceinline__ void mbar_wait(uint32_t b, uint32_t ph) {
    asm volatile("{\n.reg .pred p;\n.reg .u32 n;\nmov.u32 n, 0;\n"
                 "W:\nmbarrier.try_wait.parity.shared::cta.b64 p, [%0], %1;\n@p bra D;\n"
                 "add.u32 n, n, 1;\nsetp.le.u32 p, n, %2;\n@p bra W;\ntrap;\nD:\n}" ::"r"(b), "r"(ph), "n"(SPIN_MAX) : "memory");
}
__device__ __forceinline__ uint32_t mbar_test(uint32_t b, uint32_t ph) {
    uint32_t ok;
    asm volatile("{\n.reg .pred p;\nmbarrier.test_wait.parity.shared::cta.b64 p, [%1], %2;\nselp.u32 %0, 1, 0, p;\n}" : "=r"(ok) : "r"(b), "r"(ph) : "memory");
    return ok;
}
__device__ __forceinline__ void bulk1d(uint32_t dst, const void* src, uint32_t bar, uint64_t pol) {
    asm volatile("cp.async.bulk.shared::cluster.global.mbarrier::complete_tx::bytes.L2::cache_hint [%0], [%1], %2, [%3], %4;"
                 ::"r"(dst), "l"(src), "n"(CH), "r"(bar), "l"(pol) : "memory");
}
__device__ __forceinline__ void bulk1d_n(uint32_t dst, const void* src, uint32_t bytes, uint32_t bar) {
    asm volatile("cp.async.bulk.shared::cluster.global.mbarrier::complete_tx::bytes [%0], [%1], %2, [%3];"
                 ::"r"(dst), "l"(src), "r"(bytes), "r"(bar) : "memory");
}
__device__ __forceinline__ void tma3d(uint32_t dst, const CUtensorMap* map, int c1, int c2, uint32_t bar, uint64_t pol, int c0 = 0) {
    asm volatile("cp.async.bulk.tensor.3d.shared::cluster.global.mbarrier::complete_tx::bytes.L2::cache_hint [%0], [%1, {%3,%4,%5}], [%2], %6;"
                 ::"r"(dst), "l"(map), "r"(bar), "r"(c0), "r"(c1), "r"(c2), "l"(pol) : "memory");
}
__device__ __forceinline__ void bar_sync(int id, int n) { asm volatile("barrier.cta.sync %0, %1;" ::"r"(id), "r"(n) : "memory"); }
__device__ __forceinline__ void bar_arrive(int id, int n) { asm volatile("barrier.cta.arrive %0, %1;" ::"r"(id), "r"(n) : "memory"); }
__device__ __forceinline__ void ldsm4(uint32_t (&r)[4], uint32_t a) {
    asm volatile("ldmatrix.sync.aligned.m8n8.x4.shared.b16 {%0,%1,%2,%3}, [%4];" : "=r"(r[0]), "=r"(r[1]), "=r"(r[2]), "=r"(r[3]) : "r"(a) : "memory");
}
__device__ __forceinline__ void ldsm4t(uint32_t (&r)[4], uint32_t a) {
    asm volatile("ldmatrix.sync.aligned.m8n8.x4.trans.shared.b16 {%0,%1,%2,%3}, [%4];" : "=r"(r[0]), "=r"(r[1]), "=r"(r[2]), "=r"(r[3]) : "r"(a) : "memory");
}
__device__ __forceinline__ bool box_load(uint32_t (&r)[4], uint32_t (&s)[4], uint32_t (&u)[4], uint32_t (&v)[4], uint32_t bar, uint32_t a) {
    uint32_t ok;
    asm volatile("{\n.reg .pred p;\nmbarrier.try_wait.parity.shared::cta.b64 p, [%17], 0;\n"
                 "@p ldmatrix.sync.aligned.m8n8.x4.trans.shared.b16 {%0,%1,%2,%3}, [%18];\n"
                 "@p ldmatrix.sync.aligned.m8n8.x4.trans.shared.b16 {%4,%5,%6,%7}, [%18 + 2048];\n"
                 "@p ldmatrix.sync.aligned.m8n8.x4.trans.shared.b16 {%8,%9,%10,%11}, [%18 + 4096];\n"
                 "@p ldmatrix.sync.aligned.m8n8.x4.trans.shared.b16 {%12,%13,%14,%15}, [%18 + 6144];\n"
                 "selp.u32 %16, 1, 0, p;\n}"
                 : "+r"(r[0]), "+r"(r[1]), "+r"(r[2]), "+r"(r[3]), "+r"(s[0]), "+r"(s[1]), "+r"(s[2]), "+r"(s[3]),
                   "+r"(u[0]), "+r"(u[1]), "+r"(u[2]), "+r"(u[3]), "+r"(v[0]), "+r"(v[1]), "+r"(v[2]), "+r"(v[3]), "=r"(ok)
                 : "r"(bar), "r"(a) : "memory");
    return ok != 0;
}
__device__ __forceinline__ void mma(float (&c)[4], const uint32_t (&a)[4], uint32_t b0, uint32_t b1) {
    asm volatile("mma.sync.aligned.m16n8k16.row.col.f32.bf16.bf16.f32 {%0,%1,%2,%3}, {%4,%5,%6,%7}, {%8,%9}, {%0,%1,%2,%3};"
                 : "+f"(c[0]), "+f"(c[1]), "+f"(c[2]), "+f"(c[3]) : "r"(a[0]), "r"(a[1]), "r"(a[2]), "r"(a[3]), "r"(b0), "r"(b1));
}
__device__ __forceinline__ uint32_t lds32(uint32_t a) { uint32_t v; asm volatile("ld.shared.b32 %0, [%1];" : "=r"(v) : "r"(a) : "memory"); return v; }
__device__ __forceinline__ uint32_t ldsv(uint32_t a) { uint32_t v; asm volatile("ld.volatile.shared.b32 %0, [%1];" : "=r"(v) : "r"(a) : "memory"); return v; }
__device__ __forceinline__ void stsv(uint32_t a, uint32_t v) { asm volatile("st.volatile.shared.b32 [%0], %1;" ::"r"(a), "r"(v) : "memory"); }
__device__ __forceinline__ float ldsf(uint32_t a) { float v; asm volatile("ld.shared.f32 %0, [%1];" : "=f"(v) : "r"(a) : "memory"); return v; }
__device__ __forceinline__ uint4 lds128(uint32_t a) { uint4 v; asm volatile("ld.shared.v4.b32 {%0,%1,%2,%3}, [%4];" : "=r"(v.x), "=r"(v.y), "=r"(v.z), "=r"(v.w) : "r"(a) : "memory"); return v; }
__device__ __forceinline__ void sts16(uint32_t a, uint16_t v) { asm volatile("st.shared.b16 [%0], %1;" ::"r"(a), "h"(v) : "memory"); }
__device__ __forceinline__ void sts32(uint32_t a, uint32_t v) { asm volatile("st.shared.b32 [%0], %1;" ::"r"(a), "r"(v) : "memory"); }
__device__ __forceinline__ void stsf2(uint32_t a, float x, float y) { asm volatile("st.shared.v2.f32 [%0], {%1,%2};" ::"r"(a), "f"(x), "f"(y) : "memory"); }
__device__ __forceinline__ void sts128(uint32_t a, uint4 v) { asm volatile("st.shared.v4.b32 [%0], {%1,%2,%3,%4};" ::"r"(a), "r"(v.x), "r"(v.y), "r"(v.z), "r"(v.w) : "memory"); }
__device__ __forceinline__ uint16_t f2bf(float x) { return __bfloat16_as_ushort(__float2bfloat16_rn(x)); }
__device__ __forceinline__ float bfround(float x) { return __bfloat162float(__float2bfloat16_rn(x)); }
__device__ __forceinline__ uint32_t pack2(float lo, float hi) { uint32_t r; asm("cvt.rn.bf16x2.f32 %0, %1, %2;" : "=r"(r) : "f"(hi), "f"(lo)); return r; }
__device__ __forceinline__ float ex2(float x) { float r; asm("ex2.approx.ftz.f32 %0, %1;" : "=f"(r) : "f"(x)); return r; }
__device__ __forceinline__ float lg2(float x) { float r; asm("lg2.approx.ftz.f32 %0, %1;" : "=f"(r) : "f"(x)); return r; }

__device__ __forceinline__ float rcp(float x) { float r; asm("rcp.approx.ftz.f32 %0, %1;" : "=f"(r) : "f"(x)); return r; }

__device__ __forceinline__ uint32_t clock_lo() { uint32_t t; asm volatile("mov.u32 %0, %clock;" : "=r"(t) :: "memory"); return t; }
__device__ __forceinline__ void sleep_ns(uint32_t ns) {
    const uint32_t t0 = clock_lo();
    do { __nanosleep(200); } while (clock_lo() - t0 < 2 * ns);
}

__device__ __forceinline__ void ll_store2(ulonglong2* p, float a, float b, uint32_t tag) {
    unsigned long long x = ((unsigned long long)tag << 32) | __float_as_uint(a);
    unsigned long long y = ((unsigned long long)tag << 32) | __float_as_uint(b);
    asm volatile("st.relaxed.gpu.global.v2.b64 [%0], {%1,%2};" ::"l"(p), "l"(x), "l"(y) : "memory");
}
__device__ __forceinline__ void ll_ld2(const void* p, unsigned long long& x, unsigned long long& y) {
    asm volatile("ld.relaxed.gpu.global.v2.b64 {%0,%1}, [%2];" : "=l"(x), "=l"(y) : "l"(p) : "memory");
}
__device__ __forceinline__ void ll_gather4(const ulonglong2* p, uint32_t tag, float& r0, float& r1) {
    unsigned long long x[4], y[4]; uint32_t it = 0;
    while (true) {
        bool ok = true;
#pragma unroll
        for (int k = 0; k < 4; k++) ll_ld2(p + k * 128, x[k], y[k]);
#pragma unroll
        for (int k = 0; k < 4; k++) ok = ok && (uint32_t)(x[k] >> 32) == tag && (uint32_t)(y[k] >> 32) == tag;
        if (ok) break;
        if (++it > SPIN_MAX) __trap();
        __nanosleep(BACKOFF);
    }
    r0 = (__uint_as_float((uint32_t)x[0]) + __uint_as_float((uint32_t)x[1])) + (__uint_as_float((uint32_t)x[2]) + __uint_as_float((uint32_t)x[3]));
    r1 = (__uint_as_float((uint32_t)y[0]) + __uint_as_float((uint32_t)y[1])) + (__uint_as_float((uint32_t)y[2]) + __uint_as_float((uint32_t)y[3]));
}
__device__ __forceinline__ void cnt_rendezvous(unsigned* c, uint32_t target, int tsk) {
    TS(tsk);
    asm volatile("red.release.gpu.global.add.u32 [%0], 1;" ::"l"(c) : "memory");
    if (tsk == 18) TS(tsk + 1);
    uint32_t v, it = 0;
    while (true) {
        asm volatile("ld.acquire.gpu.global.u32 %0, [%1];" : "=r"(v) : "l"(c) : "memory");
        if ((int)(v - target) >= 0) break;
        if (++it > SPIN_MAX) __trap();
        __nanosleep(BACKOFF);
    }
    asm volatile("fence.proxy.async.global;" ::: "memory");
}

__device__ __forceinline__ void matvec_loadA(uint32_t (&a)[8][4], uint32_t tile, uint32_t bar, int w, int lane) {
    const int i = lane >> 3, rr = lane & 7, chunk = 2 * w + (i & 1);
    const uint32_t a0 = tile + (chunk >> 3) * 8192 + (rr + 8 * (i >> 1)) * 128 + (((chunk & 7) ^ rr) << 4);
#pragma unroll
    for (int hh = 0; hh < 2; hh++) {
        mbar_wait(bar + hh * 8, 0);
#pragma unroll
        for (int k = 0; k < 4; k++) ldsm4t(a[hh * 4 + k], a0 + hh * CH + k * 2048);
    }
}
__device__ __forceinline__ void matvec_mma(float (&c)[4], const uint32_t (&a)[8][4], uint32_t vec, int nvec, int lane) {
    const uint32_t va = vec + (lane & (nvec - 1)) * VROW + (lane >> 3) * 16;
    float d[4][4];
#pragma unroll
    for (int q = 0; q < 4; q++) {
        uint32_t b[4];
        ldsm4(b, va + q * 64);
        d[q][0] = d[q][1] = d[q][2] = d[q][3] = 0.f;
        mma(d[q], a[2 * q], b[0], b[1]);
        mma(d[q], a[2 * q + 1], b[2], b[3]);
    }
#pragma unroll
    for (int k = 0; k < 4; k++) c[k] = (d[0][k] + d[1][k]) + (d[2][k] + d[3][k]);
}
__device__ __forceinline__ void matvecT(float (&c)[4], uint32_t tile, uint32_t vec, int nvec, uint32_t bar, int w, int lane) {
    uint32_t a[8][4];
    matvec_loadA(a, tile, bar, w, lane);
    matvec_mma(c, a, vec, nvec, lane);
}
template <class T> __device__ __forceinline__ T* pin(T* p) { asm volatile("" : "+l"(p)); return p; }
__device__ __forceinline__ void mail_put(void* p, uint32_t v) { asm volatile("st.relaxed.gpu.global.b32 [%0], %1;" ::"l"(p), "r"(v) : "memory"); }
__device__ __forceinline__ void mail_put(void* p, float v) { mail_put(p, __float_as_uint(v)); }
__device__ __forceinline__ void out_add(__nv_bfloat16* p, float x, float y) {
    asm volatile("red.relaxed.gpu.global.add.noftz.bf16x2 [%0], %1;" ::"l"(p), "r"(pack2(x, y)) : "memory");
}
__device__ __forceinline__ bool mail_missing(const uint4& v) { return v.x == EMPTY || v.y == EMPTY || v.z == EMPTY || v.w == EMPTY; }
__device__ __forceinline__ void mail_get(uint4& v, const uint4* p, bool need = true) {
    asm volatile("{\n.reg .pred q;\nsetp.ne.u32 q, %5, 0;\n@q ld.relaxed.gpu.global.v4.b32 {%0,%1,%2,%3}, [%4];\n}"
                 : "+r"(v.x), "+r"(v.y), "+r"(v.z), "+r"(v.w) : "l"(p), "r"((uint32_t)need) : "memory");
}
__device__ __forceinline__ void sts64(uint32_t a, uint32_t x, uint32_t y) { asm volatile("st.shared.v2.b32 [%0], {%1,%2};" ::"r"(a), "r"(x), "r"(y) : "memory"); }
__device__ __forceinline__ float2 ldsf2(uint32_t a) { float2 v; asm volatile("ld.shared.v2.f32 {%0,%1}, [%2];" : "=f"(v.x), "=f"(v.y) : "r"(a) : "memory"); return v; }

__global__ void __launch_bounds__(NTHREADS, 1)
fused_decode_kernel(const char* __restrict__ wqraw, const __grid_constant__ Maps maps, const char* __restrict__ Kc, const char* __restrict__ Vc,
                    const __nv_bfloat16* __restrict__ xA, const __nv_bfloat16* __restrict__ xB,
                    __nv_bfloat16* __restrict__ out, const uint32_t zero) {
    if (threadIdx.x == 0) asm volatile("cp.async.bulk.prefetch.L2.global [%0], 32768;" ::"l"(wqraw + (size_t)blockIdx.x * 32768u) : "memory");
    asm volatile("nanosleep.u32 60;" ::: "memory");
    asm volatile("barrier.cta.sync.aligned 7, %0;" ::"n"(NTHREADS) : "memory");
    asm volatile("{\n.reg .pred p;\n.reg .u32 s;\nmov.u32 s, %smid;\nsetp.eq.u32 p, s, 0xffff;\n@p exit;\n}" ::: "memory");
    extern __shared__ char smem_raw[];
    const uint32_t sm = ((uint32_t)__cvta_generic_to_shared(smem_raw) + 1023u) & ~1023u;
    const uint32_t bars = sm + OFF_BAR;
    const int cta = blockIdx.x, h = cta >> 2, j = cta & 3;
    uint64_t pol = 0;
    if (threadIdx.x == 0) {
        TS(0);
        asm volatile("createpolicy.fractional.L2::evict_first.b64 %0, 1.0;" : "=l"(pol));
#pragma unroll
        for (int i = 0; i < WIN; i++) mbar_init(bars + (B_WQB + i) * 8, 1);
        asm volatile("fence.mbarrier_init.release.cluster;" ::: "memory");
#pragma unroll
        for (int i = 0; i < WIN; i++) {
            mbar_expect(bars + (B_WQB + i) * 8, CH);
            tma3d(sm + OFF_S0 + i * CH, &maps.wqB + (i >> 1), j * 128 + (i & 1) * 64, h * 2, bars + (B_WQB + i) * 8, pol);
        }
    }
    const int tid = threadIdx.x < 64 ? threadIdx.x + 384 : threadIdx.x - 64, warp = tid >> 5, lane = tid & 31;

    if (warp == 12) {
        const size_t kvoff = (size_t)cta * (NTILE / 2 * CH);
        const char* kp = Kc + kvoff;
        const char* vp = Vc + kvoff;
        __syncwarp();
        bar_arrive(0, NTHREADS);
        bar_sync(3, 64);
        if (lane == 0) {
            uint32_t pb[WHI];
#pragma unroll
            for (int i = 0; i < WHI; i++) pb[i] = i < WHI - WIN ? (bars + B_WO * 8) | 1u : bars + (B_WQB + i - (WHI - WIN)) * 8;
            auto pace = [&](uint32_t bar, uint32_t par) {
                uint32_t it = 0;
                while (true) {
                    const uint32_t win = ldsv(sm + OFF_WIN);
                    uint32_t busy = 0;
#pragma unroll
                    for (int i = 0; i < WHI; i++) busy += mbar_test(pb[i] & ~1u, pb[i] & 1u) ^ 1u;
                    if (busy < win) break;
                    if (++it > SPIN_MAX) __trap();
                }
#pragma unroll
                for (int i = 0; i + 1 < WHI; i++) pb[i] = pb[i + 1];
                pb[WHI - 1] = bar | par;
            };
            auto side = [&](const CUtensorMap* m, uint32_t dst, int bidx, int c1, int c2) {
                const uint32_t bar = bars + bidx * 8;
                pace(bar, 0);
                mbar_expect(bar, CH);
                tma3d(dst, m, c1, c2, bar, pol);
            };
#pragma unroll 1
            for (int i = WIN; i < 6; i++)
                side(&maps.wqB + (i >> 1), sm + OFF_S0 + i * CH, B_WQB + i, j * 128 + (i & 1) * 64, h * 2);
            TS(1);
            uint32_t slot = 0, use = 0;
            int nuv = 0;
#pragma unroll 1
            for (int n = 0; n < 2 * NTILE; n++) {
                if (n == RING) {
                    mbar_wait(bars + B_FREE * 8, 0);
#pragma unroll 1
                    for (int q = 0; q < 4; q++) side(&maps.ckv, sm + OFF_S0 + q * CH, B_CKV + q, cta * 64 + q * 16, 0);
                }
                if (nuv < 2 && n > RING && (n >= 2 * NTILE - 8 || mbar_test(bars + B_FREE * 8, 1))) {
                    mbar_wait(bars + B_FREE * 8, 1);
                    side(&maps.wuv, sm + OFF_S1 + nuv * CH, B_WUV + nuv, j * 128 + nuv * 64, h * 2);
                    nuv++;
                }
                const uint32_t fb = bars + slot * 8;
                pace(fb, use & 1);
                mbar_wait(fb + B_EMPTY * 8, (use & 1) ^ 1);
                mbar_expect(fb, CH);
                bulk1d(sm + OFF_RING + slot * CH, ((n & RUN) ? vp : kp) + (size_t)(n / NTILE * (NCTA * NTILE / 2) + n % NTILE / (2 * RUN) * RUN + n % RUN) * CH, fb, pol);
                if (((n + cta) & 3) == 0) asm volatile("red.relaxed.gpu.global.add.u32 [%0], 4;" ::"l"(&g_cnt[2]) : "memory");
                stsv(sm + OFF_NOW, n + 1);
                if (++slot == RING) { slot = 0; use++; }
            }
            TS(2);
            mbar_wait(bars + B_FREE * 8, 0);
            uint32_t tlast = clock_lo();
#pragma unroll 1
            for (int i = 0; i < 8; i++) {
                uint32_t it = 0;
                while (true) {
                    const uint32_t win = ldsv(sm + OFF_TWIN);
                    uint32_t busy = i;
#pragma unroll
                    for (int k = 0; k < 4; k++) busy += 2 * (mbar_test(pb[WHI - 4 + k] & ~1u, pb[WHI - 4 + k] & 1u) ^ 1u) - mbar_test(bars + (B_WO + k) * 8, 0);
                    if (busy < win) break;
                    if (++it > SPIN_MAX) __trap();
                }
                while (clock_lo() - tlast < BOXGAP) {}
                tlast = clock_lo();
                if (i & 1) TS(32 + (i >> 1));
                mbar_expect(bars + (B_WO + i) * 8, CH / 2);
                tma3d(sm + OFF_S0 + i * (CH / 2), &maps.woB + (i >> 2), (i & 3) * 32, h & ~3, bars + (B_WO + i) * 8, pol, (cta & 15) * 32);
            }
            TS(3);
        }
    } else if (warp == 13) {
        if (lane == 0) {
#pragma unroll
            for (int i = 0; i < NBAR; i++)
                if (i < B_WQB || i >= B_WQB + WIN)
                    mbar_init(bars + i * 8, i == B_FREE ? 8 : (i >= B_EMPTY && i < B_EMPTY + RING) ? 4 : 1);
            asm volatile("fence.mbarrier_init.release.cluster;" ::: "memory");
#pragma unroll
            for (int i = 2; i < 8; i++) asm volatile("prefetch.tensormap [%0];" ::"l"(&maps.wqB + i) : "memory");
            stsv(sm + OFF_NOW, 0); stsv(sm + OFF_WIN, WIN); stsv(sm + OFF_TWIN, PREWIN);
        }
        __syncwarp();
        bar_arrive(3, 64);
        bar_sync(0, NTHREADS);
        if (lane == 0) {
            const uint32_t base = (lds32(sm + OFF_TAG) - 1u) * (NCTA * 2 * NTILE);
            mbar_wait(bars + (B_WUK + 1) * 8, 0);
            uint32_t it = 0;
            while (true) {
                const uint32_t n = ldsv(sm + OFF_NOW);
                uint32_t v;
                asm volatile("ld.relaxed.gpu.global.u32 %0, [%1];" : "=r"(v) : "l"(&g_cnt[2]) : "memory");
                v -= base;
                if (v >= NCTA * 2 * NTILE - GATE_W) break;
                const int diff = (int)(n * NCTA) - (int)v;
                stsv(sm + OFF_WIN, diff < -THETA ? WHI : WIN - (diff > THETA) - (v >= NCTA * END_V));
                if (++it > SPIN_MAX) __trap();
                __nanosleep(BACKOFF2);
            }
            stsv(sm + OFF_WIN, WHI); stsv(sm + OFF_TWIN, TAILWIN);
            TS(24);
        }
    } else if (warp < 4) {
        const int g = lane >> 2, t = lane & 3, i = lane >> 3, rr = lane & 7;
        if (tid == 0) {
            unsigned e;
            asm volatile("ld.relaxed.gpu.global.u32 %0, [%1];" : "=r"(e) : "l"(&g_cnt[1]) : "memory");
            sts32(sm + OFF_TAG, (e >> 7) + 1u);
        }
        bar_sync(0, NTHREADS);
        const uint32_t tag = lds32(sm + OFF_TAG);
        {
            mbar_wait(bars + 8, 0);
            float q0, q1;
            ll_gather4(&g_e1[0][h * 4][tid], tag, q0, q1);
            sts16(sm + OFF_QB + tid * 2, f2bf(q0)); sts16(sm + OFF_QB + 256 + tid * 2, f2bf(q1));
        }
        bar_sync(1, 128);
        if (tid == 0) TS(4);
        uint32_t qf[8][2];
        float acc[8][4], m, l;
        auto start = [&](int b) {
#pragma unroll
            for (int c = 0; c < 8; c++) {
                const uint32_t a = sm + OFF_QB + b * 256 + (((c + g) & 7) * 8 + 2 * t) * 2;
                qf[c][0] = lds32(a); qf[c][1] = lds32(a + 128);
                acc[c][0] = acc[c][1] = acc[c][2] = acc[c][3] = 0.f;
            }
            m = -INFINITY; l = 0.f;
        };
        auto stats = [&](int b) {
#pragma unroll
            for (int o = 16; o; o >>= 1) l += __shfl_xor_sync(0xffffffffu, l, o);
            if (lane == 0) stsf2(sm + OFF_ML + b * 32 + warp * 8, m, l);
        };
        auto quad_sum = [&](float (&r)[4]) {
            float v[2][8];
#pragma unroll
            for (int c = 0; c < 8; c++) { v[0][c] = acc[c][0] + acc[(c + 7) & 7][1]; v[1][c] = acc[c][2] + acc[(c + 7) & 7][3]; }
#pragma unroll
            for (int c = 0; c < 4; c++) { v[0][c] += __shfl_xor_sync(0xffffffffu, v[0][c + 4], 2); v[1][c] += __shfl_xor_sync(0xffffffffu, v[1][c + 4], 2); }
            const int src = (lane & ~3) | ((lane + 3) & 3);
#pragma unroll
            for (int c = 0; c < 4; c++) r[c] = v[c >> 1][c & 1] + __shfl_sync(0xffffffffu, v[c >> 1][(c & 1) + 2], src);
        };
        float o0[4] = {0.f, 0.f, 0.f, 0.f};
        start(0);
        const bool diag = (t == (g >> 1));
        const uint32_t krow = sm + OFF_RING + (warp * 16 + rr + 8 * (i & 1)) * 256 + (i >> 1) * 128;
        const uint32_t vrow = sm + OFF_RING + (warp * 16 + rr + 8 * (i >> 1)) * 256 + (i & 1) * 128;
        uint32_t slot = 0, ph = 0;
        uint32_t* const e5own = pin((uint32_t*)g_e5[cta] + (tid ^ 64));
        uint32_t a[8][4] = {}, b0[RUN], b1[RUN];
        auto release = [&]() {
            __syncwarp();
            if (lane == 0) mbar_arrive(bars + (B_EMPTY + slot) * 8 + ((a[0][0] | a[1][0] | a[2][0] | a[3][0] | a[4][0] | a[5][0] | a[6][0] | a[7][0]) & zero));
            if (++slot == RING) { slot = 0; ph ^= 1; }
        };
        auto load_v = [&]() {
            mbar_wait(bars + slot * 8, ph);
#pragma unroll
            for (int c = 0; c < 8; c++) ldsm4t(a[c], vrow + slot * CH + (((c + rr) & 7) << 4));
        };
#pragma unroll 1
        for (int run = 0;; run++) {
            float slo[RUN], shi[RUN], mx = -INFINITY;
#pragma unroll
            for (int u = 0; u < RUN; u++) {
                mbar_wait(bars + slot * 8, ph);
#pragma unroll
                for (int c = 0; c < 8; c++) ldsm4(a[c], krow + slot * CH + (((c + rr) & 7) << 4));
                release();
                float s0[4] = {0.f, 0.f, 0.f, 0.f}, s1[4] = {0.f, 0.f, 0.f, 0.f};
#pragma unroll
                for (int c = 0; c < 8; c += 2) { mma(s0, a[c], qf[c][0], qf[c][1]); mma(s1, a[c + 1], qf[c + 1][0], qf[c + 1][1]); }
                slo[u] = diag ? bfround(bfround((g & 1) ? s0[1] + s1[1] : s0[0] + s1[0]) * SCALE) : -INFINITY;
                shi[u] = diag ? bfround(bfround((g & 1) ? s0[3] + s1[3] : s0[2] + s1[2]) * SCALE) : -INFINITY;
                mx = fmaxf(mx, fmaxf(slo[u], shi[u]));
            }
            int key = __float_as_int(mx);
            key ^= (key >> 31) & 0x7fffffff;
            key = __reduce_max_sync(0xffffffffu, key);
            key ^= (key >> 31) & 0x7fffffff;
            const float mn = fmaxf(m, __int_as_float(key));
            const float alpha = ex2((m - mn) * LOG2E);
            m = mn;
            l *= alpha;
#pragma unroll
            for (int u = 0; u < RUN; u++) {
                const float plo = ex2((slo[u] - mn) * LOG2E), phi = ex2((shi[u] - mn) * LOG2E);
                l += plo + phi;
                b0[u] = (g & 1) ? pack2(0.f, plo) : pack2(plo, 0.f);
                b1[u] = (g & 1) ? pack2(0.f, phi) : pack2(phi, 0.f);
            }
#pragma unroll
            for (int c = 0; c < 8; c++) { acc[c][0] *= alpha; acc[c][1] *= alpha; acc[c][2] *= alpha; acc[c][3] *= alpha; }
            if (run == NTILE / RUN - 1) break;
#pragma unroll
            for (int u = 0; u < RUN; u++) {
                load_v();
                release();
#pragma unroll
                for (int c = 0; c < 8; c++) mma(acc[c], a[c], b0[u], b1[u]);
            }
            if (run == NTILE / RUN / 2 - 1) { stats(0); quad_sum(o0); start(1); }
        }
        stats(1);
        mbar_wait(bars + B_S2 * 8, 0);
        bar_sync(1, 128);
        {
            float f[2], lse[2];
#pragma unroll
            for (int b = 0; b < 2; b++) {
                const uint4 ml0 = lds128(sm + OFF_ML + b * 32), ml1 = lds128(sm + OFF_ML + b * 32 + 16);
                const float m0 = __uint_as_float(ml0.x), m1 = __uint_as_float(ml0.z), m2 = __uint_as_float(ml1.x), m3 = __uint_as_float(ml1.z);
                const float M = fmaxf(fmaxf(m0, m1), fmaxf(m2, m3));
                const float L = (ex2((m0 - M) * LOG2E) * __uint_as_float(ml0.y) + ex2((m1 - M) * LOG2E) * __uint_as_float(ml0.w))
                              + (ex2((m2 - M) * LOG2E) * __uint_as_float(ml1.y) + ex2((m3 - M) * LOG2E) * __uint_as_float(ml1.w));
                f[b] = ex2((ldsf(sm + OFF_ML + b * 32 + warp * 8) - M) * LOG2E) * rcp(L);
                lse[b] = M * LOG2E + lg2(L);
            }
            float* const l5own = pin((float*)g_l5[h] + j);
            const uint32_t wa = sm + OFF_S2 + warp * 640 + (t * 16 + (t >> 1) * 8 + g) * 4;
            const uint32_t ra = sm + OFF_S2 + ((tid >> 4 & 1) * 40 + (tid & 2) * 40 + (tid >> 5 & 1) * 16 + (tid & 1) * 8 + (tid >> 2 & 3) * 2) * 4;
            auto publish = [&](int b, const float (&r)[4]) {
#pragma unroll
                for (int c = 0; c < 4; c++) sts32(wa + b * 2560 + (c >> 1) * 320 + (c & 1) * 32, __float_as_uint(r[c] * f[b]));
                if ((warp >> 1) != b) {
                    bar_sync(8 + b, 128);
                    const float2 r0 = ldsf2(ra + b * 2560), r1 = ldsf2(ra + b * 2560 + 640), r2 = ldsf2(ra + b * 2560 + 1280), r3 = ldsf2(ra + b * 2560 + 1920);
                    mail_put(e5own, pack2((r0.x + r1.x) + (r2.x + r3.x), (r0.y + r1.y) + (r2.y + r3.y)));
                } else {
                    bar_arrive(8 + b, 128);
                }
            };
            publish(0, o0);
            if (tid == 96) mail_put(l5own, lse[0]);
#pragma unroll
            for (int u = 0; u < RUN; u++) {
                load_v();
                if (++slot == RING) { slot = 0; ph ^= 1; }
                if (u == RUN - 1 && tid == 96) mail_put(l5own + 4, lse[1]);
#pragma unroll
                for (int c = 0; c < 8; c++) mma(acc[c], a[c], b0[u], b1[u]);
            }
            if (tid == 0) TS(5);
            quad_sum(o0);
            publish(1, o0);
        }
        if (tid == 0) TS(6);
        {
            uint32_t x[4][4][4];
            float d[4][4];
            bar_sync(4, 256 + 128);
#pragma unroll
            for (int k = 0; k < 16; k++) ldsm4(x[k >> 2][k & 3], sm + OFF_CA + ((k >> 2) * 2 + (lane & 1)) * VROW + (k & 3) * 64 + (i & 1) * 32 + (i >> 1) * 16);
            const uint32_t wa = sm + OFF_S1 + lane * 64 + ((warp ^ (rr >> 1)) << 4);
            __nv_bfloat16* const outp = pin(out + (g & 1) * 1024 + (cta & 15) * 32 + warp * 8 + t * 2);
            mbar_wait(bars + (B_WO + 4) * 8, 0);
            uint32_t it = 0;
            while (true) {
                bool ok = true;
#pragma unroll
                for (int k = 0; k < 4; k++) d[k][0] = d[k][1] = d[k][2] = d[k][3] = 0.f;
#pragma unroll
                for (int q = 0; q < 5; q++) {
                    if (q < 4) ok &= box_load(a[(q & 1) * 4], a[(q & 1) * 4 + 1], a[(q & 1) * 4 + 2], a[(q & 1) * 4 + 3], bars + (B_WO + 4 + q) * 8, wa + q * 8192);
#pragma unroll
                    for (int k = 0; k < (q ? 8 : 0); k++) {
                        const uint32_t (&u)[4] = a[(~q & 1) * 4 + (k >> 1)];
                        mma(d[k & 3], x[k >> 1][q - 1], u[(k & 1) * 2], u[(k & 1) * 2 + 1]);
                    }
                }
                asm volatile("{\n.reg .pred p;\nsetp.ne.u32 p, %0, 0;\n@p exit;\n}" ::"r"((uint32_t)(ok && lane >= 8)) : "memory");
                if (ok) break;
                if (++it > SPIN_MAX) __trap();
            }
            out_add(outp, (d[0][0] + d[1][2]) + (d[2][0] + d[3][2]), (d[0][1] + d[1][3]) + (d[2][1] + d[3][3]));
            if (tid == 0) TS(15);
        }
    } else {
        const int st = tid - 128, w = warp - 4;
        const int g = lane >> 2, t = lane & 3, i = lane >> 3, rr = lane & 7;
        if (t == 0) {
#pragma unroll
            for (int k = 0; k < 4; k++) ll_store2(&g_e1[k >> 1][cta][w * 16 + g + (k & 1) * 8], 0.f, 0.f, 0u);
        }
        if (st < 64) {
            const int which = st >> 5, b = (st >> 4) & 1, c = st & 15;
            const uint4 v = __ldg((const uint4*)((which ? xA : xB) + b * 512 + j * 128) + c);
            sts128(sm + OFF_XB + (which * 2 + b) * VROW + c * 16, v);
        }
        bar_sync(0, NTHREADS);
        const uint32_t tag = lds32(sm + OFF_TAG);
        float c[4];
#pragma unroll 1
        for (int which = 0; which < 2; which++) {
            matvecT(c, sm + OFF_S0 + which * 2 * CH, sm + OFF_XB + which * 2 * VROW, 2, bars + (B_WQB + which * 2) * 8, w, lane);
            if (t == 0) {
                ll_store2(&g_e1[which][cta][w * 16 + g], c[0], c[1], tag);
                ll_store2(&g_e1[which][cta][w * 16 + g + 8], c[2], c[3], tag);
            }
        }
        __syncwarp();
        if (lane == 0) mbar_arrive(bars + B_FREE * 8);
        if (st == 0) TS(8);
        if (st < 128) {
            float q0, q1;
            sleep_ns(POLL_DELAY);
            ll_gather4(&g_e1[1][h * 4][st], tag, q0, q1);
            sts16(sm + OFF_QA + st * 2, f2bf(q0)); sts16(sm + OFF_QA + VROW + st * 2, f2bf(q1));
        }
        bar_sync(2, 256);
        if (st == 0) TS(9);
        {
            const int row = w * 16 + rr + 8 * (i & 1);
            const uint32_t a0 = sm + OFF_S2 + (row >> 6) * CH + (row & 63) * 128;
            const uint32_t va = sm + OFF_QA + g * VROW + t * 4;
            float d[4] = {0.f, 0.f, 0.f, 0.f};
            c[0] = c[1] = c[2] = c[3] = 0.f;
            mbar_wait(bars + (B_WUK + (w >> 2)) * 8, 0);
#pragma unroll
            for (int ks = 0; ks < 8; ks++) {
                const int chunk = 2 * ks + (i >> 1);
                uint32_t a[4];
                ldsm4(a, a0 + (chunk >> 3) * 8192 + (((chunk & 7) ^ rr) << 4));
                const uint32_t b0 = (g < 2) ? lds32(va + ks * 32) : 0u, b1 = (g < 2) ? lds32(va + ks * 32 + 16) : 0u;
                if (ks & 1) mma(d, a, b0, b1); else mma(c, a, b0, b1);
            }
            if (t == 0) {
                const uint32_t qs = sm + OFF_QS + (w * 16 + g) * 2;
                sts16(qs, f2bf(c[0] + d[0])); sts16(qs + VROW, f2bf(c[1] + d[1]));
                sts16(qs + 16, f2bf(c[2] + d[2])); sts16(qs + VROW + 16, f2bf(c[3] + d[3]));
            }
            bar_sync(2, 256);
            if (w == 0) {
                const int b = lane >> 4, cc = lane & 15;
                g_qabs[(b * 32 + h) * 64 + ((j * 16 + cc) ^ (h & 7))] = lds128(sm + OFF_QS + b * VROW + cc * 16);
                __syncwarp();
                if (lane == 0) {
                    cnt_rendezvous(&g_cnt[0], tag * 128u, 18);
                    TS(10);
                    mbar_expect(bars + B_GATH * 8, 2 * CH);
                    bulk1d_n(sm + OFF_S2, g_qabs + (cta >> 6) * 2048, 2 * CH, bars + B_GATH * 8);
                }
                __syncwarp();
            }
        }
        mbar_wait(bars + B_GATH * 8, 0);
        if (st == 0) TS(11);
        {
            const int mt = w & 1, kg = w >> 1;
            const uint32_t qa = sm + OFF_S2 + (mt * 16 + rr + 8 * (i & 1)) * 1024;
            const uint32_t ka = sm + OFF_S0 + kg * CH + (rr + 8 * (i >> 1)) * 128;
            float s0[4] = {0.f, 0.f, 0.f, 0.f}, s1[4] = {0.f, 0.f, 0.f, 0.f};
            mbar_wait(bars + (B_CKV + kg) * 8, 0);
#pragma unroll 2
            for (int gq = 0; gq < 8; gq++) {
#pragma unroll
                for (int k4 = 0; k4 < 4; k4++) {
                    uint32_t a[4], b[4];
                    ldsm4(a, qa + gq * 128 + (((2 * k4 + (i >> 1)) ^ rr) << 4));
                    ldsm4(b, ka + gq * 2048 + (((2 * k4 + (i & 1)) ^ rr) << 4));
                    mma(s0, a, b[0], b[1]);
                    mma(s1, a, b[2], b[3]);
                }
            }
            const uint32_t sa = sm + OFF_SC + ((mt * 16 + g) * 68 + kg * 16 + 2 * t) * 4;
            stsf2(sa, s0[0], s0[1]); stsf2(sa + 32, s1[0], s1[1]);
            stsf2(sa + 8 * 68 * 4, s0[2], s0[3]); stsf2(sa + 8 * 68 * 4 + 32, s1[2], s1[3]);
        }
        bar_sync(2, 256);
        {
            const int head = w * 4 + i;
            const uint32_t sa = sm + OFF_SC + (head * 68 + rr * 8) * 4;
            const uint4 u0 = lds128(sa), u1 = lds128(sa + 16);
            float s[8] = {__uint_as_float(u0.x), __uint_as_float(u0.y), __uint_as_float(u0.z), __uint_as_float(u0.w),
                          __uint_as_float(u1.x), __uint_as_float(u1.y), __uint_as_float(u1.z), __uint_as_float(u1.w)};
            float mx = s[0];
#pragma unroll
            for (int k = 1; k < 8; k++) mx = fmaxf(mx, s[k]);
#pragma unroll
            for (int o = 1; o < 8; o <<= 1) mx = fmaxf(mx, __shfl_xor_sync(0xffffffffu, mx, o));
            float sum = 0.f;
#pragma unroll
            for (int k = 0; k < 8; k++) { s[k] = ex2((s[k] - mx) * (SCALE * LOG2E)); sum += s[k]; }
#pragma unroll
            for (int o = 1; o < 8; o <<= 1) sum += __shfl_xor_sync(0xffffffffu, sum, o);
            const float inv = __fdividef(1.f, sum);
            uint4 p;
            p.x = pack2(s[0] * inv, s[1] * inv); p.y = pack2(s[2] * inv, s[3] * inv);
            p.z = pack2(s[4] * inv, s[5] * inv); p.w = pack2(s[6] * inv, s[7] * inv);
            sts128(sm + OFF_P + head * 128 + ((rr ^ (head & 7)) << 4), p);
            if (rr == 0) ((float*)g_lse)[head * 128 + cta] = mx * (SCALE * LOG2E) + lg2(sum);
        }
        bar_sync(2, 256);
        {
            float o[2][8][4];
#pragma unroll
            for (int mt = 0; mt < 2; mt++)
#pragma unroll
                for (int n = 0; n < 8; n++) { o[mt][n][0] = o[mt][n][1] = o[mt][n][2] = o[mt][n][3] = 0.f; }
            const uint32_t pa = sm + OFF_P + (rr + 8 * (i & 1)) * 128;
            const uint32_t va = sm + OFF_S0 + w * 2048 + (rr + 8 * (i & 1)) * 128;
#pragma unroll 1
            for (int kq = 0; kq < 4; kq++) {
                uint32_t a0[4], a1[4];
                ldsm4(a0, pa + (((2 * kq + (i >> 1)) ^ rr) << 4));
                ldsm4(a1, pa + 2048 + (((2 * kq + (i >> 1)) ^ rr) << 4));
#pragma unroll
                for (int n = 0; n < 8; n += 2) {
                    uint32_t b[4];
                    ldsm4t(b, va + kq * CH + (((n + (i >> 1)) ^ rr) << 4));
                    mma(o[0][n], a0, b[0], b[1]); mma(o[1][n], a1, b[0], b[1]);
                    mma(o[0][n + 1], a0, b[2], b[3]); mma(o[1][n + 1], a1, b[2], b[3]);
                }
            }
#pragma unroll
            for (int mt = 0; mt < 2; mt++)
#pragma unroll
                for (int hf = 0; hf < 2; hf++) {
                    const uint32_t dst = sm + OFF_S2 + (mt * 16 + hf * 8 + g) * 1024 + w * 128 + t * 16;
#pragma unroll
                    for (int nb = 0; nb < 2; nb++) {
                        uint4 v;
                        v.x = pack2(o[mt][nb * 4 + 0][hf * 2], o[mt][nb * 4 + 0][hf * 2 + 1]);
                        v.y = pack2(o[mt][nb * 4 + 1][hf * 2], o[mt][nb * 4 + 1][hf * 2 + 1]);
                        v.z = pack2(o[mt][nb * 4 + 2][hf * 2], o[mt][nb * 4 + 2][hf * 2 + 1]);
                        v.w = pack2(o[mt][nb * 4 + 3][hf * 2], o[mt][nb * 4 + 3][hf * 2 + 1]);
                        sts128(dst + nb * 64, v);
                    }
                }
            asm volatile("fence.proxy.async.shared::cta;" ::: "memory");
            __syncwarp();
            if (lane == 0) mbar_arrive(bars + B_FREE * 8);
            if (st < 98) *(st < 64 ? &g_e4[cta][st] : st < 96 ? &g_e5[cta][st - 64] : &g_l5[h][j * 2 + st - 96]) = make_uint4(EMPTY, EMPTY, EMPTY, EMPTY);
            else if (st < 100) ((uint4*)out)[cta * 2 + st - 98] = make_uint4(0u, 0u, 0u, 0u);
        }
        bar_sync(2, 256);
        if (st == 0) {
            TS(12);
#pragma unroll 1
            for (int k = 0; k < ST_SPLIT; k++) {
                asm volatile("cp.async.bulk.tensor.3d.global.shared::cta.bulk_group [%0, {%2,%3,%4}], [%1];"
                             ::"l"(&maps.ctxp), "r"(sm + OFF_S2 + k * (2 * CH / ST_SPLIT)), "r"(0), "r"(cta), "r"(k * (128 / ST_SPLIT)) : "memory");
                if (k + 1 < ST_SPLIT) __nanosleep(ST_GAP);
            }
            asm volatile("cp.async.bulk.commit_group;" ::: "memory");
            asm volatile("cp.async.bulk.wait_group 0;" ::: "memory");
            cnt_rendezvous(&g_cnt[1], tag * 128u, 20);
            TS(13);
            mbar_expect(bars + B_GATH * 8, 2 * CH + 512);
            bulk1d_n(sm + OFF_LSE, g_lse + h * 32, 512, bars + B_GATH * 8);
#pragma unroll 1
            for (int k = 0; k < G_SPLIT; k++) {
                bulk1d_n(sm + OFF_S2 + k * (2 * CH / G_SPLIT), g_ctxp + cta * 2048 + k * (2048 / G_SPLIT), 2 * CH / G_SPLIT, bars + B_GATH * 8);
                if (k + 1 < G_SPLIT) __nanosleep(G_GAP);
            }
        }
        __syncwarp();
        {
            mbar_wait(bars + B_GATH * 8, 1);
            if (st == 0) TS(22);
            uint4 v[8];
#pragma unroll
            for (int k = 0; k < 8; k++) v[k] = lds128(sm + OFF_S2 + (k * 256 + st) * 16);
            float ls[4];
#pragma unroll
            for (int k = 0; k < 4; k++) ls[k] = ldsf(sm + OFF_LSE + (k * 32 + lane) * 4);
            float m0 = fmaxf(ls[0], ls[1]), m1 = fmaxf(ls[2], ls[3]);
#pragma unroll
            for (int o = 16; o; o >>= 1) { m0 = fmaxf(m0, __shfl_xor_sync(0xffffffffu, m0, o)); m1 = fmaxf(m1, __shfl_xor_sync(0xffffffffu, m1, o)); }
            ls[0] = ex2(ls[0] - m0); ls[1] = ex2(ls[1] - m0); ls[2] = ex2(ls[2] - m1); ls[3] = ex2(ls[3] - m1);
            float z0 = ls[0] + ls[1], z1 = ls[2] + ls[3];
#pragma unroll
            for (int o = 16; o; o >>= 1) { z0 += __shfl_xor_sync(0xffffffffu, z0, o); z1 += __shfl_xor_sync(0xffffffffu, z1, o); }
            z0 = __fdividef(1.f, z0); z1 = __fdividef(1.f, z1);
            ls[0] *= z0; ls[1] *= z0; ls[2] *= z1; ls[3] *= z1;
            float a[2][8];
#pragma unroll
            for (int e = 0; e < 8; e++) a[0][e] = a[1][e] = 0.f;
            const int rg = st >> 4;
#pragma unroll
            for (int k = 0; k < 8; k++) {
                const float wt = __shfl_sync(0xffffffffu, ls[k >> 1], rg + 16 * (k & 1));
                const uint32_t u[4] = {v[k].x, v[k].y, v[k].z, v[k].w};
#pragma unroll
                for (int e = 0; e < 4; e++) {
                    a[k >> 2][2 * e] += wt * __uint_as_float(u[e] << 16);
                    a[k >> 2][2 * e + 1] += wt * __uint_as_float(u[e] & 0xffff0000u);
                }
            }
            const int b = lane >> 4, u16 = lane & 15;
            const uint32_t ra = sm + OFF_SC + (w * 256 + b * 128 + (u16 >> 3) * 64 + ((u16 >> 2) & 1) * 32 + (u16 & 3) * 2) * 4;
#pragma unroll
            for (int e = 0; e < 8; e += 2) {
                const float k0 = b ? a[1][e] : a[0][e], k1 = b ? a[1][e + 1] : a[0][e + 1];
                const float s0 = b ? a[0][e] : a[1][e], s1 = b ? a[0][e + 1] : a[1][e + 1];
                stsf2(ra + (e >> 1) * 32, k0 + __shfl_xor_sync(0xffffffffu, s0, 16), k1 + __shfl_xor_sync(0xffffffffu, s1, 16));
            }
            bar_sync(2, 256);
            if (st == 0) mbar_arrive(bars + B_S2 * 8);
            float s = 0.f;
#pragma unroll
            for (int k = 0; k < 8; k++) s += ldsf(sm + OFF_SC + (k * 256 + st) * 4);
            const float hi = bfround(s);
            const uint32_t ca = sm + OFF_CC + (st >> 7) * VROW + (st & 127) * 2;
            sts16(ca, f2bf(hi)); sts16(ca + 2 * VROW, f2bf(s - hi));
            bar_sync(2, 256);
        }
        matvecT(c, sm + OFF_S1, sm + OFF_CC, 4, bars + B_WUV * 8, w, lane);
#pragma unroll
        for (int k = 0; k < 4; k++) c[k] += __shfl_down_sync(0xffffffffu, c[k], 1);
        if (t == 0) {
            float* const e = (float*)g_e4[cta] + w * 16 + g;
            mail_put(e, c[0]); mail_put(e + 128, c[1]); mail_put(e + 8, c[2]); mail_put(e + 136, c[3]);
        }
        __syncwarp();
        if (lane == 0) mbar_arrive(bars + B_FREE * 8);
        if (st == 0) TS(23);
        {
            const uint4* const pv = &g_e4[(cta & ~15) + (w >> 1) * 4][(w & 1) * 32 + lane];
            uint4 x[4];
            uint32_t it = 0;
            sleep_ns(POLL_DELAY2);
            while (true) {
#pragma unroll
                for (int k = 0; k < 4; k++) { x[k].x = x[k].y = x[k].z = x[k].w = 0u; mail_get(x[k], pv + k * 64); }
                if (!__any_sync(0xffffffffu, mail_missing(x[0]) | mail_missing(x[1]) | mail_missing(x[2]) | mail_missing(x[3]))) break;
                if (++it > SPIN_MAX) __trap();
                __nanosleep(BACKOFF);
            }
#define SUM4(e) ((__uint_as_float(x[0].e) + __uint_as_float(x[1].e)) + (__uint_as_float(x[2].e) + __uint_as_float(x[3].e)))
            sts64(sm + OFF_CA + w * VROW + lane * 8, pack2(SUM4(x), SUM4(y)), pack2(SUM4(z), SUM4(w)));
#undef SUM4
        }
        if (st == 0) TS(14);
        bar_sync(4, 256 + 128);
        {
            const uint32_t a0 = sm + OFF_S0 + w * 1024 + (rr + 8 * (i >> 1)) * 64 + (((i & 1) ^ (rr >> 1)) << 4);
            const uint4* const pv = pin(&g_e5[(cta & ~15) + (w >> 1) * 4 + (g & 3)][(g >> 2) * 16 + (w & 1) * 8 + t]);
            const uint32_t* const pl = pin((const uint32_t*)g_l5[(h & ~3) + (w >> 1)] + rr);
            const uint32_t wa = sm + OFF_SC + ((w * 2 + (t & 1)) * 80 + (t >> 1) * 40 + g) * 4;
            __nv_bfloat16* const outp = pin(out + (lane >> 4) * 1024 + 512 + (cta & 15) * 32 + (lane & 15) * 2);
            uint32_t a[4][2][4], xl = 0u, it = 0;
            uint4 x[2] = {make_uint4(0u, 0u, 0u, 0u), make_uint4(0u, 0u, 0u, 0u)};
            while (true) {
                if (lane < 8) asm volatile("atom.relaxed.gpu.global.or.b32 %0, [%1], 0;" : "=r"(xl) : "l"(pl) : "memory");
                if (!__any_sync(0xffffffffu, xl == EMPTY)) break;
                if (++it > SPIN_MAX) __trap();
            }
            if (st == 0) TS(25);
            mail_get(x[0], pv); mail_get(x[1], pv + 4);
            float w0 = __uint_as_float(xl), w1 = fmaxf(w0, __shfl_xor_sync(0xffffffffu, w0, 1));
            w0 = ex2(w0 - fmaxf(w1, __shfl_xor_sync(0xffffffffu, w1, 2)));
            w1 = w0 + __shfl_xor_sync(0xffffffffu, w0, 1);
            w0 *= rcp(w1 + __shfl_xor_sync(0xffffffffu, w1, 2));
            w1 = __shfl_sync(0xffffffffu, w0, 2 * t + 1);
            w0 = __shfl_sync(0xffffffffu, w0, 2 * t);
#pragma unroll
            for (int q = 0; q < 4; q++) {
                mbar_wait(bars + (B_WO + q) * 8, 0);
                ldsm4t(a[q][0], a0 + q * 8192);
                ldsm4t(a[q][1], (a0 ^ 32) + q * 8192);
            }
            if (st == 0) TS(26);
            while (true) {
                const bool n0 = mail_missing(x[0]), n1 = mail_missing(x[1]);
                if (!__any_sync(0xffffffffu, n0 | n1)) break;
                mail_get(x[0], pv, n0); mail_get(x[1], pv + 4, n1);
                if (++it > SPIN_MAX) __trap();
            }
            if (st == 0) TS(16);
            float d[2][2][4];
#pragma unroll
            for (int k = 0; k < 4; k++) {
                float (&dk)[4] = d[k >> 1][k & 1];
                dk[0] = dk[1] = dk[2] = dk[3] = 0.f;
                mma(dk, a[k >> 1][k & 1], x[k >> 1].x, x[k >> 1].y);
            }
#pragma unroll
            for (int k = 0; k < 4; k++) mma(d[k >> 1][k & 1], a[2 + (k >> 1)][k & 1], x[k >> 1].z, x[k >> 1].w);
#pragma unroll
            for (int k = 0; k < 4; k++) {
                const int e = (k & 1) * 2;
                sts32(wa + k * 32, __float_as_uint(w0 * (d[0][k >> 1][e] + d[1][k >> 1][e]) + w1 * (d[0][k >> 1][e + 1] + d[1][k >> 1][e + 1])));
            }
            if (st == 0) TS(17);
            if (w == 0) {
                bar_sync(5, 256);
                const uint32_t ra = sm + OFF_SC + ((lane >> 4) * 40 + (lane & 15) * 2) * 4;
                float2 r[16];
#pragma unroll
                for (int k = 0; k < 16; k++) r[k] = ldsf2(ra + k * 320);
#pragma unroll
                for (int o = 1; o < 16; o <<= 1)
#pragma unroll
                    for (int k = 0; k < 16; k += 2 * o) { r[k].x += r[k + o].x; r[k].y += r[k + o].y; }
                out_add(outp, r[0].x, r[0].y);
            } else {
                bar_arrive(5, 256);
            }
        }
    }
}

typedef CUresult (*EncodeFn)(CUtensorMap*, CUtensorMapDataType, cuuint32_t, void*, const cuuint64_t*, const cuuint64_t*,
                             const cuuint32_t*, const cuuint32_t*, CUtensorMapInterleave, CUtensorMapSwizzle,
                             CUtensorMapL2promotion, CUtensorMapFloatOOBfill);

void make_map(EncodeFn enc, CUtensorMap* m, void* p, unsigned rows, unsigned cols, unsigned br, unsigned bg) {
    cuuint64_t gd[3] = {64, rows, cols / 64};
    cuuint64_t gs[2] = {(cuuint64_t)cols * 2, 128};
    cuuint32_t bx[3] = {64, br, bg};
    cuuint32_t es[3] = {1, 1, 1};
    enc(m, CU_TENSOR_MAP_DATA_TYPE_BFLOAT16, 3, p, gd, gs, bx, es, CU_TENSOR_MAP_INTERLEAVE_NONE,
        CU_TENSOR_MAP_SWIZZLE_128B, CU_TENSOR_MAP_L2_PROMOTION_L2_128B, CU_TENSOR_MAP_FLOAT_OOB_FILL_NONE);
}

}

extern "C" void kernel_launch(void* const* d_in, const int* in_sizes, int n_in, void* d_out, int out_size) {
    static EncodeFn enc = nullptr;
    if (!enc) {
        void* fn = nullptr;
        cudaDriverEntryPointQueryResult qr;
        cudaGetDriverEntryPoint("cuTensorMapEncodeTiled", &fn, cudaEnableDefault, &qr);
        enc = (EncodeFn)fn;
        cudaFuncSetAttribute(fused_decode_kernel, cudaFuncAttributeMaxDynamicSharedMemorySize, SMEM_BYTES);
    }
    Maps maps;
    make_map(enc, &maps.wqB, d_in[9], 512, 4096, 64, 2);
    make_map(enc, &maps.wqA, d_in[2], 512, 4096, 64, 2);
    make_map(enc, &maps.wuk, d_in[3], 512, 4096, 64, 2);
    make_map(enc, &maps.wuv, d_in[4], 512, 4096, 64, 2);
    for (int k = 0; k < 2; k++) {
        cuuint64_t gd[3] = {512, 128, 32};
        cuuint64_t gs[2] = {1024, 131072};
        cuuint32_t bx[3] = {32, 32, 4};
        cuuint32_t es[3] = {1, 1, 1};
        enc(&maps.woB + k, CU_TENSOR_MAP_DATA_TYPE_BFLOAT16, 3, d_in[k ? 5 : 10], gd, gs, bx, es, CU_TENSOR_MAP_INTERLEAVE_NONE,
            CU_TENSOR_MAP_SWIZZLE_64B, CU_TENSOR_MAP_L2_PROMOTION_L2_256B, CU_TENSOR_MAP_FLOAT_OOB_FILL_NONE);
    }
    make_map(enc, &maps.ckv, d_in[1], 8192, 512, 16, 8);
    {
        void* p = nullptr;
        cudaGetSymbolAddress(&p, g_ctxp);
        cuuint64_t gd[3] = {128, 128, 128};
        cuuint64_t gs[2] = {256, 32768};
        cuuint32_t bx[3] = {128, 1, 128 / ST_SPLIT};
        cuuint32_t es[3] = {1, 1, 1};
        enc(&maps.ctxp, CU_TENSOR_MAP_DATA_TYPE_BFLOAT16, 3, p, gd, gs, bx, es, CU_TENSOR_MAP_INTERLEAVE_NONE,
            CU_TENSOR_MAP_SWIZZLE_NONE, CU_TENSOR_MAP_L2_PROMOTION_NONE, CU_TENSOR_MAP_FLOAT_OOB_FILL_NONE);
    }
    fused_decode_kernel<<<NCTA, NTHREADS, SMEM_BYTES>>>((const char*)d_in[9], maps, (const char*)d_in[7], (const char*)d_in[8],
                                                         (const __nv_bfloat16*)d_in[0], (const __nv_bfloat16*)d_in[6],
                                                         (__nv_bfloat16*)d_out, 0u);
}
```

```cpp
#include <cuda_runtime.h>
#include <cuda.h>
#include <cuda_bf16.h>
#include <stdint.h>

#define RING 7
#define WIN 4
#define WHI 5
#define THETA 64
#define END_V 40
#define GATE_W 64
#define PREWIN 4
#define TAILWIN 6
#define BOXGAP 350
#define POLL_DELAY 2500
#define POLL_DELAY2 3000
#define ST_SPLIT 32
#define ST_GAP 200
#define G_SPLIT 8
#define G_GAP 250
#define BACKOFF 200
#define BACKOFF2 100

namespace {

constexpr int NCTA = 128;
constexpr int NTHREADS = 448;
constexpr uint32_t CH = 16384;
constexpr int NTILE = 32;
constexpr int RUN = 4;

constexpr uint32_t OFF_RING = 0;
constexpr uint32_t OFF_S0 = RING * CH;
constexpr uint32_t OFF_S1 = OFF_S0 + 2 * CH;
constexpr uint32_t OFF_S2 = OFF_S1 + 2 * CH;
constexpr uint32_t OFF_P = OFF_S2 + 2 * CH;
constexpr uint32_t OFF_SC = OFF_P + 4096;
constexpr uint32_t VROW = 272;
constexpr uint32_t OFF_XB = OFF_SC + 8704;
constexpr uint32_t OFF_XA = OFF_XB + 2 * VROW;
constexpr uint32_t OFF_QA = OFF_XA + 2 * VROW;
constexpr uint32_t OFF_QS = OFF_QA + 2 * VROW;
constexpr uint32_t OFF_CC = OFF_QS + 2 * VROW;
constexpr uint32_t OFF_CA = OFF_P;
constexpr uint32_t OFF_QB = OFF_CC + 4 * VROW;
constexpr uint32_t OFF_LSE = OFF_QB + 512;
constexpr uint32_t OFF_ML = OFF_LSE + 512;
constexpr uint32_t OFF_TAG = OFF_ML + 64;
constexpr uint32_t OFF_NOW = OFF_TAG + 4;
constexpr uint32_t OFF_WIN = OFF_TAG + 8;
constexpr uint32_t OFF_TWIN = OFF_TAG + 12;
constexpr uint32_t OFF_BAR = OFF_TAG + 16;
constexpr int B_EMPTY = RING;
constexpr int B_WQB = 2 * RING;
constexpr int B_WQA = B_WQB + 2;
constexpr int B_WUK = B_WQA + 2;
constexpr int B_WUV = B_WUK + 2;
constexpr int B_CKV = B_WUV + 2;
constexpr int B_WO = B_CKV + 4;
constexpr int B_FREE = B_WO + 8;
constexpr int B_GATH = B_FREE + 1;
constexpr int B_S2 = B_GATH + 1;
constexpr int NBAR = B_S2 + 1;
constexpr uint32_t TS_OFF = OFF_BAR + NBAR * 8;
constexpr uint32_t SMEM_USED = TS_OFF;
constexpr uint32_t SMEM_BYTES = SMEM_USED + 1024;
static_assert(SMEM_BYTES <= 232448, "smem");
static_assert(RING >= RUN && RING >= WHI && WHI >= WIN && WHI >= 4 && WIN >= 3 && WIN <= 6 && TAILWIN >= 4, "windows");

constexpr float LOG2E = 1.4426950408889634f;
constexpr float SCALE = 0.08838834764831845f;
#define SPIN_LOG 22
constexpr uint32_t SPIN_MAX = 1u << SPIN_LOG;

struct Maps { CUtensorMap wqB, wqA, wuk, wuv, woB, woA, ckv, ctxp; };

__device__ __align__(256) unsigned g_cnt[32];
__device__ __align__(256) ulonglong2 g_e1[2][NCTA][128];
__device__ __align__(256) uint4 g_qabs[2 * 32 * 64];
__device__ __align__(256) uint4 g_ctxp[NCTA * 128 * 16];
__device__ __align__(256) float4 g_lse[32 * 32];
__device__ __align__(256) uint4 g_e4[NCTA][64];
__device__ __align__(256) uint4 g_e5[NCTA][32];
__device__ __align__(256) uint4 g_l5[32][8];
constexpr uint32_t EMPTY = 0xffffffffu;

#define TS(k) do {} while (0)

__device__ __forceinline__ void mbar_init(uint32_t b, int c) { asm volatile("mbarrier.init.shared::cta.b64 [%0], %1;" ::"r"(b), "r"(c) : "memory"); }
__device__ __forceinline__ void mbar_expect(uint32_t b, uint32_t bytes) { asm volatile("mbarrier.arrive.expect_tx.shared::cta.b64 _, [%0], %1;" ::"r"(b), "r"(bytes) : "memory"); }
__device__ __forceinline__ void mbar_arrive(uint32_t b) { asm volatile("mbarrier.arrive.shared::cta.b64 _, [%0];" ::"r"(b) : "memory"); }
__device__ __forceinline__ void mbar_wait(uint32_t b, uint32_t ph) {
    asm volatile("{\n.reg .pred p;\n.reg .u32 n;\nmov.u32 n, 0;\n"
                 "W:\nmbarrier.try_wait.parity.shared::cta.b64 p, [%0], %1;\n@p bra D;\n"
                 "add.u32 n, n, 1;\nsetp.le.u32 p, n, %2;\n@p bra W;\ntrap;\nD:\n}" ::"r"(b), "r"(ph), "n"(SPIN_MAX) : "memory");
}
__device__ __forceinline__ uint32_t mbar_test(uint32_t b, uint32_t ph) {
    uint32_t ok;
    asm volatile("{\n.reg .pred p;\nmbarrier.test_wait.parity.shared::cta.b64 p, [%1], %2;\nselp.u32 %0, 1, 0, p;\n}" : "=r"(ok) : "r"(b), "r"(ph) : "memory");
    return ok;
}
__device__ __forceinline__ void bulk1d(uint32_t dst, const void* src, uint32_t bar, uint64_t pol) {
    asm volatile("cp.async.bulk.shared::cluster.global.mbarrier::complete_tx::bytes.L2::cache_hint [%0], [%1], %2, [%3], %4;"
                 ::"r"(dst), "l"(src), "n"(CH), "r"(bar), "l"(pol) : "memory");
}
__device__ __forceinline__ void bulk1d_n(uint32_t dst, const void* src, uint32_t bytes, uint32_t bar) {
    asm volatile("cp.async.bulk.shared::cluster.global.mbarrier::complete_tx::bytes [%0], [%1], %2, [%3];"
                 ::"r"(dst), "l"(src), "r"(bytes), "r"(bar) : "memory");
}
__device__ __forceinline__ void tma3d(uint32_t dst, const CUtensorMap* map, int c1, int c2, uint32_t bar, uint64_t pol, int c0 = 0) {
    asm volatile("cp.async.bulk.tensor.3d.shared::cluster.global.mbarrier::complete_tx::bytes.L2::cache_hint [%0], [%1, {%3,%4,%5}], [%2], %6;"
                 ::"r"(dst), "l"(map), "r"(bar), "r"(c0), "r"(c1), "r"(c2), "l"(pol) : "memory");
}
__device__ __forceinline__ void bar_sync(int id, int n) { asm volatile("barrier.cta.sync %0, %1;" ::"r"(id), "r"(n) : "memory"); }
__device__ __forceinline__ void bar_arrive(int id, int n) { asm volatile("barrier.cta.arrive %0, %1;" ::"r"(id), "r"(n) : "memory"); }
__device__ __forceinline__ void ldsm4(uint32_t (&r)[4], uint32_t a) {
    asm volatile("ldmatrix.sync.aligned.m8n8.x4.shared.b16 {%0,%1,%2,%3}, [%4];" : "=r"(r[0]), "=r"(r[1]), "=r"(r[2]), "=r"(r[3]) : "r"(a) : "memory");
}
__device__ __forceinline__ void ldsm4t(uint32_t (&r)[4], uint32_t a) {
    asm volatile("ldmatrix.sync.aligned.m8n8.x4.trans.shared.b16 {%0,%1,%2,%3}, [%4];" : "=r"(r[0]), "=r"(r[1]), "=r"(r[2]), "=r"(r[3]) : "r"(a) : "memory");
}
__device__ __forceinline__ bool box_load(uint32_t (&r)[4], uint32_t (&s)[4], uint32_t (&u)[4], uint32_t (&v)[4], uint32_t bar, uint32_t a) {
    uint32_t ok;
    asm volatile("{\n.reg .pred p;\nmbarrier.try_wait.parity.shared::cta.b64 p, [%17], 0;\n"
                 "@p ldmatrix.sync.aligned.m8n8.x4.trans.shared.b16 {%0,%1,%2,%3}, [%18];\n"
                 "@p ldmatrix.sync.aligned.m8n8.x4.trans.shared.b16 {%4,%5,%6,%7}, [%18 + 2048];\n"
                 "@p ldmatrix.sync.aligned.m8n8.x4.trans.shared.b16 {%8,%9,%10,%11}, [%18 + 4096];\n"
                 "@p ldmatrix.sync.aligned.m8n8.x4.trans.shared.b16 {%12,%13,%14,%15}, [%18 + 6144];\n"
                 "selp.u32 %16, 1, 0, p;\n}"
                 : "+r"(r[0]), "+r"(r[1]), "+r"(r[2]), "+r"(r[3]), "+r"(s[0]), "+r"(s[1]), "+r"(s[2]), "+r"(s[3]),
                   "+r"(u[0]), "+r"(u[1]), "+r"(u[2]), "+r"(u[3]), "+r"(v[0]), "+r"(v[1]), "+r"(v[2]), "+r"(v[3]), "=r"(ok)
                 : "r"(bar), "r"(a) : "memory");
    return ok != 0;
}
__device__ __forceinline__ void mma(float (&c)[4], const uint32_t (&a)[4], uint32_t b0, uint32_t b1) {
    asm volatile("mma.sync.aligned.m16n8k16.row.col.f32.bf16.bf16.f32 {%0,%1,%2,%3}, {%4,%5,%6,%7}, {%8,%9}, {%0,%1,%2,%3};"
                 : "+f"(c[0]), "+f"(c[1]), "+f"(c[2]), "+f"(c[3]) : "r"(a[0]), "r"(a[1]), "r"(a[2]), "r"(a[3]), "r"(b0), "r"(b1));
}
__device__ __forceinline__ uint32_t lds32(uint32_t a) { uint32_t v; asm volatile("ld.shared.b32 %0, [%1];" : "=r"(v) : "r"(a) : "memory"); return v; }
__device__ __forceinline__ uint32_t ldsv(uint32_t a) { uint32_t v; asm volatile("ld.volatile.shared.b32 %0, [%1];" : "=r"(v) : "r"(a) : "memory"); return v; }
__device__ __forceinline__ void stsv(uint32_t a, uint32_t v) { asm volatile("st.volatile.shared.b32 [%0], %1;" ::"r"(a), "r"(v) : "memory"); }
__device__ __forceinline__ float ldsf(uint32_t a) { float v; asm volatile("ld.shared.f32 %0, [%1];" : "=f"(v) : "r"(a) : "memory"); return v; }
__device__ __forceinline__ uint4 lds128(uint32_t a) { uint4 v; asm volatile("ld.shared.v4.b32 {%0,%1,%2,%3}, [%4];" : "=r"(v.x), "=r"(v.y), "=r"(v.z), "=r"(v.w) : "r"(a) : "memory"); return v; }
__device__ __forceinline__ void sts16(uint32_t a, uint16_t v) { asm volatile("st.shared.b16 [%0], %1;" ::"r"(a), "h"(v) : "memory"); }
__device__ __forceinline__ void sts32(uint32_t a, uint32_t v) { asm volatile("st.shared.b32 [%0], %1;" ::"r"(a), "r"(v) : "memory"); }
__device__ __forceinline__ void stsf2(uint32_t a, float x, float y) { asm volatile("st.shared.v2.f32 [%0], {%1,%2};" ::"r"(a), "f"(x), "f"(y) : "memory"); }
__device__ __forceinline__ void sts128(uint32_t a, uint4 v) { asm volatile("st.shared.v4.b32 [%0], {%1,%2,%3,%4};" ::"r"(a), "r"(v.x), "r"(v.y), "r"(v.z), "r"(v.w) : "memory"); }
__device__ __forceinline__ uint16_t f2bf(float x) { return __bfloat16_as_ushort(__float2bfloat16_rn(x)); }
__device__ __forceinline__ float bfround(float x) { return __bfloat162float(__float2bfloat16_rn(x)); }
__device__ __forceinline__ uint32_t pack2(float lo, float hi) { uint32_t r; asm("cvt.rn.bf16x2.f32 %0, %1, %2;" : "=r"(r) : "f"(hi), "f"(lo)); return r; }
__device__ __forceinline__ float ex2(float x) { float r; asm("ex2.approx.ftz.f32 %0, %1;" : "=f"(r) : "f"(x)); return r; }
__device__ __forceinline__ float lg2(float x) { float r; asm("lg2.approx.ftz.f32 %0, %1;" : "=f"(r) : "f"(x)); return r; }

__device__ __forceinline__ float rcp(float x) { float r; asm("rcp.approx.ftz.f32 %0, %1;" : "=f"(r) : "f"(x)); return r; }

__device__ __forceinline__ uint32_t clock_lo() { uint32_t t; asm volatile("mov.u32 %0, %clock;" : "=r"(t) :: "memory"); return t; }
__device__ __forceinline__ void sleep_ns(uint32_t ns) {
    const uint32_t t0 = clock_lo();
    do { __nanosleep(200); } while (clock_lo() - t0 < 2 * ns);
}

__device__ __forceinline__ void ll_store2(ulonglong2* p, float a, float b, uint32_t tag) {
    unsigned long long x = ((unsigned long long)tag << 32) | __float_as_uint(a);
    unsigned long long y = ((unsigned long long)tag << 32) | __float_as_uint(b);
    asm volatile("st.relaxed.gpu.global.v2.b64 [%0], {%1,%2};" ::"l"(p), "l"(x), "l"(y) : "memory");
}
__device__ __forceinline__ void ll_ld2(const void* p, unsigned long long& x, unsigned long long& y) {
    asm volatile("ld.relaxed.gpu.global.v2.b64 {%0,%1}, [%2];" : "=l"(x), "=l"(y) : "l"(p) : "memory");
}
__device__ __forceinline__ void ll_gather4(const ulonglong2* p, uint32_t tag, float& r0, float& r1) {
    unsigned long long x[4], y[4]; uint32_t it = 0;
    while (true) {
        bool ok = true;
#pragma unroll
        for (int k = 0; k < 4; k++) ll_ld2(p + k * 128, x[k], y[k]);
#pragma unroll
        for (int k = 0; k < 4; k++) ok = ok && (uint32_t)(x[k] >> 32) == tag && (uint32_t)(y[k] >> 32) == tag;
        if (ok) break;
        if (++it > SPIN_MAX) __trap();
        __nanosleep(BACKOFF);
    }
    r0 = (__uint_as_float((uint32_t)x[0]) + __uint_as_float((uint32_t)x[1])) + (__uint_as_float((uint32_t)x[2]) + __uint_as_float((uint32_t)x[3]));
    r1 = (__uint_as_float((uint32_t)y[0]) + __uint_as_float((uint32_t)y[1])) + (__uint_as_float((uint32_t)y[2]) + __uint_as_float((uint32_t)y[3]));
}
__device__ __forceinline__ void cnt_rendezvous(unsigned* c, uint32_t target, int tsk) {
    TS(tsk);
    asm volatile("red.release.gpu.global.add.u32 [%0], 1;" ::"l"(c) : "memory");
    if (tsk == 18) TS(tsk + 1);
    uint32_t v, it = 0;
    while (true) {
        asm volatile("ld.acquire.gpu.global.u32 %0, [%1];" : "=r"(v) : "l"(c) : "memory");
        if ((int)(v - target) >= 0) break;
        if (++it > SPIN_MAX) __trap();
        __nanosleep(BACKOFF);
    }
    asm volatile("fence.proxy.async.global;" ::: "memory");
}

__device__ __forceinline__ void matvec_loadA(uint32_t (&a)[8][4], uint32_t tile, uint32_t bar, int w, int lane) {
    const int i = lane >> 3, rr = lane & 7, chunk = 2 * w + (i & 1);
    const uint32_t a0 = tile + (chunk >> 3) * 8192 + (rr + 8 * (i >> 1)) * 128 + (((chunk & 7) ^ rr) << 4);
#pragma unroll
    for (int hh = 0; hh < 2; hh++) {
        mbar_wait(bar + hh * 8, 0);
#pragma unroll
        for (int k = 0; k < 4; k++) ldsm4t(a[hh * 4 + k], a0 + hh * CH + k * 2048);
    }
}
__device__ __forceinline__ void matvec_mma(float (&c)[4], const uint32_t (&a)[8][4], uint32_t vec, int nvec, int lane) {
    const uint32_t va = vec + (lane & (nvec - 1)) * VROW + (lane >> 3) * 16;
    float d[4][4];
#pragma unroll
    for (int q = 0; q < 4; q++) {
        uint32_t b[4];
        ldsm4(b, va + q * 64);
        d[q][0] = d[q][1] = d[q][2] = d[q][3] = 0.f;
        mma(d[q], a[2 * q], b[0], b[1]);
        mma(d[q], a[2 * q + 1], b[2], b[3]);
    }
#pragma unroll
    for (int k = 0; k < 4; k++) c[k] = (d[0][k] + d[1][k]) + (d[2][k] + d[3][k]);
}
__device__ __forceinline__ void matvecT(float (&c)[4], uint32_t tile, uint32_t vec, int nvec, uint32_t bar, int w, int lane) {
    uint32_t a[8][4];
    matvec_loadA(a, tile, bar, w, lane);
    matvec_mma(c, a, vec, nvec, lane);
}
template <class T> __device__ __forceinline__ T* pin(T* p) { asm volatile("" : "+l"(p)); return p; }
__device__ __forceinline__ void mail_put(void* p, uint32_t v) { asm volatile("st.relaxed.gpu.global.b32 [%0], %1;" ::"l"(p), "r"(v) : "memory"); }
__device__ __forceinline__ void mail_put(void* p, float v) { mail_put(p, __float_as_uint(v)); }
__device__ __forceinline__ void out_add(__nv_bfloat16* p, float x, float y) {
    asm volatile("red.relaxed.gpu.global.add.noftz.bf16x2 [%0], %1;" ::"l"(p), "r"(pack2(x, y)) : "memory");
}
__device__ __forceinline__ bool mail_missing(const uint4& v) { return v.x == EMPTY || v.y == EMPTY || v.z == EMPTY || v.w == EMPTY; }
__device__ __forceinline__ void mail_get(uint4& v, const uint4* p, bool need = true) {
    asm volatile("{\n.reg .pred q;\nsetp.ne.u32 q, %5, 0;\n@q ld.relaxed.gpu.global.v4.b32 {%0,%1,%2,%3}, [%4];\n}"
                 : "+r"(v.x), "+r"(v.y), "+r"(v.z), "+r"(v.w) : "l"(p), "r"((uint32_t)need) : "memory");
}
__device__ __forceinline__ void sts64(uint32_t a, uint32_t x, uint32_t y) { asm volatile("st.shared.v2.b32 [%0], {%1,%2};" ::"r"(a), "r"(x), "r"(y) : "memory"); }
__device__ __forceinline__ float2 ldsf2(uint32_t a) { float2 v; asm volatile("ld.shared.v2.f32 {%0,%1}, [%2];" : "=f"(v.x), "=f"(v.y) : "r"(a) : "memory"); return v; }

__global__ void __launch_bounds__(NTHREADS, 1)
fused_decode_kernel(const char* __restrict__ wqraw, const __grid_constant__ Maps maps, const char* __restrict__ Kc, const char* __restrict__ Vc,
                    const __nv_bfloat16* __restrict__ xA, const __nv_bfloat16* __restrict__ xB,
                    __nv_bfloat16* __restrict__ out, const uint32_t zero) {
    if (threadIdx.x == 0) asm volatile("cp.async.bulk.prefetch.L2.global [%0], 32768;" ::"l"(wqraw + (size_t)blockIdx.x * 32768u) : "memory");
    asm volatile("nanosleep.u32 60;" ::: "memory");
    asm volatile("barrier.cta.sync.aligned 7, %0;" ::"n"(NTHREADS) : "memory");
    asm volatile("{\n.reg .pred p;\n.reg .u32 s;\nmov.u32 s, %smid;\nsetp.eq.u32 p, s, 0xffff;\n@p exit;\n}" ::: "memory");
    extern __shared__ char smem_raw[];
    const uint32_t sm = ((uint32_t)__cvta_generic_to_shared(smem_raw) + 1023u) & ~1023u;
    const uint32_t bars = sm + OFF_BAR;
    const int cta = blockIdx.x, h = cta >> 2, j = cta & 3;
    uint64_t pol = 0;
    if (threadIdx.x == 0) {
        TS(0);
        asm volatile("createpolicy.fractional.L2::evict_first.b64 %0, 1.0;" : "=l"(pol));
#pragma unroll
        for (int i = 0; i < WIN; i++) mbar_init(bars + (B_WQB + i) * 8, 1);
        asm volatile("fence.mbarrier_init.release.cluster;" ::: "memory");
#pragma unroll
        for (int i = 0; i < WIN; i++) {
            mbar_expect(bars + (B_WQB + i) * 8, CH);
            tma3d(sm + OFF_S0 + i * CH, &maps.wqB + (i >> 1), j * 128 + (i & 1) * 64, h * 2, bars + (B_WQB + i) * 8, pol);
        }
    }
    const int tid = threadIdx.x < 64 ? threadIdx.x + 384 : threadIdx.x - 64, warp = tid >> 5, lane = tid & 31;

    if (warp == 12) {
        const size_t kvoff = (size_t)cta * (NTILE / 2 * CH);
        const char* kp = Kc + kvoff;
        const char* vp = Vc + kvoff;
        __syncwarp();
        bar_arrive(0, NTHREADS);
        bar_sync(3, 64);
        if (lane == 0) {
            uint32_t pb[WHI];
#pragma unroll
            for (int i = 0; i < WHI; i++) pb[i] = i < WHI - WIN ? (bars + B_WO * 8) | 1u : bars + (B_WQB + i - (WHI - WIN)) * 8;
            auto pace = [&](uint32_t bar, uint32_t par) {
                uint32_t it = 0;
                while (true) {
                    const uint32_t win = ldsv(sm + OFF_WIN);
                    uint32_t busy = 0;
#pragma unroll
                    for (int i = 0; i < WHI; i++) busy += mbar_test(pb[i] & ~1u, pb[i] & 1u) ^ 1u;
                    if (busy < win) break;
                    if (++it > SPIN_MAX) __trap();
                }
#pragma unroll
                for (int i = 0; i + 1 < WHI; i++) pb[i] = pb[i + 1];
                pb[WHI - 1] = bar | par;
            };
            auto side = [&](const CUtensorMap* m, uint32_t dst, int bidx, int c1, int c2) {
                const uint32_t bar = bars + bidx * 8;
                pace(bar, 0);
                mbar_expect(bar, CH);
                tma3d(dst, m, c1, c2, bar, pol);
            };
#pragma unroll 1
            for (int i = WIN; i < 6; i++)
                side(&maps.wqB + (i >> 1), sm + OFF_S0 + i * CH, B_WQB + i, j * 128 + (i & 1) * 64, h * 2);
            TS(1);
            uint32_t slot = 0, use = 0;
            int nuv = 0;
#pragma unroll 1
            for (int n = 0; n < 2 * NTILE; n++) {
                if (n == RING) {
                    mbar_wait(bars + B_FREE * 8, 0);
#pragma unroll 1
                    for (int q = 0; q < 4; q++) side(&maps.ckv, sm + OFF_S0 + q * CH, B_CKV + q, cta * 64 + q * 16, 0);
                }
                if (nuv < 2 && n > RING && (n >= 2 * NTILE - 8 || mbar_test(bars + B_FREE * 8, 1))) {
                    mbar_wait(bars + B_FREE * 8, 1);
                    side(&maps.wuv, sm + OFF_S1 + nuv * CH, B_WUV + nuv, j * 128 + nuv * 64, h * 2);
                    nuv++;
                }
                const uint32_t fb = bars + slot * 8;
                pace(fb, use & 1);
                mbar_wait(fb + B_EMPTY * 8, (use & 1) ^ 1);
                mbar_expect(fb, CH);
                bulk1d(sm + OFF_RING + slot * CH, ((n & RUN) ? vp : kp) + (size_t)(n / NTILE * (NCTA * NTILE / 2) + n % NTILE / (2 * RUN) * RUN + n % RUN) * CH, fb, pol);
                if (((n + cta) & 3) == 0) asm volatile("red.relaxed.gpu.global.add.u32 [%0], 4;" ::"l"(&g_cnt[2]) : "memory");
                stsv(sm + OFF_NOW, n + 1);
                if (++slot == RING) { slot = 0; use++; }
            }
            TS(2);
            mbar_wait(bars + B_FREE * 8, 0);
            uint32_t tlast = clock_lo();
#pragma unroll 1
            for (int i = 0; i < 8; i++) {
                uint32_t it = 0;
                while (true) {
                    const uint32_t win = ldsv(sm + OFF_TWIN);
                    uint32_t busy = i;
#pragma unroll
                    for (int k = 0; k < 4; k++) busy += 2 * (mbar_test(pb[WHI - 4 + k] & ~1u, pb[WHI - 4 + k] & 1u) ^ 1u) - mbar_test(bars + (B_WO + k) * 8, 0);
                    if (busy < win) break;
                    if (++it > SPIN_MAX) __trap();
                }
                while (clock_lo() - tlast < BOXGAP) {}
                tlast = clock_lo();
                if (i & 1) TS(32 + (i >> 1));
                mbar_expect(bars + (B_WO + i) * 8, CH / 2);
                tma3d(sm + OFF_S0 + i * (CH / 2), &maps.woB + (i >> 2), (i & 3) * 32, h & ~3, bars + (B_WO + i) * 8, pol, (cta & 15) * 32);
            }
            TS(3);
        }
    } else if (warp == 13) {
        if (lane == 0) {
#pragma unroll
            for (int i = 0; i < NBAR; i++)
                if (i < B_WQB || i >= B_WQB + WIN)
                    mbar_init(bars + i * 8, i == B_FREE ? 8 : (i >= B_EMPTY && i < B_EMPTY + RING) ? 4 : 1);
            asm volatile("fence.mbarrier_init.release.cluster;" ::: "memory");
#pragma unroll
            for (int i = 2; i < 8; i++) asm volatile("prefetch.tensormap [%0];" ::"l"(&maps.wqB + i) : "memory");
            stsv(sm + OFF_NOW, 0); stsv(sm + OFF_WIN, WIN); stsv(sm + OFF_TWIN, PREWIN);
        }
        __syncwarp();
        bar_arrive(3, 64);
        bar_sync(0, NTHREADS);
        if (lane == 0) {
            const uint32_t base = (lds32(sm + OFF_TAG) - 1u) * (NCTA * 2 * NTILE);
            mbar_wait(bars + (B_WUK + 1) * 8, 0);
            uint32_t it = 0;
            while (true) {
                const uint32_t n = ldsv(sm + OFF_NOW);
                uint32_t v;
                asm volatile("ld.relaxed.gpu.global.u32 %0, [%1];" : "=r"(v) : "l"(&g_cnt[2]) : "memory");
                v -= base;
                if (v >= NCTA * 2 * NTILE - GATE_W) break;
                const int diff = (int)(n * NCTA) - (int)v;
                stsv(sm + OFF_WIN, diff < -THETA ? WHI : WIN - (diff > THETA) - (v >= NCTA * END_V));
                if (++it > SPIN_MAX) __trap();
                __nanosleep(BACKOFF2);
            }
            stsv(sm + OFF_WIN, WHI); stsv(sm + OFF_TWIN, TAILWIN);
            TS(24);
        }
    } else if (warp < 4) {
        const int g = lane >> 2, t = lane & 3, i = lane >> 3, rr = lane & 7;
        if (tid == 0) {
            unsigned e;
            asm volatile("ld.relaxed.gpu.global.u32 %0, [%1];" : "=r"(e) : "l"(&g_cnt[1]) : "memory");
            sts32(sm + OFF_TAG, (e >> 7) + 1u);
        }
        bar_sync(0, NTHREADS);
        const uint32_t tag = lds32(sm + OFF_TAG);
        {
            mbar_wait(bars + 8, 0);
            float q0, q1;
            ll_gather4(&g_e1[0][h * 4][tid], tag, q0, q1);
            sts16(sm + OFF_QB + tid * 2, f2bf(q0)); sts16(sm + OFF_QB + 256 + tid * 2, f2bf(q1));
        }
        bar_sync(1, 128);
        if (tid == 0) TS(4);
        uint32_t qf[8][2];
        float acc[8][4], m, l;
        auto start = [&](int b) {
#pragma unroll
            for (int c = 0; c < 8; c++) {
                const uint32_t a = sm + OFF_QB + b * 256 + (((c + g) & 7) * 8 + 2 * t) * 2;
                qf[c][0] = lds32(a); qf[c][1] = lds32(a + 128);
                acc[c][0] = acc[c][1] = acc[c][2] = acc[c][3] = 0.f;
            }
            m = -INFINITY; l = 0.f;
        };
        auto stats = [&](int b) {
#pragma unroll
            for (int o = 16; o; o >>= 1) l += __shfl_xor_sync(0xffffffffu, l, o);
            if (lane == 0) stsf2(sm + OFF_ML + b * 32 + warp * 8, m, l);
        };
        auto quad_sum = [&](float (&r)[4]) {
            float v[2][8];
#pragma unroll
            for (int c = 0; c < 8; c++) { v[0][c] = acc[c][0] + acc[(c + 7) & 7][1]; v[1][c] = acc[c][2] + acc[(c + 7) & 7][3]; }
#pragma unroll
            for (int c = 0; c < 4; c++) { v[0][c] += __shfl_xor_sync(0xffffffffu, v[0][c + 4], 2); v[1][c] += __shfl_xor_sync(0xffffffffu, v[1][c + 4], 2); }
            const int src = (lane & ~3) | ((lane + 3) & 3);
#pragma unroll
            for (int c = 0; c < 4; c++) r[c] = v[c >> 1][c & 1] + __shfl_sync(0xffffffffu, v[c >> 1][(c & 1) + 2], src);
        };
        auto factor = [&](int b, float& lse) {
            bar_sync(1, 128);
            const uint4 ml0 = lds128(sm + OFF_ML + b * 32), ml1 = lds128(sm + OFF_ML + b * 32 + 16);
            const float m0 = __uint_as_float(ml0.x), m1 = __uint_as_float(ml0.z), m2 = __uint_as_float(ml1.x), m3 = __uint_as_float(ml1.z);
            const float M = fmaxf(fmaxf(m0, m1), fmaxf(m2, m3));
            const float L = (ex2((m0 - M) * LOG2E) * __uint_as_float(ml0.y) + ex2((m1 - M) * LOG2E) * __uint_as_float(ml0.w))
                          + (ex2((m2 - M) * LOG2E) * __uint_as_float(ml1.y) + ex2((m3 - M) * LOG2E) * __uint_as_float(ml1.w));
            lse = M * LOG2E + lg2(L);
            return ex2((ldsf(sm + OFF_ML + b * 32 + warp * 8) - M) * LOG2E) * rcp(L);
        };
        auto publish = [&](uint32_t* dst, const float (&r)[4], float f) {
            const uint32_t wa = sm + OFF_S2 + warp * 640 + (t * 16 + (t >> 1) * 8 + g) * 4;
            const uint32_t ra = sm + OFF_S2 + ((tid >> 4 & 1) * 40 + (tid & 2) * 40 + (tid >> 5 & 1) * 16 + (tid & 1) * 8 + (tid >> 2 & 3) * 2) * 4;
#pragma unroll
            for (int c = 0; c < 4; c++) sts32(wa + (c >> 1) * 320 + (c & 1) * 32, __float_as_uint(r[c] * f));
            bar_sync(1, 128);
            const float2 r0 = ldsf2(ra), r1 = ldsf2(ra + 640), r2 = ldsf2(ra + 1280), r3 = ldsf2(ra + 1920);
            if (tid < 64) mail_put(dst, pack2((r0.x + r1.x) + (r2.x + r3.x), (r0.y + r1.y) + (r2.y + r3.y)));
        };
        float o0[4] = {0.f, 0.f, 0.f, 0.f};
        start(0);
        const bool diag = (t == (g >> 1));
        const uint32_t krow = sm + OFF_RING + (warp * 16 + rr + 8 * (i & 1)) * 256 + (i >> 1) * 128;
        const uint32_t vrow = sm + OFF_RING + (warp * 16 + rr + 8 * (i >> 1)) * 256 + (i & 1) * 128;
        uint32_t slot = 0, ph = 0;
        uint32_t a[8][4] = {}, b0[RUN], b1[RUN];
        auto release = [&]() {
            __syncwarp();
            if (lane == 0) mbar_arrive(bars + (B_EMPTY + slot) * 8 + ((a[0][0] | a[1][0] | a[2][0] | a[3][0] | a[4][0] | a[5][0] | a[6][0] | a[7][0]) & zero));
            if (++slot == RING) { slot = 0; ph ^= 1; }
        };
        auto load_v = [&]() {
            mbar_wait(bars + slot * 8, ph);
#pragma unroll
            for (int c = 0; c < 8; c++) ldsm4t(a[c], vrow + slot * CH + (((c + rr) & 7) << 4));
        };
#pragma unroll 1
        for (int run = 0;; run++) {
            float slo[RUN], shi[RUN], mx = -INFINITY;
#pragma unroll
            for (int u = 0; u < RUN; u++) {
                mbar_wait(bars + slot * 8, ph);
#pragma unroll
                for (int c = 0; c < 8; c++) ldsm4(a[c], krow + slot * CH + (((c + rr) & 7) << 4));
                release();
                float s0[4] = {0.f, 0.f, 0.f, 0.f}, s1[4] = {0.f, 0.f, 0.f, 0.f};
#pragma unroll
                for (int c = 0; c < 8; c += 2) { mma(s0, a[c], qf[c][0], qf[c][1]); mma(s1, a[c + 1], qf[c + 1][0], qf[c + 1][1]); }
                slo[u] = diag ? bfround(bfround((g & 1) ? s0[1] + s1[1] : s0[0] + s1[0]) * SCALE) : -INFINITY;
                shi[u] = diag ? bfround(bfround((g & 1) ? s0[3] + s1[3] : s0[2] + s1[2]) * SCALE) : -INFINITY;
                mx = fmaxf(mx, fmaxf(slo[u], shi[u]));
            }
            int key = __float_as_int(mx);
            key ^= (key >> 31) & 0x7fffffff;
            key = __reduce_max_sync(0xffffffffu, key);
            key ^= (key >> 31) & 0x7fffffff;
            const float mn = fmaxf(m, __int_as_float(key));
            const float alpha = ex2((m - mn) * LOG2E);
            m = mn;
            l *= alpha;
#pragma unroll
            for (int u = 0; u < RUN; u++) {
                const float plo = ex2((slo[u] - mn) * LOG2E), phi = ex2((shi[u] - mn) * LOG2E);
                l += plo + phi;
                b0[u] = (g & 1) ? pack2(0.f, plo) : pack2(plo, 0.f);
                b1[u] = (g & 1) ? pack2(0.f, phi) : pack2(phi, 0.f);
            }
#pragma unroll
            for (int c = 0; c < 8; c++) { acc[c][0] *= alpha; acc[c][1] *= alpha; acc[c][2] *= alpha; acc[c][3] *= alpha; }
            if (run == NTILE / RUN - 1) break;
#pragma unroll
            for (int u = 0; u < RUN; u++) {
                load_v();
                release();
#pragma unroll
                for (int c = 0; c < 8; c++) mma(acc[c], a[c], b0[u], b1[u]);
            }
            if (run == NTILE / RUN / 2 - 1) { stats(0); quad_sum(o0); start(1); }
            if (run == NTILE / RUN - 2) {
                float lse;
                mbar_wait(bars + B_S2 * 8, 0);
                publish((uint32_t*)g_e5[cta] + tid, o0, factor(0, lse));
                if (tid == 96) mail_put((float*)g_l5[h] + j, lse);
            }
        }
        {
            float lse;
            stats(1);
            const float f = factor(1, lse);
            uint32_t* const e5own = pin((uint32_t*)g_e5[cta] + 64 + tid);
            float* const l5own = pin((float*)g_l5[h] + 4 + j);
#pragma unroll
            for (int u = 0; u < RUN; u++) {
                load_v();
                if (++slot == RING) { slot = 0; ph ^= 1; }
                if (u == RUN - 1 && tid == 96) mail_put(l5own, lse);
#pragma unroll
                for (int c = 0; c < 8; c++) mma(acc[c], a[c], b0[u], b1[u]);
            }
            if (tid == 0) TS(5);
            quad_sum(o0);
            publish(e5own, o0, f);
        }
        if (tid == 0) TS(6);
        {
            uint32_t x[4][4][4];
            float d[4][4];
            bar_sync(4, 256 + 128);
#pragma unroll
            for (int k = 0; k < 16; k++) ldsm4(x[k >> 2][k & 3], sm + OFF_CA + ((k >> 2) * 2 + (lane & 1)) * VROW + (k & 3) * 64 + (i & 1) * 32 + (i >> 1) * 16);
            const uint32_t wa = sm + OFF_S1 + lane * 64 + ((warp ^ (rr >> 1)) << 4);
            __nv_bfloat16* const outp = pin(out + (g & 1) * 1024 + (cta & 15) * 32 + warp * 8 + t * 2);
            mbar_wait(bars + (B_WO + 4) * 8, 0);
            uint32_t it = 0;
            while (true) {
                bool ok = true;
#pragma unroll
                for (int k = 0; k < 4; k++) d[k][0] = d[k][1] = d[k][2] = d[k][3] = 0.f;
#pragma unroll
                for (int q = 0; q < 5; q++) {
                    if (q < 4) ok &= box_load(a[(q & 1) * 4], a[(q & 1) * 4 + 1], a[(q & 1) * 4 + 2], a[(q & 1) * 4 + 3], bars + (B_WO + 4 + q) * 8, wa + q * 8192);
#pragma unroll
                    for (int k = 0; k < (q ? 8 : 0); k++) {
                        const uint32_t (&u)[4] = a[(~q & 1) * 4 + (k >> 1)];
                        mma(d[k & 3], x[k >> 1][q - 1], u[(k & 1) * 2], u[(k & 1) * 2 + 1]);
                    }
                }
                asm volatile("{\n.reg .pred p;\nsetp.ne.u32 p, %0, 0;\n@p exit;\n}" ::"r"((uint32_t)(ok && lane >= 8)) : "memory");
                if (ok) break;
                if (++it > SPIN_MAX) __trap();
            }
            out_add(outp, (d[0][0] + d[1][2]) + (d[2][0] + d[3][2]), (d[0][1] + d[1][3]) + (d[2][1] + d[3][3]));
            if (tid == 0) TS(15);
        }
    } else {
        const int st = tid - 128, w = warp - 4;
        const int g = lane >> 2, t = lane & 3, i = lane >> 3, rr = lane & 7;
        if (t == 0) {
#pragma unroll
            for (int k = 0; k < 4; k++) ll_store2(&g_e1[k >> 1][cta][w * 16 + g + (k & 1) * 8], 0.f, 0.f, 0u);
        }
        if (st < 64) {
            const int which = st >> 5, b = (st >> 4) & 1, c = st & 15;
            const uint4 v = __ldg((const uint4*)((which ? xA : xB) + b * 512 + j * 128) + c);
            sts128(sm + OFF_XB + (which * 2 + b) * VROW + c * 16, v);
        }
        bar_sync(0, NTHREADS);
        const uint32_t tag = lds32(sm + OFF_TAG);
        float c[4];
#pragma unroll 1
        for (int which = 0; which < 2; which++) {
            matvecT(c, sm + OFF_S0 + which * 2 * CH, sm + OFF_XB + which * 2 * VROW, 2, bars + (B_WQB + which * 2) * 8, w, lane);
            if (t == 0) {
                ll_store2(&g_e1[which][cta][w * 16 + g], c[0], c[1], tag);
                ll_store2(&g_e1[which][cta][w * 16 + g + 8], c[2], c[3], tag);
            }
        }
        __syncwarp();
        if (lane == 0) mbar_arrive(bars + B_FREE * 8);
        if (st == 0) TS(8);
        if (st < 128) {
            float q0, q1;
            sleep_ns(POLL_DELAY);
            ll_gather4(&g_e1[1][h * 4][st], tag, q0, q1);
            sts16(sm + OFF_QA + st * 2, f2bf(q0)); sts16(sm + OFF_QA + VROW + st * 2, f2bf(q1));
        }
        bar_sync(2, 256);
        if (st == 0) TS(9);
        {
            const int row = w * 16 + rr + 8 * (i & 1);
            const uint32_t a0 = sm + OFF_S2 + (row >> 6) * CH + (row & 63) * 128;
            const uint32_t va = sm + OFF_QA + g * VROW + t * 4;
            float d[4] = {0.f, 0.f, 0.f, 0.f};
            c[0] = c[1] = c[2] = c[3] = 0.f;
            mbar_wait(bars + (B_WUK + (w >> 2)) * 8, 0);
#pragma unroll
            for (int ks = 0; ks < 8; ks++) {
                const int chunk = 2 * ks + (i >> 1);
                uint32_t a[4];
                ldsm4(a, a0 + (chunk >> 3) * 8192 + (((chunk & 7) ^ rr) << 4));
                const uint32_t b0 = (g < 2) ? lds32(va + ks * 32) : 0u, b1 = (g < 2) ? lds32(va + ks * 32 + 16) : 0u;
                if (ks & 1) mma(d, a, b0, b1); else mma(c, a, b0, b1);
            }
            if (t == 0) {
                const uint32_t qs = sm + OFF_QS + (w * 16 + g) * 2;
                sts16(qs, f2bf(c[0] + d[0])); sts16(qs + VROW, f2bf(c[1] + d[1]));
                sts16(qs + 16, f2bf(c[2] + d[2])); sts16(qs + VROW + 16, f2bf(c[3] + d[3]));
            }
            bar_sync(2, 256);
            if (w == 0) {
                const int b = lane >> 4, cc = lane & 15;
                g_qabs[(b * 32 + h) * 64 + ((j * 16 + cc) ^ (h & 7))] = lds128(sm + OFF_QS + b * VROW + cc * 16);
                __syncwarp();
                if (lane == 0) {
                    cnt_rendezvous(&g_cnt[0], tag * 128u, 18);
                    TS(10);
                    mbar_expect(bars + B_GATH * 8, 2 * CH);
                    bulk1d_n(sm + OFF_S2, g_qabs + (cta >> 6) * 2048, 2 * CH, bars + B_GATH * 8);
                }
                __syncwarp();
            }
        }
        mbar_wait(bars + B_GATH * 8, 0);
        if (st == 0) TS(11);
        {
            const int mt = w & 1, kg = w >> 1;
            const uint32_t qa = sm + OFF_S2 + (mt * 16 + rr + 8 * (i & 1)) * 1024;
            const uint32_t ka = sm + OFF_S0 + kg * CH + (rr + 8 * (i >> 1)) * 128;
            float s0[4] = {0.f, 0.f, 0.f, 0.f}, s1[4] = {0.f, 0.f, 0.f, 0.f};
            mbar_wait(bars + (B_CKV + kg) * 8, 0);
#pragma unroll 2
            for (int gq = 0; gq < 8; gq++) {
#pragma unroll
                for (int k4 = 0; k4 < 4; k4++) {
                    uint32_t a[4], b[4];
                    ldsm4(a, qa + gq * 128 + (((2 * k4 + (i >> 1)) ^ rr) << 4));
                    ldsm4(b, ka + gq * 2048 + (((2 * k4 + (i & 1)) ^ rr) << 4));
                    mma(s0, a, b[0], b[1]);
                    mma(s1, a, b[2], b[3]);
                }
            }
            const uint32_t sa = sm + OFF_SC + ((mt * 16 + g) * 68 + kg * 16 + 2 * t) * 4;
            stsf2(sa, s0[0], s0[1]); stsf2(sa + 32, s1[0], s1[1]);
            stsf2(sa + 8 * 68 * 4, s0[2], s0[3]); stsf2(sa + 8 * 68 * 4 + 32, s1[2], s1[3]);
        }
        bar_sync(2, 256);
        {
            const int head = w * 4 + i;
            const uint32_t sa = sm + OFF_SC + (head * 68 + rr * 8) * 4;
            const uint4 u0 = lds128(sa), u1 = lds128(sa + 16);
            float s[8] = {__uint_as_float(u0.x), __uint_as_float(u0.y), __uint_as_float(u0.z), __uint_as_float(u0.w),
                          __uint_as_float(u1.x), __uint_as_float(u1.y), __uint_as_float(u1.z), __uint_as_float(u1.w)};
            float mx = s[0];
#pragma unroll
            for (int k = 1; k < 8; k++) mx = fmaxf(mx, s[k]);
#pragma unroll
            for (int o = 1; o < 8; o <<= 1) mx = fmaxf(mx, __shfl_xor_sync(0xffffffffu, mx, o));
            float sum = 0.f;
#pragma unroll
            for (int k = 0; k < 8; k++) { s[k] = ex2((s[k] - mx) * (SCALE * LOG2E)); sum += s[k]; }
#pragma unroll
            for (int o = 1; o < 8; o <<= 1) sum += __shfl_xor_sync(0xffffffffu, sum, o);
            const float inv = __fdividef(1.f, sum);
            uint4 p;
            p.x = pack2(s[0] * inv, s[1] * inv); p.y = pack2(s[2] * inv, s[3] * inv);
            p.z = pack2(s[4] * inv, s[5] * inv); p.w = pack2(s[6] * inv, s[7] * inv);
            sts128(sm + OFF_P + head * 128 + ((rr ^ (head & 7)) << 4), p);
            if (rr == 0) ((float*)g_lse)[head * 128 + cta] = mx * (SCALE * LOG2E) + lg2(sum);
        }
        bar_sync(2, 256);
        {
            float o[2][8][4];
#pragma unroll
            for (int mt = 0; mt < 2; mt++)
#pragma unroll
                for (int n = 0; n < 8; n++) { o[mt][n][0] = o[mt][n][1] = o[mt][n][2] = o[mt][n][3] = 0.f; }
            const uint32_t pa = sm + OFF_P + (rr + 8 * (i & 1)) * 128;
            const uint32_t va = sm + OFF_S0 + w * 2048 + (rr + 8 * (i & 1)) * 128;
#pragma unroll 1
            for (int kq = 0; kq < 4; kq++) {
                uint32_t a0[4], a1[4];
                ldsm4(a0, pa + (((2 * kq + (i >> 1)) ^ rr) << 4));
                ldsm4(a1, pa + 2048 + (((2 * kq + (i >> 1)) ^ rr) << 4));
#pragma unroll
                for (int n = 0; n < 8; n += 2) {
                    uint32_t b[4];
                    ldsm4t(b, va + kq * CH + (((n + (i >> 1)) ^ rr) << 4));
                    mma(o[0][n], a0, b[0], b[1]); mma(o[1][n], a1, b[0], b[1]);
                    mma(o[0][n + 1], a0, b[2], b[3]); mma(o[1][n + 1], a1, b[2], b[3]);
                }
            }
#pragma unroll
            for (int mt = 0; mt < 2; mt++)
#pragma unroll
                for (int hf = 0; hf < 2; hf++) {
                    const uint32_t dst = sm + OFF_S2 + (mt * 16 + hf * 8 + g) * 1024 + w * 128 + t * 16;
#pragma unroll
                    for (int nb = 0; nb < 2; nb++) {
                        uint4 v;
                        v.x = pack2(o[mt][nb * 4 + 0][hf * 2], o[mt][nb * 4 + 0][hf * 2 + 1]);
                        v.y = pack2(o[mt][nb * 4 + 1][hf * 2], o[mt][nb * 4 + 1][hf * 2 + 1]);
                        v.z = pack2(o[mt][nb * 4 + 2][hf * 2], o[mt][nb * 4 + 2][hf * 2 + 1]);
                        v.w = pack2(o[mt][nb * 4 + 3][hf * 2], o[mt][nb * 4 + 3][hf * 2 + 1]);
                        sts128(dst + nb * 64, v);
                    }
                }
            asm volatile("fence.proxy.async.shared::cta;" ::: "memory");
            __syncwarp();
            if (lane == 0) mbar_arrive(bars + B_FREE * 8);
            if (st < 98) *(st < 64 ? &g_e4[cta][st] : st < 96 ? &g_e5[cta][st - 64] : &g_l5[h][j * 2 + st - 96]) = make_uint4(EMPTY, EMPTY, EMPTY, EMPTY);
            else if (st < 100) ((uint4*)out)[cta * 2 + st - 98] = make_uint4(0u, 0u, 0u, 0u);
        }
        bar_sync(2, 256);
        if (st == 0) {
            TS(12);
#pragma unroll 1
            for (int k = 0; k < ST_SPLIT; k++) {
                asm volatile("cp.async.bulk.tensor.3d.global.shared::cta.bulk_group [%0, {%2,%3,%4}], [%1];"
                             ::"l"(&maps.ctxp), "r"(sm + OFF_S2 + k * (2 * CH / ST_SPLIT)), "r"(0), "r"(cta), "r"(k * (128 / ST_SPLIT)) : "memory");
                if (k + 1 < ST_SPLIT) __nanosleep(ST_GAP);
            }
            asm volatile("cp.async.bulk.commit_group;" ::: "memory");
            asm volatile("cp.async.bulk.wait_group 0;" ::: "memory");
            cnt_rendezvous(&g_cnt[1], tag * 128u, 20);
            TS(13);
            mbar_expect(bars + B_GATH * 8, 2 * CH + 512);
            bulk1d_n(sm + OFF_LSE, g_lse + h * 32, 512, bars + B_GATH * 8);
#pragma unroll 1
            for (int k = 0; k < G_SPLIT; k++) {
                bulk1d_n(sm + OFF_S2 + k * (2 * CH / G_SPLIT), g_ctxp + cta * 2048 + k * (2048 / G_SPLIT), 2 * CH / G_SPLIT, bars + B_GATH * 8);
                if (k + 1 < G_SPLIT) __nanosleep(G_GAP);
            }
        }
        __syncwarp();
        {
            mbar_wait(bars + B_GATH * 8, 1);
            if (st == 0) TS(22);
            uint4 v[8];
#pragma unroll
            for (int k = 0; k < 8; k++) v[k] = lds128(sm + OFF_S2 + (k * 256 + st) * 16);
            float ls[4];
#pragma unroll
            for (int k = 0; k < 4; k++) ls[k] = ldsf(sm + OFF_LSE + (k * 32 + lane) * 4);
            float m0 = fmaxf(ls[0], ls[1]), m1 = fmaxf(ls[2], ls[3]);
#pragma unroll
            for (int o = 16; o; o >>= 1) { m0 = fmaxf(m0, __shfl_xor_sync(0xffffffffu, m0, o)); m1 = fmaxf(m1, __shfl_xor_sync(0xffffffffu, m1, o)); }
            ls[0] = ex2(ls[0] - m0); ls[1] = ex2(ls[1] - m0); ls[2] = ex2(ls[2] - m1); ls[3] = ex2(ls[3] - m1);
            float z0 = ls[0] + ls[1], z1 = ls[2] + ls[3];
#pragma unroll
            for (int o = 16; o; o >>= 1) { z0 += __shfl_xor_sync(0xffffffffu, z0, o); z1 += __shfl_xor_sync(0xffffffffu, z1, o); }
            z0 = __fdividef(1.f, z0); z1 = __fdividef(1.f, z1);
            ls[0] *= z0; ls[1] *= z0; ls[2] *= z1; ls[3] *= z1;
            float a[2][8];
#pragma unroll
            for (int e = 0; e < 8; e++) a[0][e] = a[1][e] = 0.f;
            const int rg = st >> 4;
#pragma unroll
            for (int k = 0; k < 8; k++) {
                const float wt = __shfl_sync(0xffffffffu, ls[k >> 1], rg + 16 * (k & 1));
                const uint32_t u[4] = {v[k].x, v[k].y, v[k].z, v[k].w};
#pragma unroll
                for (int e = 0; e < 4; e++) {
                    a[k >> 2][2 * e] += wt * __uint_as_float(u[e] << 16);
                    a[k >> 2][2 * e + 1] += wt * __uint_as_float(u[e] & 0xffff0000u);
                }
            }
            const int b = lane >> 4, u16 = lane & 15;
            const uint32_t ra = sm + OFF_SC + (w * 256 + b * 128 + (u16 >> 3) * 64 + ((u16 >> 2) & 1) * 32 + (u16 & 3) * 2) * 4;
#pragma unroll
            for (int e = 0; e < 8; e += 2) {
                const float k0 = b ? a[1][e] : a[0][e], k1 = b ? a[1][e + 1] : a[0][e + 1];
                const float s0 = b ? a[0][e] : a[1][e], s1 = b ? a[0][e + 1] : a[1][e + 1];
                stsf2(ra + (e >> 1) * 32, k0 + __shfl_xor_sync(0xffffffffu, s0, 16), k1 + __shfl_xor_sync(0xffffffffu, s1, 16));
            }
            bar_sync(2, 256);
            if (st == 0) mbar_arrive(bars + B_S2 * 8);
            float s = 0.f;
#pragma unroll
            for (int k = 0; k < 8; k++) s += ldsf(sm + OFF_SC + (k * 256 + st) * 4);
            const float hi = bfround(s);
            const uint32_t ca = sm + OFF_CC + (st >> 7) * VROW + (st & 127) * 2;
            sts16(ca, f2bf(hi)); sts16(ca + 2 * VROW, f2bf(s - hi));
            bar_sync(2, 256);
        }
        matvecT(c, sm + OFF_S1, sm + OFF_CC, 4, bars + B_WUV * 8, w, lane);
#pragma unroll
        for (int k = 0; k < 4; k++) c[k] += __shfl_down_sync(0xffffffffu, c[k], 1);
        if (t == 0) {
            float* const e = (float*)g_e4[cta] + w * 16 + g;
            mail_put(e, c[0]); mail_put(e + 128, c[1]); mail_put(e + 8, c[2]); mail_put(e + 136, c[3]);
        }
        __syncwarp();
        if (lane == 0) mbar_arrive(bars + B_FREE * 8);
        if (st == 0) TS(23);
        {
            const uint4* const pv = &g_e4[(cta & ~15) + (w >> 1) * 4][(w & 1) * 32 + lane];
            uint4 x[4];
            uint32_t it = 0;
            sleep_ns(POLL_DELAY2);
            while (true) {
#pragma unroll
                for (int k = 0; k < 4; k++) { x[k].x = x[k].y = x[k].z = x[k].w = 0u; mail_get(x[k], pv + k * 64); }
                if (!__any_sync(0xffffffffu, mail_missing(x[0]) | mail_missing(x[1]) | mail_missing(x[2]) | mail_missing(x[3]))) break;
                if (++it > SPIN_MAX) __trap();
                __nanosleep(BACKOFF);
            }
#define SUM4(e) ((__uint_as_float(x[0].e) + __uint_as_float(x[1].e)) + (__uint_as_float(x[2].e) + __uint_as_float(x[3].e)))
            sts64(sm + OFF_CA + w * VROW + lane * 8, pack2(SUM4(x), SUM4(y)), pack2(SUM4(z), SUM4(w)));
#undef SUM4
        }
        if (st == 0) TS(14);
        bar_sync(4, 256 + 128);
        {
            const uint32_t a0 = sm + OFF_S0 + w * 1024 + (rr + 8 * (i >> 1)) * 64 + (((i & 1) ^ (rr >> 1)) << 4);
            const uint4* const pv = pin(&g_e5[(cta & ~15) + (w >> 1) * 4 + (g & 3)][(g >> 2) * 16 + (w & 1) * 8 + t]);
            const uint32_t* const pl = pin((const uint32_t*)g_l5[(h & ~3) + (w >> 1)] + rr);
            const uint32_t wa = sm + OFF_SC + ((w * 2 + (t & 1)) * 80 + (t >> 1) * 40 + g) * 4;
            __nv_bfloat16* const outp = pin(out + (lane >> 4) * 1024 + 512 + (cta & 15) * 32 + (lane & 15) * 2);
            uint32_t a[4][2][4], xl = 0u, it = 0;
            uint4 x[2] = {make_uint4(0u, 0u, 0u, 0u), make_uint4(0u, 0u, 0u, 0u)};
            while (true) {
                if (lane < 8) asm volatile("atom.relaxed.gpu.global.or.b32 %0, [%1], 0;" : "=r"(xl) : "l"(pl) : "memory");
                if (!__any_sync(0xffffffffu, xl == EMPTY)) break;
                if (++it > SPIN_MAX) __trap();
            }
            if (st == 0) TS(25);
            mail_get(x[0], pv); mail_get(x[1], pv + 4);
            float w0 = __uint_as_float(xl), w1 = fmaxf(w0, __shfl_xor_sync(0xffffffffu, w0, 1));
            w0 = ex2(w0 - fmaxf(w1, __shfl_xor_sync(0xffffffffu, w1, 2)));
            w1 = w0 + __shfl_xor_sync(0xffffffffu, w0, 1);
            w0 *= rcp(w1 + __shfl_xor_sync(0xffffffffu, w1, 2));
            w1 = __shfl_sync(0xffffffffu, w0, 2 * t + 1);
            w0 = __shfl_sync(0xffffffffu, w0, 2 * t);
#pragma unroll
            for (int q = 0; q < 4; q++) {
                mbar_wait(bars + (B_WO + q) * 8, 0);
                ldsm4t(a[q][0], a0 + q * 8192);
                ldsm4t(a[q][1], (a0 ^ 32) + q * 8192);
            }
            if (st == 0) TS(26);
            while (true) {
                const bool n0 = mail_missing(x[0]), n1 = mail_missing(x[1]);
                if (!__any_sync(0xffffffffu, n0 | n1)) break;
                mail_get(x[0], pv, n0); mail_get(x[1], pv + 4, n1);
                if (++it > SPIN_MAX) __trap();
            }
            if (st == 0) TS(16);
            float d[2][2][4];
#pragma unroll
            for (int k = 0; k < 4; k++) {
                float (&dk)[4] = d[k >> 1][k & 1];
                dk[0] = dk[1] = dk[2] = dk[3] = 0.f;
                mma(dk, a[k >> 1][k & 1], x[k >> 1].x, x[k >> 1].y);
            }
#pragma unroll
            for (int k = 0; k < 4; k++) mma(d[k >> 1][k & 1], a[2 + (k >> 1)][k & 1], x[k >> 1].z, x[k >> 1].w);
#pragma unroll
            for (int k = 0; k < 4; k++) {
                const int e = (k & 1) * 2;
                sts32(wa + k * 32, __float_as_uint(w0 * (d[0][k >> 1][e] + d[1][k >> 1][e]) + w1 * (d[0][k >> 1][e + 1] + d[1][k >> 1][e + 1])));
            }
            if (st == 0) TS(17);
            if (w == 0) {
                bar_sync(5, 256);
                const uint32_t ra = sm + OFF_SC + ((lane >> 4) * 40 + (lane & 15) * 2) * 4;
                float2 r[16];
#pragma unroll
                for (int k = 0; k < 16; k++) r[k] = ldsf2(ra + k * 320);
#pragma unroll
                for (int o = 1; o < 16; o <<= 1)
#pragma unroll
                    for (int k = 0; k < 16; k += 2 * o) { r[k].x += r[k + o].x; r[k].y += r[k + o].y; }
                out_add(outp, r[0].x, r[0].y);
            } else {
                bar_arrive(5, 256);
            }
        }
    }
}

typedef CUresult (*EncodeFn)(CUtensorMap*, CUtensorMapDataType, cuuint32_t, void*, const cuuint64_t*, const cuuint64_t*,
                             const cuuint32_t*, const cuuint32_t*, CUtensorMapInterleave, CUtensorMapSwizzle,
                             CUtensorMapL2promotion, CUtensorMapFloatOOBfill);

void make_map(EncodeFn enc, CUtensorMap* m, void* p, unsigned rows, unsigned cols, unsigned br, unsigned bg) {
    cuuint64_t gd[3] = {64, rows, cols / 64};
    cuuint64_t gs[2] = {(cuuint64_t)cols * 2, 128};
    cuuint32_t bx[3] = {64, br, bg};
    cuuint32_t es[3] = {1, 1, 1};
    enc(m, CU_TENSOR_MAP_DATA_TYPE_BFLOAT16, 3, p, gd, gs, bx, es, CU_TENSOR_MAP_INTERLEAVE_NONE,
        CU_TENSOR_MAP_SWIZZLE_128B, CU_TENSOR_MAP_L2_PROMOTION_L2_128B, CU_TENSOR_MAP_FLOAT_OOB_FILL_NONE);
}

}

extern "C" void kernel_launch(void* const* d_in, const int* in_sizes, int n_in, void* d_out, int out_size) {
    static EncodeFn enc = nullptr;
    if (!enc) {
        void* fn = nullptr;
        cudaDriverEntryPointQueryResult qr;
        cudaGetDriverEntryPoint("cuTensorMapEncodeTiled", &fn, cudaEnableDefault, &qr);
        enc = (EncodeFn)fn;
        cudaFuncSetAttribute(fused_decode_kernel, cudaFuncAttributeMaxDynamicSharedMemorySize, SMEM_BYTES);
    }
    Maps maps;
    make_map(enc, &maps.wqB, d_in[9], 512, 4096, 64, 2);
    make_map(enc, &maps.wqA, d_in[2], 512, 4096, 64, 2);
    make_map(enc, &maps.wuk, d_in[3], 512, 4096, 64, 2);
    make_map(enc, &maps.wuv, d_in[4], 512, 4096, 64, 2);
    for (int k = 0; k < 2; k++) {
        cuuint64_t gd[3] = {512, 128, 32};
        cuuint64_t gs[2] = {1024, 131072};
        cuuint32_t bx[3] = {32, 32, 4};
        cuuint32_t es[3] = {1, 1, 1};
        enc(&maps.woB + k, CU_TENSOR_MAP_DATA_TYPE_BFLOAT16, 3, d_in[k ? 5 : 10], gd, gs, bx, es, CU_TENSOR_MAP_INTERLEAVE_NONE,
            CU_TENSOR_MAP_SWIZZLE_64B, CU_TENSOR_MAP_L2_PROMOTION_L2_256B, CU_TENSOR_MAP_FLOAT_OOB_FILL_NONE);
    }
    make_map(enc, &maps.ckv, d_in[1], 8192, 512, 16, 8);
    {
        void* p = nullptr;
        cudaGetSymbolAddress(&p, g_ctxp);
        cuuint64_t gd[3] = {128, 128, 128};
        cuuint64_t gs[2] = {256, 32768};
        cuuint32_t bx[3] = {128, 1, 128 / ST_SPLIT};
        cuuint32_t es[3] = {1, 1, 1};
        enc(&maps.ctxp, CU_TENSOR_MAP_DATA_TYPE_BFLOAT16, 3, p, gd, gs, bx, es, CU_TENSOR_MAP_INTERLEAVE_NONE,
            CU_TENSOR_MAP_SWIZZLE_NONE, CU_TENSOR_MAP_L2_PROMOTION_NONE, CU_TENSOR_MAP_FLOAT_OOB_FILL_NONE);
    }
    fused_decode_kernel<<<NCTA, NTHREADS, SMEM_BYTES>>>((const char*)d_in[9], maps, (const char*)d_in[7], (const char*)d_in[8],
                                                         (const __nv_bfloat16*)d_in[0], (const __nv_bfloat16*)d_in[6],
                                                         (__nv_bfloat16*)d_out, 0u);
}
```

```cpp
#include <cuda_runtime.h>
#include <cuda.h>
#include <cuda_bf16.h>
#include <stdint.h>

#define RING 7
#define WIN 4
#define WHI 5
#define THETA 64
#define END_V 40
#define GATE_W 192
#define OP_CLK16 158
#define BOX_FIRST 450
#define BOX_CLK 600
#define TAIL_LO 4
#define TAIL_HI 7
#define POLL_DELAY 2500
#define POLL_DELAY2 3000
#define ST_SPLIT 32
#define ST_GAP 200
#define G_SPLIT 8
#define G_GAP 250
#define BACKOFF 200
#define BACKOFF2 100

namespace {

constexpr int NCTA = 128;
constexpr int NTHREADS = 448;
constexpr uint32_t CH = 16384;
constexpr int NTILE = 32;
constexpr int RUN = 4;

constexpr uint32_t OFF_RING = 0;
constexpr uint32_t OFF_S0 = RING * CH;
constexpr uint32_t OFF_S1 = OFF_S0 + 2 * CH;
constexpr uint32_t OFF_S2 = OFF_S1 + 2 * CH;
constexpr uint32_t OFF_P = OFF_S2 + 2 * CH;
constexpr uint32_t OFF_SC = OFF_P + 4096;
constexpr uint32_t VROW = 272;
constexpr uint32_t OFF_XB = OFF_SC + 8704;
constexpr uint32_t OFF_XA = OFF_XB + 2 * VROW;
constexpr uint32_t OFF_QA = OFF_XA + 2 * VROW;
constexpr uint32_t OFF_QS = OFF_QA + 2 * VROW;
constexpr uint32_t OFF_CC = OFF_QS + 2 * VROW;
constexpr uint32_t OFF_CA = OFF_P;
constexpr uint32_t OFF_QB = OFF_CC + 4 * VROW;
constexpr uint32_t OFF_LSE = OFF_QB + 512;
constexpr uint32_t OFF_ML = OFF_LSE + 512;
constexpr uint32_t OFF_TAG = OFF_ML + 64;
constexpr uint32_t OFF_NOW = OFF_TAG + 4;
constexpr uint32_t OFF_WIN = OFF_TAG + 8;
constexpr uint32_t OFF_BAR = OFF_TAG + 16;
constexpr int B_EMPTY = RING;
constexpr int B_WQB = 2 * RING;
constexpr int B_WQA = B_WQB + 2;
constexpr int B_WUK = B_WQA + 2;
constexpr int B_WUV = B_WUK + 2;
constexpr int B_CKV = B_WUV + 2;
constexpr int B_WO = B_CKV + 4;
constexpr int B_FREE = B_WO + 8;
constexpr int B_GATH = B_FREE + 1;
constexpr int B_S2 = B_GATH + 1;
constexpr int NBAR = B_S2 + 1;
constexpr uint32_t TS_OFF = OFF_BAR + NBAR * 8;
constexpr uint32_t SMEM_USED = TS_OFF;
constexpr uint32_t SMEM_BYTES = SMEM_USED + 1024;
static_assert(SMEM_BYTES <= 232448, "smem");
static_assert(RING >= RUN && RING >= WHI && WHI >= WIN && WHI >= 4 && WIN >= 3 && WIN <= 6 && TAIL_HI >= 4, "windows");

constexpr float LOG2E = 1.4426950408889634f;
constexpr float SCALE = 0.08838834764831845f;
#define SPIN_LOG 22
constexpr uint32_t SPIN_MAX = 1u << SPIN_LOG;

struct Maps { CUtensorMap wqB, wqA, wuk, wuv, woB, woA, ckv, ctxp; };

__device__ __align__(256) unsigned g_cnt[32];
__device__ __align__(256) ulonglong2 g_e1[2][NCTA][128];
__device__ __align__(256) uint4 g_qabs[2 * 32 * 64];
__device__ __align__(256) uint4 g_ctxp[NCTA * 128 * 16];
__device__ __align__(256) float4 g_lse[32 * 32];
__device__ __align__(256) uint4 g_e4[NCTA][64];
__device__ __align__(256) uint4 g_e5[NCTA][32];
__device__ __align__(256) uint4 g_l5[32][8];
constexpr uint32_t EMPTY = 0xffffffffu;

#define TS(k) do {} while (0)

__device__ __forceinline__ void mbar_init(uint32_t b, int c) { asm volatile("mbarrier.init.shared::cta.b64 [%0], %1;" ::"r"(b), "r"(c) : "memory"); }
__device__ __forceinline__ void mbar_expect(uint32_t b, uint32_t bytes) { asm volatile("mbarrier.arrive.expect_tx.shared::cta.b64 _, [%0], %1;" ::"r"(b), "r"(bytes) : "memory"); }
__device__ __forceinline__ void mbar_arrive(uint32_t b) { asm volatile("mbarrier.arrive.shared::cta.b64 _, [%0];" ::"r"(b) : "memory"); }
__device__ __forceinline__ void mbar_wait(uint32_t b, uint32_t ph) {
    asm volatile("{\n.reg .pred p;\n.reg .u32 n;\nmov.u32 n, 0;\n"
                 "W:\nmbarrier.try_wait.parity.shared::cta.b64 p, [%0], %1;\n@p bra D;\n"
                 "add.u32 n, n, 1;\nsetp.le.u32 p, n, %2;\n@p bra W;\ntrap;\nD:\n}" ::"r"(b), "r"(ph), "n"(SPIN_MAX) : "memory");
}
__device__ __forceinline__ uint32_t mbar_test(uint32_t b, uint32_t ph) {
    uint32_t ok;
    asm volatile("{\n.reg .pred p;\nmbarrier.test_wait.parity.shared::cta.b64 p, [%1], %2;\nselp.u32 %0, 1, 0, p;\n}" : "=r"(ok) : "r"(b), "r"(ph) : "memory");
    return ok;
}
__device__ __forceinline__ void bulk1d(uint32_t dst, const void* src, uint32_t bar, uint64_t pol) {
    asm volatile("cp.async.bulk.shared::cluster.global.mbarrier::complete_tx::bytes.L2::cache_hint [%0], [%1], %2, [%3], %4;"
                 ::"r"(dst), "l"(src), "n"(CH), "r"(bar), "l"(pol) : "memory");
}
__device__ __forceinline__ void bulk1d_n(uint32_t dst, const void* src, uint32_t bytes, uint32_t bar) {
    asm volatile("cp.async.bulk.shared::cluster.global.mbarrier::complete_tx::bytes [%0], [%1], %2, [%3];"
                 ::"r"(dst), "l"(src), "r"(bytes), "r"(bar) : "memory");
}
__device__ __forceinline__ void tma3d(uint32_t dst, const CUtensorMap* map, int c1, int c2, uint32_t bar, uint64_t pol, int c0 = 0) {
    asm volatile("cp.async.bulk.tensor.3d.shared::cluster.global.mbarrier::complete_tx::bytes.L2::cache_hint [%0], [%1, {%3,%4,%5}], [%2], %6;"
                 ::"r"(dst), "l"(map), "r"(bar), "r"(c0), "r"(c1), "r"(c2), "l"(pol) : "memory");
}
__device__ __forceinline__ void bar_sync(int id, int n) { asm volatile("barrier.cta.sync %0, %1;" ::"r"(id), "r"(n) : "memory"); }
__device__ __forceinline__ void bar_arrive(int id, int n) { asm volatile("barrier.cta.arrive %0, %1;" ::"r"(id), "r"(n) : "memory"); }
__device__ __forceinline__ void ldsm4(uint32_t (&r)[4], uint32_t a) {
    asm volatile("ldmatrix.sync.aligned.m8n8.x4.shared.b16 {%0,%1,%2,%3}, [%4];" : "=r"(r[0]), "=r"(r[1]), "=r"(r[2]), "=r"(r[3]) : "r"(a) : "memory");
}
__device__ __forceinline__ void ldsm4t(uint32_t (&r)[4], uint32_t a) {
    asm volatile("ldmatrix.sync.aligned.m8n8.x4.trans.shared.b16 {%0,%1,%2,%3}, [%4];" : "=r"(r[0]), "=r"(r[1]), "=r"(r[2]), "=r"(r[3]) : "r"(a) : "memory");
}
__device__ __forceinline__ bool box_load(uint32_t (&r)[4], uint32_t (&s)[4], uint32_t (&u)[4], uint32_t (&v)[4], uint32_t bar, uint32_t a) {
    uint32_t ok;
    asm volatile("{\n.reg .pred p;\nmbarrier.try_wait.parity.shared::cta.b64 p, [%17], 0;\n"
                 "@p ldmatrix.sync.aligned.m8n8.x4.trans.shared.b16 {%0,%1,%2,%3}, [%18];\n"
                 "@p ldmatrix.sync.aligned.m8n8.x4.trans.shared.b16 {%4,%5,%6,%7}, [%18 + 2048];\n"
                 "@p ldmatrix.sync.aligned.m8n8.x4.trans.shared.b16 {%8,%9,%10,%11}, [%18 + 4096];\n"
                 "@p ldmatrix.sync.aligned.m8n8.x4.trans.shared.b16 {%12,%13,%14,%15}, [%18 + 6144];\n"
                 "selp.u32 %16, 1, 0, p;\n}"
                 : "+r"(r[0]), "+r"(r[1]), "+r"(r[2]), "+r"(r[3]), "+r"(s[0]), "+r"(s[1]), "+r"(s[2]), "+r"(s[3]),
                   "+r"(u[0]), "+r"(u[1]), "+r"(u[2]), "+r"(u[3]), "+r"(v[0]), "+r"(v[1]), "+r"(v[2]), "+r"(v[3]), "=r"(ok)
                 : "r"(bar), "r"(a) : "memory");
    return ok != 0;
}
__device__ __forceinline__ void mma(float (&c)[4], const uint32_t (&a)[4], uint32_t b0, uint32_t b1) {
    asm volatile("mma.sync.aligned.m16n8k16.row.col.f32.bf16.bf16.f32 {%0,%1,%2,%3}, {%4,%5,%6,%7}, {%8,%9}, {%0,%1,%2,%3};"
                 : "+f"(c[0]), "+f"(c[1]), "+f"(c[2]), "+f"(c[3]) : "r"(a[0]), "r"(a[1]), "r"(a[2]), "r"(a[3]), "r"(b0), "r"(b1));
}
__device__ __forceinline__ uint32_t lds32(uint32_t a) { uint32_t v; asm volatile("ld.shared.b32 %0, [%1];" : "=r"(v) : "r"(a) : "memory"); return v; }
__device__ __forceinline__ uint32_t ldsv(uint32_t a) { uint32_t v; asm volatile("ld.volatile.shared.b32 %0, [%1];" : "=r"(v) : "r"(a) : "memory"); return v; }
__device__ __forceinline__ void stsv(uint32_t a, uint32_t v) { asm volatile("st.volatile.shared.b32 [%0], %1;" ::"r"(a), "r"(v) : "memory"); }
__device__ __forceinline__ float ldsf(uint32_t a) { float v; asm volatile("ld.shared.f32 %0, [%1];" : "=f"(v) : "r"(a) : "memory"); return v; }
__device__ __forceinline__ uint4 lds128(uint32_t a) { uint4 v; asm volatile("ld.shared.v4.b32 {%0,%1,%2,%3}, [%4];" : "=r"(v.x), "=r"(v.y), "=r"(v.z), "=r"(v.w) : "r"(a) : "memory"); return v; }
__device__ __forceinline__ void sts16(uint32_t a, uint16_t v) { asm volatile("st.shared.b16 [%0], %1;" ::"r"(a), "h"(v) : "memory"); }
__device__ __forceinline__ void sts32(uint32_t a, uint32_t v) { asm volatile("st.shared.b32 [%0], %1;" ::"r"(a), "r"(v) : "memory"); }
__device__ __forceinline__ void stsf2(uint32_t a, float x, float y) { asm volatile("st.shared.v2.f32 [%0], {%1,%2};" ::"r"(a), "f"(x), "f"(y) : "memory"); }
__device__ __forceinline__ void sts128(uint32_t a, uint4 v) { asm volatile("st.shared.v4.b32 [%0], {%1,%2,%3,%4};" ::"r"(a), "r"(v.x), "r"(v.y), "r"(v.z), "r"(v.w) : "memory"); }
__device__ __forceinline__ uint16_t f2bf(float x) { return __bfloat16_as_ushort(__float2bfloat16_rn(x)); }
__device__ __forceinline__ float bfround(float x) { return __bfloat162float(__float2bfloat16_rn(x)); }
__device__ __forceinline__ uint32_t pack2(float lo, float hi) { uint32_t r; asm("cvt.rn.bf16x2.f32 %0, %1, %2;" : "=r"(r) : "f"(hi), "f"(lo)); return r; }
__device__ __forceinline__ float ex2(float x) { float r; asm("ex2.approx.ftz.f32 %0, %1;" : "=f"(r) : "f"(x)); return r; }
__device__ __forceinline__ float lg2(float x) { float r; asm("lg2.approx.ftz.f32 %0, %1;" : "=f"(r) : "f"(x)); return r; }

__device__ __forceinline__ float rcp(float x) { float r; asm("rcp.approx.ftz.f32 %0, %1;" : "=f"(r) : "f"(x)); return r; }

__device__ __forceinline__ uint32_t clock_lo() { uint32_t t; asm volatile("mov.u32 %0, %clock;" : "=r"(t) :: "memory"); return t; }
__device__ __forceinline__ void sleep_ns(uint32_t ns) {
    const uint32_t t0 = clock_lo();
    do { __nanosleep(200); } while (clock_lo() - t0 < 2 * ns);
}

__device__ __forceinline__ void ll_store2(ulonglong2* p, float a, float b, uint32_t tag) {
    unsigned long long x = ((unsigned long long)tag << 32) | __float_as_uint(a);
    unsigned long long y = ((unsigned long long)tag << 32) | __float_as_uint(b);
    asm volatile("st.relaxed.gpu.global.v2.b64 [%0], {%1,%2};" ::"l"(p), "l"(x), "l"(y) : "memory");
}
__device__ __forceinline__ void ll_ld2(const void* p, unsigned long long& x, unsigned long long& y) {
    asm volatile("ld.relaxed.gpu.global.v2.b64 {%0,%1}, [%2];" : "=l"(x), "=l"(y) : "l"(p) : "memory");
}
__device__ __forceinline__ void ll_gather4(const ulonglong2* p, uint32_t tag, float& r0, float& r1) {
    unsigned long long x[4], y[4]; uint32_t it = 0;
    while (true) {
        bool ok = true;
#pragma unroll
        for (int k = 0; k < 4; k++) ll_ld2(p + k * 128, x[k], y[k]);
#pragma unroll
        for (int k = 0; k < 4; k++) ok = ok && (uint32_t)(x[k] >> 32) == tag && (uint32_t)(y[k] >> 32) == tag;
        if (ok) break;
        if (++it > SPIN_MAX) __trap();
        __nanosleep(BACKOFF);
    }
    r0 = (__uint_as_float((uint32_t)x[0]) + __uint_as_float((uint32_t)x[1])) + (__uint_as_float((uint32_t)x[2]) + __uint_as_float((uint32_t)x[3]));
    r1 = (__uint_as_float((uint32_t)y[0]) + __uint_as_float((uint32_t)y[1])) + (__uint_as_float((uint32_t)y[2]) + __uint_as_float((uint32_t)y[3]));
}
__device__ __forceinline__ void cnt_rendezvous(unsigned* c, uint32_t target, int tsk) {
    TS(tsk);
    asm volatile("red.release.gpu.global.add.u32 [%0], 1;" ::"l"(c) : "memory");
    if (tsk == 18) TS(tsk + 1);
    uint32_t v, it = 0;
    while (true) {
        asm volatile("ld.acquire.gpu.global.u32 %0, [%1];" : "=r"(v) : "l"(c) : "memory");
        if ((int)(v - target) >= 0) break;
        if (++it > SPIN_MAX) __trap();
        __nanosleep(BACKOFF);
    }
    asm volatile("fence.proxy.async.global;" ::: "memory");
}

__device__ __forceinline__ void matvec_loadA(uint32_t (&a)[8][4], uint32_t tile, uint32_t bar, int w, int lane) {
    const int i = lane >> 3, rr = lane & 7, chunk = 2 * w + (i & 1);
    const uint32_t a0 = tile + (chunk >> 3) * 8192 + (rr + 8 * (i >> 1)) * 128 + (((chunk & 7) ^ rr) << 4);
#pragma unroll
    for (int hh = 0; hh < 2; hh++) {
        mbar_wait(bar + hh * 8, 0);
#pragma unroll
        for (int k = 0; k < 4; k++) ldsm4t(a[hh * 4 + k], a0 + hh * CH + k * 2048);
    }
}
__device__ __forceinline__ void matvec_mma(float (&c)[4], const uint32_t (&a)[8][4], uint32_t vec, int nvec, int lane) {
    const uint32_t va = vec + (lane & (nvec - 1)) * VROW + (lane >> 3) * 16;
    float d[4][4];
#pragma unroll
    for (int q = 0; q < 4; q++) {
        uint32_t b[4];
        ldsm4(b, va + q * 64);
        d[q][0] = d[q][1] = d[q][2] = d[q][3] = 0.f;
        mma(d[q], a[2 * q], b[0], b[1]);
        mma(d[q], a[2 * q + 1], b[2], b[3]);
    }
#pragma unroll
    for (int k = 0; k < 4; k++) c[k] = (d[0][k] + d[1][k]) + (d[2][k] + d[3][k]);
}
__device__ __forceinline__ void matvecT(float (&c)[4], uint32_t tile, uint32_t vec, int nvec, uint32_t bar, int w, int lane) {
    uint32_t a[8][4];
    matvec_loadA(a, tile, bar, w, lane);
    matvec_mma(c, a, vec, nvec, lane);
}
template <class T> __device__ __forceinline__ T* pin(T* p) { asm volatile("" : "+l"(p)); return p; }
__device__ __forceinline__ void mail_put(void* p, uint32_t v) { asm volatile("st.relaxed.gpu.global.b32 [%0], %1;" ::"l"(p), "r"(v) : "memory"); }
__device__ __forceinline__ void mail_put(void* p, float v) { mail_put(p, __float_as_uint(v)); }
__device__ __forceinline__ void out_add(__nv_bfloat16* p, float x, float y) {
    asm volatile("red.relaxed.gpu.global.add.noftz.bf16x2 [%0], %1;" ::"l"(p), "r"(pack2(x, y)) : "memory");
}
__device__ __forceinline__ bool mail_missing(const uint4& v) { return v.x == EMPTY || v.y == EMPTY || v.z == EMPTY || v.w == EMPTY; }
__device__ __forceinline__ void mail_get(uint4& v, const uint4* p, bool need = true) {
    asm volatile("{\n.reg .pred q;\nsetp.ne.u32 q, %5, 0;\n@q ld.relaxed.gpu.global.v4.b32 {%0,%1,%2,%3}, [%4];\n}"
                 : "+r"(v.x), "+r"(v.y), "+r"(v.z), "+r"(v.w) : "l"(p), "r"((uint32_t)need) : "memory");
}
__device__ __forceinline__ void sts64(uint32_t a, uint32_t x, uint32_t y) { asm volatile("st.shared.v2.b32 [%0], {%1,%2};" ::"r"(a), "r"(x), "r"(y) : "memory"); }
__device__ __forceinline__ float2 ldsf2(uint32_t a) { float2 v; asm volatile("ld.shared.v2.f32 {%0,%1}, [%2];" : "=f"(v.x), "=f"(v.y) : "r"(a) : "memory"); return v; }

__global__ void __launch_bounds__(NTHREADS, 1)
fused_decode_kernel(const char* __restrict__ wqraw, const __grid_constant__ Maps maps, const char* __restrict__ Kc, const char* __restrict__ Vc,
                    const __nv_bfloat16* __restrict__ xA, const __nv_bfloat16* __restrict__ xB,
                    __nv_bfloat16* __restrict__ out, const uint32_t zero) {
    if (threadIdx.x == 0) asm volatile("cp.async.bulk.prefetch.L2.global [%0], 32768;" ::"l"(wqraw + (size_t)blockIdx.x * 32768u) : "memory");
    asm volatile("nanosleep.u32 60;" ::: "memory");
    asm volatile("barrier.cta.sync.aligned 7, %0;" ::"n"(NTHREADS) : "memory");
    asm volatile("{\n.reg .pred p;\n.reg .u32 s;\nmov.u32 s, %smid;\nsetp.eq.u32 p, s, 0xffff;\n@p exit;\n}" ::: "memory");
    extern __shared__ char smem_raw[];
    const uint32_t sm = ((uint32_t)__cvta_generic_to_shared(smem_raw) + 1023u) & ~1023u;
    const uint32_t bars = sm + OFF_BAR;
    const int cta = blockIdx.x, h = cta >> 2, j = cta & 3;
    uint64_t pol = 0;
    if (threadIdx.x == 0) {
        TS(0);
        asm volatile("createpolicy.fractional.L2::evict_first.b64 %0, 1.0;" : "=l"(pol));
#pragma unroll
        for (int i = 0; i < WIN; i++) mbar_init(bars + (B_WQB + i) * 8, 1);
        asm volatile("fence.mbarrier_init.release.cluster;" ::: "memory");
#pragma unroll
        for (int i = 0; i < WIN; i++) {
            mbar_expect(bars + (B_WQB + i) * 8, CH);
            tma3d(sm + OFF_S0 + i * CH, &maps.wqB + (i >> 1), j * 128 + (i & 1) * 64, h * 2, bars + (B_WQB + i) * 8, pol);
        }
    }
    const int tid = threadIdx.x < 64 ? threadIdx.x + 384 : threadIdx.x - 64, warp = tid >> 5, lane = tid & 31;

    if (warp == 12) {
        const size_t kvoff = (size_t)cta * (NTILE / 2 * CH);
        const char* kp = Kc + kvoff;
        const char* vp = Vc + kvoff;
        __syncwarp();
        bar_arrive(0, NTHREADS);
        bar_sync(3, 64);
        if (lane == 0) {
            uint32_t pb[WHI];
#pragma unroll
            for (int i = 0; i < WHI; i++) pb[i] = i < WHI - WIN ? (bars + B_WO * 8) | 1u : bars + (B_WQB + i - (WHI - WIN)) * 8;
            auto pace = [&](uint32_t bar, uint32_t par) {
                uint32_t it = 0;
                while (true) {
                    const uint32_t win = ldsv(sm + OFF_WIN);
                    uint32_t busy = 0;
#pragma unroll
                    for (int i = 0; i < WHI; i++) busy += mbar_test(pb[i] & ~1u, pb[i] & 1u) ^ 1u;
                    if (busy < win) break;
                    if (++it > SPIN_MAX) __trap();
                }
#pragma unroll
                for (int i = 0; i + 1 < WHI; i++) pb[i] = pb[i + 1];
                pb[WHI - 1] = bar | par;
            };
            auto side = [&](const CUtensorMap* m, uint32_t dst, int bidx, int c1, int c2) {
                const uint32_t bar = bars + bidx * 8;
                pace(bar, 0);
                mbar_expect(bar, CH);
                tma3d(dst, m, c1, c2, bar, pol);
            };
#pragma unroll 1
            for (int i = WIN; i < 6; i++)
                side(&maps.wqB + (i >> 1), sm + OFF_S0 + i * CH, B_WQB + i, j * 128 + (i & 1) * 64, h * 2);
            TS(1);
            uint32_t slot = 0, use = 0, tend = 0;
            int nuv = 0;
#pragma unroll 1
            for (int n = 0; n < 2 * NTILE; n++) {
                if (n == RING) {
                    mbar_wait(bars + B_FREE * 8, 0);
#pragma unroll 1
                    for (int q = 0; q < 4; q++) side(&maps.ckv, sm + OFF_S0 + q * CH, B_CKV + q, cta * 64 + q * 16, 0);
                }
                if (nuv < 2 && n > RING && (n >= 2 * NTILE - 8 || mbar_test(bars + B_FREE * 8, 1))) {
                    mbar_wait(bars + B_FREE * 8, 1);
                    side(&maps.wuv, sm + OFF_S1 + nuv * CH, B_WUV + nuv, j * 128 + nuv * 64, h * 2);
                    nuv++;
                }
                const uint32_t fb = bars + slot * 8;
                pace(fb, use & 1);
                mbar_wait(fb + B_EMPTY * 8, (use & 1) ^ 1);
                mbar_expect(fb, CH);
                bulk1d(sm + OFF_RING + slot * CH, ((n & RUN) ? vp : kp) + (size_t)(n / NTILE * (NCTA * NTILE / 2) + n % NTILE / (2 * RUN) * RUN + n % RUN) * CH, fb, pol);
                stsv(sm + OFF_NOW, n + 1);
                if (((n + cta) & 3) == 0) {
                    if (n >= 2 * NTILE - 6 && n < 2 * NTILE - 2) {
                        const uint32_t left = -atomicAdd(&g_cnt[2], 4u) & (NCTA * 2 * NTILE - 1);
                        stsv(sm + OFF_NOW, n + 1 + (left & zero));
                        tend = clock_lo() + left * OP_CLK16 / 16;
                    } else {
                        asm volatile("red.relaxed.gpu.global.add.u32 [%0], 4;" ::"l"(&g_cnt[2]) : "memory");
                    }
                }
                if (++slot == RING) { slot = 0; use++; }
            }
            TS(2);
            mbar_wait(bars + B_FREE * 8, 0);
#pragma unroll 1
            for (int i = 0; i < 8; i++) {
                uint32_t it = 0;
                while (true) {
                    uint32_t busy = i;
#pragma unroll
                    for (int k = 0; k < 4; k++) busy += 2 * (mbar_test(pb[WHI - 4 + k] & ~1u, pb[WHI - 4 + k] & 1u) ^ 1u);
#pragma unroll
                    for (int k = 0; k < 5; k++) busy -= mbar_test(bars + (B_WO + k) * 8, 0);
                    const uint32_t due = tend - BOX_FIRST + i * BOX_CLK;
                    if (busy < TAIL_LO) break;
                    if (busy < TAIL_HI && (int)(due - clock_lo()) < 400) {
                        while ((int)(due - clock_lo()) > 0) {}
                        break;
                    }
                    if (++it > SPIN_MAX) __trap();
                }
                if (i & 1) TS(32 + (i >> 1));
                mbar_expect(bars + (B_WO + i) * 8, CH / 2);
                tma3d(sm + OFF_S0 + i * (CH / 2), &maps.woB + (i >> 2), (i & 3) * 32, h & ~3, bars + (B_WO + i) * 8, pol, (cta & 15) * 32);
            }
            TS(3);
        }
    } else if (warp == 13) {
        if (lane == 0) {
#pragma unroll
            for (int i = 0; i < NBAR; i++)
                if (i < B_WQB || i >= B_WQB + WIN)
                    mbar_init(bars + i * 8, i == B_FREE ? 8 : (i >= B_EMPTY && i < B_EMPTY + RING) ? 4 : 1);
            asm volatile("fence.mbarrier_init.release.cluster;" ::: "memory");
#pragma unroll
            for (int i = 2; i < 8; i++) asm volatile("prefetch.tensormap [%0];" ::"l"(&maps.wqB + i) : "memory");
            stsv(sm + OFF_NOW, 0); stsv(sm + OFF_WIN, WIN);
        }
        __syncwarp();
        bar_arrive(3, 64);
        bar_sync(0, NTHREADS);
        if (lane == 0) {
            const uint32_t base = (lds32(sm + OFF_TAG) - 1u) * (NCTA * 2 * NTILE);
            mbar_wait(bars + (B_WUK + 1) * 8, 0);
            uint32_t it = 0;
            while (true) {
                const uint32_t n = ldsv(sm + OFF_NOW);
                uint32_t v;
                asm volatile("ld.relaxed.gpu.global.u32 %0, [%1];" : "=r"(v) : "l"(&g_cnt[2]) : "memory");
                v -= base;
                if (v >= NCTA * 2 * NTILE - GATE_W) break;
                const int diff = (int)(n * NCTA) - (int)v;
                stsv(sm + OFF_WIN, diff < -THETA ? WHI : WIN - (diff > THETA) - (v >= NCTA * END_V));
                if (++it > SPIN_MAX) __trap();
                __nanosleep(BACKOFF2);
            }
            stsv(sm + OFF_WIN, WHI);
            TS(24);
        }
    } else if (warp < 4) {
        const int g = lane >> 2, t = lane & 3, i = lane >> 3, rr = lane & 7;
        if (tid == 0) {
            unsigned e;
            asm volatile("ld.relaxed.gpu.global.u32 %0, [%1];" : "=r"(e) : "l"(&g_cnt[1]) : "memory");
            sts32(sm + OFF_TAG, (e >> 7) + 1u);
        }
        bar_sync(0, NTHREADS);
        const uint32_t tag = lds32(sm + OFF_TAG);
        {
            mbar_wait(bars + 8, 0);
            float q0, q1;
            ll_gather4(&g_e1[0][h * 4][tid], tag, q0, q1);
            sts16(sm + OFF_QB + tid * 2, f2bf(q0)); sts16(sm + OFF_QB + 256 + tid * 2, f2bf(q1));
        }
        bar_sync(1, 128);
        if (tid == 0) TS(4);
        uint32_t qf[8][2];
        float acc[8][4], m, l;
        auto start = [&](int b) {
#pragma unroll
            for (int c = 0; c < 8; c++) {
                const uint32_t a = sm + OFF_QB + b * 256 + (((c + g) & 7) * 8 + 2 * t) * 2;
                qf[c][0] = lds32(a); qf[c][1] = lds32(a + 128);
                acc[c][0] = acc[c][1] = acc[c][2] = acc[c][3] = 0.f;
            }
            m = -INFINITY; l = 0.f;
        };
        auto stats = [&](int b) {
#pragma unroll
            for (int o = 16; o; o >>= 1) l += __shfl_xor_sync(0xffffffffu, l, o);
            if (lane == 0) stsf2(sm + OFF_ML + b * 32 + warp * 8, m, l);
        };
        auto quad_sum = [&](float (&r)[4]) {
            float v[2][8];
#pragma unroll
            for (int c = 0; c < 8; c++) { v[0][c] = acc[c][0] + acc[(c + 7) & 7][1]; v[1][c] = acc[c][2] + acc[(c + 7) & 7][3]; }
#pragma unroll
            for (int c = 0; c < 4; c++) { v[0][c] += __shfl_xor_sync(0xffffffffu, v[0][c + 4], 2); v[1][c] += __shfl_xor_sync(0xffffffffu, v[1][c + 4], 2); }
            const int src = (lane & ~3) | ((lane + 3) & 3);
#pragma unroll
            for (int c = 0; c < 4; c++) r[c] = v[c >> 1][c & 1] + __shfl_sync(0xffffffffu, v[c >> 1][(c & 1) + 2], src);
        };
        auto factor = [&](int b, float& lse) {
            bar_sync(1, 128);
            const uint4 ml0 = lds128(sm + OFF_ML + b * 32), ml1 = lds128(sm + OFF_ML + b * 32 + 16);
            const float m0 = __uint_as_float(ml0.x), m1 = __uint_as_float(ml0.z), m2 = __uint_as_float(ml1.x), m3 = __uint_as_float(ml1.z);
            const float M = fmaxf(fmaxf(m0, m1), fmaxf(m2, m3));
            const float L = (ex2((m0 - M) * LOG2E) * __uint_as_float(ml0.y) + ex2((m1 - M) * LOG2E) * __uint_as_float(ml0.w))
                          + (ex2((m2 - M) * LOG2E) * __uint_as_float(ml1.y) + ex2((m3 - M) * LOG2E) * __uint_as_float(ml1.w));
            lse = M * LOG2E + lg2(L);
            return ex2((ldsf(sm + OFF_ML + b * 32 + warp * 8) - M) * LOG2E) * rcp(L);
        };
        auto publish = [&](uint32_t* dst, const float (&r)[4], float f) {
            const uint32_t wa = sm + OFF_S2 + warp * 640 + (t * 16 + (t >> 1) * 8 + g) * 4;
            const uint32_t ra = sm + OFF_S2 + ((tid >> 4 & 1) * 40 + (tid & 2) * 40 + (tid >> 5 & 1) * 16 + (tid & 1) * 8 + (tid >> 2 & 3) * 2) * 4;
#pragma unroll
            for (int c = 0; c < 4; c++) sts32(wa + (c >> 1) * 320 + (c & 1) * 32, __float_as_uint(r[c] * f));
            bar_sync(1, 128);
            const float2 r0 = ldsf2(ra), r1 = ldsf2(ra + 640), r2 = ldsf2(ra + 1280), r3 = ldsf2(ra + 1920);
            if (tid < 64) mail_put(dst, pack2((r0.x + r1.x) + (r2.x + r3.x), (r0.y + r1.y) + (r2.y + r3.y)));
        };
        float o0[4] = {0.f, 0.f, 0.f, 0.f};
        start(0);
        const bool diag = (t == (g >> 1));
        const uint32_t krow = sm + OFF_RING + (warp * 16 + rr + 8 * (i & 1)) * 256 + (i >> 1) * 128;
        const uint32_t vrow = sm + OFF_RING + (warp * 16 + rr + 8 * (i >> 1)) * 256 + (i & 1) * 128;
        uint32_t slot = 0, ph = 0;
        uint32_t a[8][4] = {}, b0[RUN], b1[RUN];
        auto release = [&]() {
            __syncwarp();
            if (lane == 0) mbar_arrive(bars + (B_EMPTY + slot) * 8 + ((a[0][0] | a[1][0] | a[2][0] | a[3][0] | a[4][0] | a[5][0] | a[6][0] | a[7][0]) & zero));
            if (++slot == RING) { slot = 0; ph ^= 1; }
        };
        auto load_v = [&]() {
            mbar_wait(bars + slot * 8, ph);
#pragma unroll
            for (int c = 0; c < 8; c++) ldsm4t(a[c], vrow + slot * CH + (((c + rr) & 7) << 4));
        };
#pragma unroll 1
        for (int run = 0;; run++) {
            float slo[RUN], shi[RUN], mx = -INFINITY;
#pragma unroll
            for (int u = 0; u < RUN; u++) {
                mbar_wait(bars + slot * 8, ph);
#pragma unroll
                for (int c = 0; c < 8; c++) ldsm4(a[c], krow + slot * CH + (((c + rr) & 7) << 4));
                release();
                float s0[4] = {0.f, 0.f, 0.f, 0.f}, s1[4] = {0.f, 0.f, 0.f, 0.f};
#pragma unroll
                for (int c = 0; c < 8; c += 2) { mma(s0, a[c], qf[c][0], qf[c][1]); mma(s1, a[c + 1], qf[c + 1][0], qf[c + 1][1]); }
                slo[u] = diag ? bfround(bfround((g & 1) ? s0[1] + s1[1] : s0[0] + s1[0]) * SCALE) : -INFINITY;
                shi[u] = diag ? bfround(bfround((g & 1) ? s0[3] + s1[3] : s0[2] + s1[2]) * SCALE) : -INFINITY;
                mx = fmaxf(mx, fmaxf(slo[u], shi[u]));
            }
            int key = __float_as_int(mx);
            key ^= (key >> 31) & 0x7fffffff;
            key = __reduce_max_sync(0xffffffffu, key);
            key ^= (key >> 31) & 0x7fffffff;
            const float mn = fmaxf(m, __int_as_float(key));
            const float alpha = ex2((m - mn) * LOG2E);
            m = mn;
            l *= alpha;
#pragma unroll
            for (int u = 0; u < RUN; u++) {
                const float plo = ex2((slo[u] - mn) * LOG2E), phi = ex2((shi[u] - mn) * LOG2E);
                l += plo + phi;
                b0[u] = (g & 1) ? pack2(0.f, plo) : pack2(plo, 0.f);
                b1[u] = (g & 1) ? pack2(0.f, phi) : pack2(phi, 0.f);
            }
#pragma unroll
            for (int c = 0; c < 8; c++) { acc[c][0] *= alpha; acc[c][1] *= alpha; acc[c][2] *= alpha; acc[c][3] *= alpha; }
            if (run == NTILE / RUN - 1) break;
#pragma unroll
            for (int u = 0; u < RUN; u++) {
                load_v();
                release();
#pragma unroll
                for (int c = 0; c < 8; c++) mma(acc[c], a[c], b0[u], b1[u]);
            }
            if (run == NTILE / RUN / 2 - 1) { stats(0); quad_sum(o0); start(1); }
            if (run == NTILE / RUN - 2) {
                float lse;
                mbar_wait(bars + B_S2 * 8, 0);
                publish((uint32_t*)g_e5[cta] + tid, o0, factor(0, lse));
                if (tid == 96) mail_put((float*)g_l5[h] + j, lse);
            }
        }
        {
            float lse;
            stats(1);
            const float f = factor(1, lse);
            uint32_t* const e5own = pin((uint32_t*)g_e5[cta] + 64 + tid);
            float* const l5own = pin((float*)g_l5[h] + 4 + j);
#pragma unroll
            for (int u = 0; u < RUN; u++) {
                load_v();
                if (++slot == RING) { slot = 0; ph ^= 1; }
                if (u == RUN - 1 && tid == 96) mail_put(l5own, lse);
#pragma unroll
                for (int c = 0; c < 8; c++) mma(acc[c], a[c], b0[u], b1[u]);
            }
            if (tid == 0) TS(5);
            quad_sum(o0);
            publish(e5own, o0, f);
        }
        if (tid == 0) TS(6);
        {
            uint32_t x[4][4][4];
            float d[4][4];
            bar_sync(4, 256 + 128);
#pragma unroll
            for (int k = 0; k < 16; k++) ldsm4(x[k >> 2][k & 3], sm + OFF_CA + ((k >> 2) * 2 + (lane & 1)) * VROW + (k & 3) * 64 + (i & 1) * 32 + (i >> 1) * 16);
            const uint32_t wa = sm + OFF_S1 + lane * 64 + ((warp ^ (rr >> 1)) << 4);
            __nv_bfloat16* const outp = pin(out + (g & 1) * 1024 + (cta & 15) * 32 + warp * 8 + t * 2);
            mbar_wait(bars + (B_WO + 4) * 8, 0);
            uint32_t it = 0;
            while (true) {
                bool ok = true;
#pragma unroll
                for (int k = 0; k < 4; k++) d[k][0] = d[k][1] = d[k][2] = d[k][3] = 0.f;
#pragma unroll
                for (int q = 0; q < 5; q++) {
                    if (q < 4) ok &= box_load(a[(q & 1) * 4], a[(q & 1) * 4 + 1], a[(q & 1) * 4 + 2], a[(q & 1) * 4 + 3], bars + (B_WO + 4 + q) * 8, wa + q * 8192);
#pragma unroll
                    for (int k = 0; k < (q ? 8 : 0); k++) {
                        const uint32_t (&u)[4] = a[(~q & 1) * 4 + (k >> 1)];
                        mma(d[k & 3], x[k >> 1][q - 1], u[(k & 1) * 2], u[(k & 1) * 2 + 1]);
                    }
                }
                asm volatile("{\n.reg .pred p;\nsetp.ne.u32 p, %0, 0;\n@p exit;\n}" ::"r"((uint32_t)(ok && lane >= 8)) : "memory");
                if (ok) break;
                if (++it > SPIN_MAX) __trap();
            }
            out_add(outp, (d[0][0] + d[1][2]) + (d[2][0] + d[3][2]), (d[0][1] + d[1][3]) + (d[2][1] + d[3][3]));
            if (tid == 0) TS(15);
        }
    } else {
        const int st = tid - 128, w = warp - 4;
        const int g = lane >> 2, t = lane & 3, i = lane >> 3, rr = lane & 7;
        if (t == 0) {
#pragma unroll
            for (int k = 0; k < 4; k++) ll_store2(&g_e1[k >> 1][cta][w * 16 + g + (k & 1) * 8], 0.f, 0.f, 0u);
        }
        if (st < 64) {
            const int which = st >> 5, b = (st >> 4) & 1, c = st & 15;
            const uint4 v = __ldg((const uint4*)((which ? xA : xB) + b * 512 + j * 128) + c);
            sts128(sm + OFF_XB + (which * 2 + b) * VROW + c * 16, v);
        }
        bar_sync(0, NTHREADS);
        const uint32_t tag = lds32(sm + OFF_TAG);
        float c[4];
#pragma unroll 1
        for (int which = 0; which < 2; which++) {
            matvecT(c, sm + OFF_S0 + which * 2 * CH, sm + OFF_XB + which * 2 * VROW, 2, bars + (B_WQB + which * 2) * 8, w, lane);
            if (t == 0) {
                ll_store2(&g_e1[which][cta][w * 16 + g], c[0], c[1], tag);
                ll_store2(&g_e1[which][cta][w * 16 + g + 8], c[2], c[3], tag);
            }
        }
        __syncwarp();
        if (lane == 0) mbar_arrive(bars + B_FREE * 8);
        if (st == 0) TS(8);
        if (st < 128) {
            float q0, q1;
            sleep_ns(POLL_DELAY);
            ll_gather4(&g_e1[1][h * 4][st], tag, q0, q1);
            sts16(sm + OFF_QA + st * 2, f2bf(q0)); sts16(sm + OFF_QA + VROW + st * 2, f2bf(q1));
        }
        bar_sync(2, 256);
        if (st == 0) TS(9);
        {
            const int row = w * 16 + rr + 8 * (i & 1);
            const uint32_t a0 = sm + OFF_S2 + (row >> 6) * CH + (row & 63) * 128;
            const uint32_t va = sm + OFF_QA + g * VROW + t * 4;
            float d[4] = {0.f, 0.f, 0.f, 0.f};
            c[0] = c[1] = c[2] = c[3] = 0.f;
            mbar_wait(bars + (B_WUK + (w >> 2)) * 8, 0);
#pragma unroll
            for (int ks = 0; ks < 8; ks++) {
                const int chunk = 2 * ks + (i >> 1);
                uint32_t a[4];
                ldsm4(a, a0 + (chunk >> 3) * 8192 + (((chunk & 7) ^ rr) << 4));
                const uint32_t b0 = (g < 2) ? lds32(va + ks * 32) : 0u, b1 = (g < 2) ? lds32(va + ks * 32 + 16) : 0u;
                if (ks & 1) mma(d, a, b0, b1); else mma(c, a, b0, b1);
            }
            if (t == 0) {
                const uint32_t qs = sm + OFF_QS + (w * 16 + g) * 2;
                sts16(qs, f2bf(c[0] + d[0])); sts16(qs + VROW, f2bf(c[1] + d[1]));
                sts16(qs + 16, f2bf(c[2] + d[2])); sts16(qs + VROW + 16, f2bf(c[3] + d[3]));
            }
            bar_sync(2, 256);
            if (w == 0) {
                const int b = lane >> 4, cc = lane & 15;
                g_qabs[(b * 32 + h) * 64 + ((j * 16 + cc) ^ (h & 7))] = lds128(sm + OFF_QS + b * VROW + cc * 16);
                __syncwarp();
                if (lane == 0) {
                    cnt_rendezvous(&g_cnt[0], tag * 128u, 18);
                    TS(10);
                    mbar_expect(bars + B_GATH * 8, 2 * CH);
                    bulk1d_n(sm + OFF_S2, g_qabs + (cta >> 6) * 2048, 2 * CH, bars + B_GATH * 8);
                }
                __syncwarp();
            }
        }
        mbar_wait(bars + B_GATH * 8, 0);
        if (st == 0) TS(11);
        {
            const int mt = w & 1, kg = w >> 1;
            const uint32_t qa = sm + OFF_S2 + (mt * 16 + rr + 8 * (i & 1)) * 1024;
            const uint32_t ka = sm + OFF_S0 + kg * CH + (rr + 8 * (i >> 1)) * 128;
            float s0[4] = {0.f, 0.f, 0.f, 0.f}, s1[4] = {0.f, 0.f, 0.f, 0.f};
            mbar_wait(bars + (B_CKV + kg) * 8, 0);
#pragma unroll 2
            for (int gq = 0; gq < 8; gq++) {
#pragma unroll
                for (int k4 = 0; k4 < 4; k4++) {
                    uint32_t a[4], b[4];
                    ldsm4(a, qa + gq * 128 + (((2 * k4 + (i >> 1)) ^ rr) << 4));
                    ldsm4(b, ka + gq * 2048 + (((2 * k4 + (i & 1)) ^ rr) << 4));
                    mma(s0, a, b[0], b[1]);
                    mma(s1, a, b[2], b[3]);
                }
            }
            const uint32_t sa = sm + OFF_SC + ((mt * 16 + g) * 68 + kg * 16 + 2 * t) * 4;
            stsf2(sa, s0[0], s0[1]); stsf2(sa + 32, s1[0], s1[1]);
            stsf2(sa + 8 * 68 * 4, s0[2], s0[3]); stsf2(sa + 8 * 68 * 4 + 32, s1[2], s1[3]);
        }
        bar_sync(2, 256);
        {
            const int head = w * 4 + i;
            const uint32_t sa = sm + OFF_SC + (head * 68 + rr * 8) * 4;
            const uint4 u0 = lds128(sa), u1 = lds128(sa + 16);
            float s[8] = {__uint_as_float(u0.x), __uint_as_float(u0.y), __uint_as_float(u0.z), __uint_as_float(u0.w),
                          __uint_as_float(u1.x), __uint_as_float(u1.y), __uint_as_float(u1.z), __uint_as_float(u1.w)};
            float mx = s[0];
#pragma unroll
            for (int k = 1; k < 8; k++) mx = fmaxf(mx, s[k]);
#pragma unroll
            for (int o = 1; o < 8; o <<= 1) mx = fmaxf(mx, __shfl_xor_sync(0xffffffffu, mx, o));
            float sum = 0.f;
#pragma unroll
            for (int k = 0; k < 8; k++) { s[k] = ex2((s[k] - mx) * (SCALE * LOG2E)); sum += s[k]; }
#pragma unroll
            for (int o = 1; o < 8; o <<= 1) sum += __shfl_xor_sync(0xffffffffu, sum, o);
            const float inv = __fdividef(1.f, sum);
            uint4 p;
            p.x = pack2(s[0] * inv, s[1] * inv); p.y = pack2(s[2] * inv, s[3] * inv);
            p.z = pack2(s[4] * inv, s[5] * inv); p.w = pack2(s[6] * inv, s[7] * inv);
            sts128(sm + OFF_P + head * 128 + ((rr ^ (head & 7)) << 4), p);
            if (rr == 0) ((float*)g_lse)[head * 128 + cta] = mx * (SCALE * LOG2E) + lg2(sum);
        }
        bar_sync(2, 256);
        {
            float o[2][8][4];
#pragma unroll
            for (int mt = 0; mt < 2; mt++)
#pragma unroll
                for (int n = 0; n < 8; n++) { o[mt][n][0] = o[mt][n][1] = o[mt][n][2] = o[mt][n][3] = 0.f; }
            const uint32_t pa = sm + OFF_P + (rr + 8 * (i & 1)) * 128;
            const uint32_t va = sm + OFF_S0 + w * 2048 + (rr + 8 * (i & 1)) * 128;
#pragma unroll 1
            for (int kq = 0; kq < 4; kq++) {
                uint32_t a0[4], a1[4];
                ldsm4(a0, pa + (((2 * kq + (i >> 1)) ^ rr) << 4));
                ldsm4(a1, pa + 2048 + (((2 * kq + (i >> 1)) ^ rr) << 4));
#pragma unroll
                for (int n = 0; n < 8; n += 2) {
                    uint32_t b[4];
                    ldsm4t(b, va + kq * CH + (((n + (i >> 1)) ^ rr) << 4));
                    mma(o[0][n], a0, b[0], b[1]); mma(o[1][n], a1, b[0], b[1]);
                    mma(o[0][n + 1], a0, b[2], b[3]); mma(o[1][n + 1], a1, b[2], b[3]);
                }
            }
#pragma unroll
            for (int mt = 0; mt < 2; mt++)
#pragma unroll
                for (int hf = 0; hf < 2; hf++) {
                    const uint32_t dst = sm + OFF_S2 + (mt * 16 + hf * 8 + g) * 1024 + w * 128 + t * 16;
#pragma unroll
                    for (int nb = 0; nb < 2; nb++) {
                        uint4 v;
                        v.x = pack2(o[mt][nb * 4 + 0][hf * 2], o[mt][nb * 4 + 0][hf * 2 + 1]);
                        v.y = pack2(o[mt][nb * 4 + 1][hf * 2], o[mt][nb * 4 + 1][hf * 2 + 1]);
                        v.z = pack2(o[mt][nb * 4 + 2][hf * 2], o[mt][nb * 4 + 2][hf * 2 + 1]);
                        v.w = pack2(o[mt][nb * 4 + 3][hf * 2], o[mt][nb * 4 + 3][hf * 2 + 1]);
                        sts128(dst + nb * 64, v);
                    }
                }
            asm volatile("fence.proxy.async.shared::cta;" ::: "memory");
            __syncwarp();
            if (lane == 0) mbar_arrive(bars + B_FREE * 8);
            if (st < 98) *(st < 64 ? &g_e4[cta][st] : st < 96 ? &g_e5[cta][st - 64] : &g_l5[h][j * 2 + st - 96]) = make_uint4(EMPTY, EMPTY, EMPTY, EMPTY);
            else if (st < 100) ((uint4*)out)[cta * 2 + st - 98] = make_uint4(0u, 0u, 0u, 0u);
        }
        bar_sync(2, 256);
        if (st == 0) {
            TS(12);
#pragma unroll 1
            for (int k = 0; k < ST_SPLIT; k++) {
                asm volatile("cp.async.bulk.tensor.3d.global.shared::cta.bulk_group [%0, {%2,%3,%4}], [%1];"
                             ::"l"(&maps.ctxp), "r"(sm + OFF_S2 + k * (2 * CH / ST_SPLIT)), "r"(0), "r"(cta), "r"(k * (128 / ST_SPLIT)) : "memory");
                if (k + 1 < ST_SPLIT) __nanosleep(ST_GAP);
            }
            asm volatile("cp.async.bulk.commit_group;" ::: "memory");
            asm volatile("cp.async.bulk.wait_group 0;" ::: "memory");
            cnt_rendezvous(&g_cnt[1], tag * 128u, 20);
            TS(13);
            mbar_expect(bars + B_GATH * 8, 2 * CH + 512);
            bulk1d_n(sm + OFF_LSE, g_lse + h * 32, 512, bars + B_GATH * 8);
#pragma unroll 1
            for (int k = 0; k < G_SPLIT; k++) {
                bulk1d_n(sm + OFF_S2 + k * (2 * CH / G_SPLIT), g_ctxp + cta * 2048 + k * (2048 / G_SPLIT), 2 * CH / G_SPLIT, bars + B_GATH * 8);
                if (k + 1 < G_SPLIT) __nanosleep(G_GAP);
            }
        }
        __syncwarp();
        {
            mbar_wait(bars + B_GATH * 8, 1);
            if (st == 0) TS(22);
            uint4 v[8];
#pragma unroll
            for (int k = 0; k < 8; k++) v[k] = lds128(sm + OFF_S2 + (k * 256 + st) * 16);
            float ls[4];
#pragma unroll
            for (int k = 0; k < 4; k++) ls[k] = ldsf(sm + OFF_LSE + (k * 32 + lane) * 4);
            float m0 = fmaxf(ls[0], ls[1]), m1 = fmaxf(ls[2], ls[3]);
#pragma unroll
            for (int o = 16; o; o >>= 1) { m0 = fmaxf(m0, __shfl_xor_sync(0xffffffffu, m0, o)); m1 = fmaxf(m1, __shfl_xor_sync(0xffffffffu, m1, o)); }
            ls[0] = ex2(ls[0] - m0); ls[1] = ex2(ls[1] - m0); ls[2] = ex2(ls[2] - m1); ls[3] = ex2(ls[3] - m1);
            float z0 = ls[0] + ls[1], z1 = ls[2] + ls[3];
#pragma unroll
            for (int o = 16; o; o >>= 1) { z0 += __shfl_xor_sync(0xffffffffu, z0, o); z1 += __shfl_xor_sync(0xffffffffu, z1, o); }
            z0 = __fdividef(1.f, z0); z1 = __fdividef(1.f, z1);
            ls[0] *= z0; ls[1] *= z0; ls[2] *= z1; ls[3] *= z1;
            float a[2][8];
#pragma unroll
            for (int e = 0; e < 8; e++) a[0][e] = a[1][e] = 0.f;
            const int rg = st >> 4;
#pragma unroll
            for (int k = 0; k < 8; k++) {
                const float wt = __shfl_sync(0xffffffffu, ls[k >> 1], rg + 16 * (k & 1));
                const uint32_t u[4] = {v[k].x, v[k].y, v[k].z, v[k].w};
#pragma unroll
                for (int e = 0; e < 4; e++) {
                    a[k >> 2][2 * e] += wt * __uint_as_float(u[e] << 16);
                    a[k >> 2][2 * e + 1] += wt * __uint_as_float(u[e] & 0xffff0000u);
                }
            }
            const int b = lane >> 4, u16 = lane & 15;
            const uint32_t ra = sm + OFF_SC + (w * 256 + b * 128 + (u16 >> 3) * 64 + ((u16 >> 2) & 1) * 32 + (u16 & 3) * 2) * 4;
#pragma unroll
            for (int e = 0; e < 8; e += 2) {
                const float k0 = b ? a[1][e] : a[0][e], k1 = b ? a[1][e + 1] : a[0][e + 1];
                const float s0 = b ? a[0][e] : a[1][e], s1 = b ? a[0][e + 1] : a[1][e + 1];
                stsf2(ra + (e >> 1) * 32, k0 + __shfl_xor_sync(0xffffffffu, s0, 16), k1 + __shfl_xor_sync(0xffffffffu, s1, 16));
            }
            bar_sync(2, 256);
            if (st == 0) mbar_arrive(bars + B_S2 * 8);
            float s = 0.f;
#pragma unroll
            for (int k = 0; k < 8; k++) s += ldsf(sm + OFF_SC + (k * 256 + st) * 4);
            const float hi = bfround(s);
            const uint32_t ca = sm + OFF_CC + (st >> 7) * VROW + (st & 127) * 2;
            sts16(ca, f2bf(hi)); sts16(ca + 2 * VROW, f2bf(s - hi));
            bar_sync(2, 256);
        }
        matvecT(c, sm + OFF_S1, sm + OFF_CC, 4, bars + B_WUV * 8, w, lane);
#pragma unroll
        for (int k = 0; k < 4; k++) c[k] += __shfl_down_sync(0xffffffffu, c[k], 1);
        if (t == 0) {
            float* const e = (float*)g_e4[cta] + w * 16 + g;
            mail_put(e, c[0]); mail_put(e + 128, c[1]); mail_put(e + 8, c[2]); mail_put(e + 136, c[3]);
        }
        __syncwarp();
        if (lane == 0) mbar_arrive(bars + B_FREE * 8);
        if (st == 0) TS(23);
        {
            const uint4* const pv = &g_e4[(cta & ~15) + (w >> 1) * 4][(w & 1) * 32 + lane];
            uint4 x[4];
            uint32_t it = 0;
            sleep_ns(POLL_DELAY2);
            while (true) {
#pragma unroll
                for (int k = 0; k < 4; k++) { x[k].x = x[k].y = x[k].z = x[k].w = 0u; mail_get(x[k], pv + k * 64); }
                if (!__any_sync(0xffffffffu, mail_missing(x[0]) | mail_missing(x[1]) | mail_missing(x[2]) | mail_missing(x[3]))) break;
                if (++it > SPIN_MAX) __trap();
                __nanosleep(BACKOFF);
            }
#define SUM4(e) ((__uint_as_float(x[0].e) + __uint_as_float(x[1].e)) + (__uint_as_float(x[2].e) + __uint_as_float(x[3].e)))
            sts64(sm + OFF_CA + w * VROW + lane * 8, pack2(SUM4(x), SUM4(y)), pack2(SUM4(z), SUM4(w)));
#undef SUM4
        }
        if (st == 0) TS(14);
        bar_sync(4, 256 + 128);
        {
            const uint32_t a0 = sm + OFF_S0 + w * 1024 + (rr + 8 * (i >> 1)) * 64 + (((i & 1) ^ (rr >> 1)) << 4);
            const uint4* const pv = pin(&g_e5[(cta & ~15) + (w >> 1) * 4 + (g & 3)][(g >> 2) * 16 + (w & 1) * 8 + t]);
            const uint32_t* const pl = pin((const uint32_t*)g_l5[(h & ~3) + (w >> 1)] + rr);
            const uint32_t wa = sm + OFF_SC + ((w * 2 + (t & 1)) * 80 + (t >> 1) * 40 + g) * 4;
            __nv_bfloat16* const outp = pin(out + (lane >> 4) * 1024 + 512 + (cta & 15) * 32 + (lane & 15) * 2);
            uint32_t a[4][2][4], xl = 0u, it = 0;
            uint4 x[2] = {make_uint4(0u, 0u, 0u, 0u), make_uint4(0u, 0u, 0u, 0u)};
            while (true) {
                if (lane < 8) asm volatile("atom.relaxed.gpu.global.or.b32 %0, [%1], 0;" : "=r"(xl) : "l"(pl) : "memory");
                if (!__any_sync(0xffffffffu, xl == EMPTY)) break;
                if (++it > SPIN_MAX) __trap();
            }
            if (st == 0) TS(25);
            mail_get(x[0], pv); mail_get(x[1], pv + 4);
            float w0 = __uint_as_float(xl), w1 = fmaxf(w0, __shfl_xor_sync(0xffffffffu, w0, 1));
            w0 = ex2(w0 - fmaxf(w1, __shfl_xor_sync(0xffffffffu, w1, 2)));
            w1 = w0 + __shfl_xor_sync(0xffffffffu, w0, 1);
            w0 *= rcp(w1 + __shfl_xor_sync(0xffffffffu, w1, 2));
            w1 = __shfl_sync(0xffffffffu, w0, 2 * t + 1);
            w0 = __shfl_sync(0xffffffffu, w0, 2 * t);
#pragma unroll
            for (int q = 0; q < 4; q++) {
                mbar_wait(bars + (B_WO + q) * 8, 0);
                ldsm4t(a[q][0], a0 + q * 8192);
                ldsm4t(a[q][1], (a0 ^ 32) + q * 8192);
            }
            if (st == 0) TS(26);
            while (true) {
                const bool n0 = mail_missing(x[0]), n1 = mail_missing(x[1]);
                if (!__any_sync(0xffffffffu, n0 | n1)) break;
                mail_get(x[0], pv, n0); mail_get(x[1], pv + 4, n1);
                if (++it > SPIN_MAX) __trap();
            }
            if (st == 0) TS(16);
            float d[2][2][4];
#pragma unroll
            for (int k = 0; k < 4; k++) {
                float (&dk)[4] = d[k >> 1][k & 1];
                dk[0] = dk[1] = dk[2] = dk[3] = 0.f;
                mma(dk, a[k >> 1][k & 1], x[k >> 1].x, x[k >> 1].y);
            }
#pragma unroll
            for (int k = 0; k < 4; k++) mma(d[k >> 1][k & 1], a[2 + (k >> 1)][k & 1], x[k >> 1].z, x[k >> 1].w);
#pragma unroll
            for (int k = 0; k < 4; k++) {
                const int e = (k & 1) * 2;
                sts32(wa + k * 32, __float_as_uint(w0 * (d[0][k >> 1][e] + d[1][k >> 1][e]) + w1 * (d[0][k >> 1][e + 1] + d[1][k >> 1][e + 1])));
            }
            if (st == 0) TS(17);
            if (w == 0) {
                bar_sync(5, 256);
                const uint32_t ra = sm + OFF_SC + ((lane >> 4) * 40 + (lane & 15) * 2) * 4;
                float2 r[16];
#pragma unroll
                for (int k = 0; k < 16; k++) r[k] = ldsf2(ra + k * 320);
#pragma unroll
                for (int o = 1; o < 16; o <<= 1)
#pragma unroll
                    for (int k = 0; k < 16; k += 2 * o) { r[k].x += r[k + o].x; r[k].y += r[k + o].y; }
                out_add(outp, r[0].x, r[0].y);
            } else {
                bar_arrive(5, 256);
            }
        }
    }
}

typedef CUresult (*EncodeFn)(CUtensorMap*, CUtensorMapDataType, cuuint32_t, void*, const cuuint64_t*, const cuuint64_t*,
                             const cuuint32_t*, const cuuint32_t*, CUtensorMapInterleave, CUtensorMapSwizzle,
                             CUtensorMapL2promotion, CUtensorMapFloatOOBfill);

void make_map(EncodeFn enc, CUtensorMap* m, void* p, unsigned rows, unsigned cols, unsigned br, unsigned bg) {
    cuuint64_t gd[3] = {64, rows, cols / 64};
    cuuint64_t gs[2] = {(cuuint64_t)cols * 2, 128};
    cuuint32_t bx[3] = {64, br, bg};
    cuuint32_t es[3] = {1, 1, 1};
    enc(m, CU_TENSOR_MAP_DATA_TYPE_BFLOAT16, 3, p, gd, gs, bx, es, CU_TENSOR_MAP_INTERLEAVE_NONE,
        CU_TENSOR_MAP_SWIZZLE_128B, CU_TENSOR_MAP_L2_PROMOTION_L2_128B, CU_TENSOR_MAP_FLOAT_OOB_FILL_NONE);
}

}

extern "C" void kernel_launch(void* const* d_in, const int* in_sizes, int n_in, void* d_out, int out_size) {
    static EncodeFn enc = nullptr;
    if (!enc) {
        void* fn = nullptr;
        cudaDriverEntryPointQueryResult qr;
        cudaGetDriverEntryPoint("cuTensorMapEncodeTiled", &fn, cudaEnableDefault, &qr);
        enc = (EncodeFn)fn;
        cudaFuncSetAttribute(fused_decode_kernel, cudaFuncAttributeMaxDynamicSharedMemorySize, SMEM_BYTES);
    }
    Maps maps;
    make_map(enc, &maps.wqB, d_in[9], 512, 4096, 64, 2);
    make_map(enc, &maps.wqA, d_in[2], 512, 4096, 64, 2);
    make_map(enc, &maps.wuk, d_in[3], 512, 4096, 64, 2);
    make_map(enc, &maps.wuv, d_in[4], 512, 4096, 64, 2);
    for (int k = 0; k < 2; k++) {
        cuuint64_t gd[3] = {512, 128, 32};
        cuuint64_t gs[2] = {1024, 131072};
        cuuint32_t bx[3] = {32, 32, 4};
        cuuint32_t es[3] = {1, 1, 1};
        enc(&maps.woB + k, CU_TENSOR_MAP_DATA_TYPE_BFLOAT16, 3, d_in[k ? 5 : 10], gd, gs, bx, es, CU_TENSOR_MAP_INTERLEAVE_NONE,
            CU_TENSOR_MAP_SWIZZLE_64B, CU_TENSOR_MAP_L2_PROMOTION_L2_256B, CU_TENSOR_MAP_FLOAT_OOB_FILL_NONE);
    }
    make_map(enc, &maps.ckv, d_in[1], 8192, 512, 16, 8);
    {
        void* p = nullptr;
        cudaGetSymbolAddress(&p, g_ctxp);
        cuuint64_t gd[3] = {128, 128, 128};
        cuuint64_t gs[2] = {256, 32768};
        cuuint32_t bx[3] = {128, 1, 128 / ST_SPLIT};
        cuuint32_t es[3] = {1, 1, 1};
        enc(&maps.ctxp, CU_TENSOR_MAP_DATA_TYPE_BFLOAT16, 3, p, gd, gs, bx, es, CU_TENSOR_MAP_INTERLEAVE_NONE,
            CU_TENSOR_MAP_SWIZZLE_NONE, CU_TENSOR_MAP_L2_PROMOTION_NONE, CU_TENSOR_MAP_FLOAT_OOB_FILL_NONE);
    }
    fused_decode_kernel<<<NCTA, NTHREADS, SMEM_BYTES>>>((const char*)d_in[9], maps, (const char*)d_in[7], (const char*)d_in[8],
                                                         (const __nv_bfloat16*)d_in[0], (const __nv_bfloat16*)d_in[6],
                                                         (__nv_bfloat16*)d_out, 0u);
}
```

```cpp
#include <cuda_runtime.h>
#include <cuda.h>
#include <cuda_bf16.h>
#include <stdint.h>

#define RING 7
#define WIN 4
#define WHI 5
#define THETA 64
#define END_V 40
#define GATE_W 192
#define OP_CLK16 158
#define BOX_FIRST 550
#define BOX_CLK 600
#define TAIL_LO 4
#define TAIL_HI 7
#define POLL_DELAY 2500
#define POLL_DELAY2 3000
#define ST_SPLIT 32
#define ST_GAP 200
#define G_SPLIT 8
#define G_GAP 250
#define BACKOFF 200
#define BACKOFF2 100

namespace {

constexpr int NCTA = 128;
constexpr int NTHREADS = 448;
constexpr uint32_t CH = 16384;
constexpr int NTILE = 32;
constexpr int RUN = 4;

constexpr uint32_t OFF_RING = 0;
constexpr uint32_t OFF_S0 = RING * CH;
constexpr uint32_t OFF_S1 = OFF_S0 + 2 * CH;
constexpr uint32_t OFF_S2 = OFF_S1 + 2 * CH;
constexpr uint32_t OFF_P = OFF_S2 + 2 * CH;
constexpr uint32_t OFF_SC = OFF_P + 4096;
constexpr uint32_t VROW = 272;
constexpr uint32_t OFF_XB = OFF_SC + 8704;
constexpr uint32_t OFF_XA = OFF_XB + 2 * VROW;
constexpr uint32_t OFF_QA = OFF_XA + 2 * VROW;
constexpr uint32_t OFF_QS = OFF_QA + 2 * VROW;
constexpr uint32_t OFF_CC = OFF_QS + 2 * VROW;
constexpr uint32_t OFF_CA = OFF_P;
constexpr uint32_t OFF_QB = OFF_CC + 4 * VROW;
constexpr uint32_t OFF_LSE = OFF_QB + 512;
constexpr uint32_t OFF_ML = OFF_LSE + 512;
constexpr uint32_t OFF_TAG = OFF_ML + 64;
constexpr uint32_t OFF_NOW = OFF_TAG + 4;
constexpr uint32_t OFF_WIN = OFF_TAG + 8;
constexpr uint32_t OFF_BAR = OFF_TAG + 16;
constexpr int B_EMPTY = RING;
constexpr int B_WQB = 2 * RING;
constexpr int B_WQA = B_WQB + 2;
constexpr int B_WUK = B_WQA + 2;
constexpr int B_WUV = B_WUK + 2;
constexpr int B_CKV = B_WUV + 2;
constexpr int B_WO = B_CKV + 4;
constexpr int B_FREE = B_WO + 8;
constexpr int B_GATH = B_FREE + 1;
constexpr int B_S2 = B_GATH + 1;
constexpr int NBAR = B_S2 + 1;
constexpr uint32_t TS_OFF = OFF_BAR + NBAR * 8;
constexpr uint32_t SMEM_USED = TS_OFF;
constexpr uint32_t SMEM_BYTES = SMEM_USED + 1024;
static_assert(SMEM_BYTES <= 232448, "smem");
static_assert(RING >= RUN && RING >= WHI && WHI >= WIN && WHI >= 4 && WIN >= 3 && WIN <= 6 && TAIL_HI >= 4, "windows");

constexpr float LOG2E = 1.4426950408889634f;
constexpr float SCALE = 0.08838834764831845f;
#define SPIN_LOG 22
constexpr uint32_t SPIN_MAX = 1u << SPIN_LOG;

struct Maps { CUtensorMap wqB, wqA, wuk, wuv, woB, woA, ckv, ctxp; };

__device__ __align__(256) unsigned g_cnt[32];
__device__ __align__(256) ulonglong2 g_e1[2][NCTA][128];
__device__ __align__(256) uint4 g_qabs[2 * 32 * 64];
__device__ __align__(256) uint4 g_ctxp[NCTA * 128 * 16];
__device__ __align__(256) float4 g_lse[32 * 32];
__device__ __align__(256) uint4 g_e4[NCTA][64];
__device__ __align__(256) uint4 g_e5[NCTA][32];
__device__ __align__(256) uint4 g_l5[32][8];
constexpr uint32_t EMPTY = 0xffffffffu;

#define TS(k) do {} while (0)

__device__ __forceinline__ void mbar_init(uint32_t b, int c) { asm volatile("mbarrier.init.shared::cta.b64 [%0], %1;" ::"r"(b), "r"(c) : "memory"); }
__device__ __forceinline__ void mbar_expect(uint32_t b, uint32_t bytes) { asm volatile("mbarrier.arrive.expect_tx.shared::cta.b64 _, [%0], %1;" ::"r"(b), "r"(bytes) : "memory"); }
__device__ __forceinline__ void mbar_arrive(uint32_t b) { asm volatile("mbarrier.arrive.shared::cta.b64 _, [%0];" ::"r"(b) : "memory"); }
__device__ __forceinline__ void mbar_wait(uint32_t b, uint32_t ph) {
    asm volatile("{\n.reg .pred p;\n.reg .u32 n;\nmov.u32 n, 0;\n"
                 "W:\nmbarrier.try_wait.parity.shared::cta.b64 p, [%0], %1;\n@p bra D;\n"
                 "add.u32 n, n, 1;\nsetp.le.u32 p, n, %2;\n@p bra W;\ntrap;\nD:\n}" ::"r"(b), "r"(ph), "n"(SPIN_MAX) : "memory");
}
__device__ __forceinline__ uint32_t mbar_test(uint32_t b, uint32_t ph) {
    uint32_t ok;
    asm volatile("{\n.reg .pred p;\nmbarrier.test_wait.parity.shared::cta.b64 p, [%1], %2;\nselp.u32 %0, 1, 0, p;\n}" : "=r"(ok) : "r"(b), "r"(ph) : "memory");
    return ok;
}
__device__ __forceinline__ void bulk1d(uint32_t dst, const void* src, uint32_t bar, uint64_t pol) {
    asm volatile("cp.async.bulk.shared::cluster.global.mbarrier::complete_tx::bytes.L2::cache_hint [%0], [%1], %2, [%3], %4;"
                 ::"r"(dst), "l"(src), "n"(CH), "r"(bar), "l"(pol) : "memory");
}
__device__ __forceinline__ void bulk1d_n(uint32_t dst, const void* src, uint32_t bytes, uint32_t bar) {
    asm volatile("cp.async.bulk.shared::cluster.global.mbarrier::complete_tx::bytes [%0], [%1], %2, [%3];"
                 ::"r"(dst), "l"(src), "r"(bytes), "r"(bar) : "memory");
}
__device__ __forceinline__ void tma3d(uint32_t dst, const CUtensorMap* map, int c1, int c2, uint32_t bar, uint64_t pol, int c0 = 0) {
    asm volatile("cp.async.bulk.tensor.3d.shared::cluster.global.mbarrier::complete_tx::bytes.L2::cache_hint [%0], [%1, {%3,%4,%5}], [%2], %6;"
                 ::"r"(dst), "l"(map), "r"(bar), "r"(c0), "r"(c1), "r"(c2), "l"(pol) : "memory");
}
__device__ __forceinline__ void bar_sync(int id, int n) { asm volatile("barrier.cta.sync %0, %1;" ::"r"(id), "r"(n) : "memory"); }
__device__ __forceinline__ void bar_arrive(int id, int n) { asm volatile("barrier.cta.arrive %0, %1;" ::"r"(id), "r"(n) : "memory"); }
__device__ __forceinline__ void ldsm4(uint32_t (&r)[4], uint32_t a) {
    asm volatile("ldmatrix.sync.aligned.m8n8.x4.shared.b16 {%0,%1,%2,%3}, [%4];" : "=r"(r[0]), "=r"(r[1]), "=r"(r[2]), "=r"(r[3]) : "r"(a) : "memory");
}
__device__ __forceinline__ void ldsm4t(uint32_t (&r)[4], uint32_t a) {
    asm volatile("ldmatrix.sync.aligned.m8n8.x4.trans.shared.b16 {%0,%1,%2,%3}, [%4];" : "=r"(r[0]), "=r"(r[1]), "=r"(r[2]), "=r"(r[3]) : "r"(a) : "memory");
}
__device__ __forceinline__ bool box_load(uint32_t (&r)[4], uint32_t (&s)[4], uint32_t (&u)[4], uint32_t (&v)[4], uint32_t bar, uint32_t a) {
    uint32_t ok;
    asm volatile("{\n.reg .pred p;\nmbarrier.try_wait.parity.shared::cta.b64 p, [%17], 0;\n"
                 "@p ldmatrix.sync.aligned.m8n8.x4.trans.shared.b16 {%0,%1,%2,%3}, [%18];\n"
                 "@p ldmatrix.sync.aligned.m8n8.x4.trans.shared.b16 {%4,%5,%6,%7}, [%18 + 2048];\n"
                 "@p ldmatrix.sync.aligned.m8n8.x4.trans.shared.b16 {%8,%9,%10,%11}, [%18 + 4096];\n"
                 "@p ldmatrix.sync.aligned.m8n8.x4.trans.shared.b16 {%12,%13,%14,%15}, [%18 + 6144];\n"
                 "selp.u32 %16, 1, 0, p;\n}"
                 : "+r"(r[0]), "+r"(r[1]), "+r"(r[2]), "+r"(r[3]), "+r"(s[0]), "+r"(s[1]), "+r"(s[2]), "+r"(s[3]),
                   "+r"(u[0]), "+r"(u[1]), "+r"(u[2]), "+r"(u[3]), "+r"(v[0]), "+r"(v[1]), "+r"(v[2]), "+r"(v[3]), "=r"(ok)
                 : "r"(bar), "r"(a) : "memory");
    return ok != 0;
}
__device__ __forceinline__ void mma(float (&c)[4], const uint32_t (&a)[4], uint32_t b0, uint32_t b1) {
    asm volatile("mma.sync.aligned.m16n8k16.row.col.f32.bf16.bf16.f32 {%0,%1,%2,%3}, {%4,%5,%6,%7}, {%8,%9}, {%0,%1,%2,%3};"
                 : "+f"(c[0]), "+f"(c[1]), "+f"(c[2]), "+f"(c[3]) : "r"(a[0]), "r"(a[1]), "r"(a[2]), "r"(a[3]), "r"(b0), "r"(b1));
}
__device__ __forceinline__ uint32_t lds32(uint32_t a) { uint32_t v; asm volatile("ld.shared.b32 %0, [%1];" : "=r"(v) : "r"(a) : "memory"); return v; }
__device__ __forceinline__ uint32_t ldsv(uint32_t a) { uint32_t v; asm volatile("ld.volatile.shared.b32 %0, [%1];" : "=r"(v) : "r"(a) : "memory"); return v; }
__device__ __forceinline__ void stsv(uint32_t a, uint32_t v) { asm volatile("st.volatile.shared.b32 [%0], %1;" ::"r"(a), "r"(v) : "memory"); }
__device__ __forceinline__ float ldsf(uint32_t a) { float v; asm volatile("ld.shared.f32 %0, [%1];" : "=f"(v) : "r"(a) : "memory"); return v; }
__device__ __forceinline__ uint4 lds128(uint32_t a) { uint4 v; asm volatile("ld.shared.v4.b32 {%0,%1,%2,%3}, [%4];" : "=r"(v.x), "=r"(v.y), "=r"(v.z), "=r"(v.w) : "r"(a) : "memory"); return v; }
__device__ __forceinline__ void sts16(uint32_t a, uint16_t v) { asm volatile("st.shared.b16 [%0], %1;" ::"r"(a), "h"(v) : "memory"); }
__device__ __forceinline__ void sts32(uint32_t a, uint32_t v) { asm volatile("st.shared.b32 [%0], %1;" ::"r"(a), "r"(v) : "memory"); }
__device__ __forceinline__ void stsf2(uint32_t a, float x, float y) { asm volatile("st.shared.v2.f32 [%0], {%1,%2};" ::"r"(a), "f"(x), "f"(y) : "memory"); }
__device__ __forceinline__ void sts128(uint32_t a, uint4 v) { asm volatile("st.shared.v4.b32 [%0], {%1,%2,%3,%4};" ::"r"(a), "r"(v.x), "r"(v.y), "r"(v.z), "r"(v.w) : "memory"); }
__device__ __forceinline__ uint16_t f2bf(float x) { return __bfloat16_as_ushort(__float2bfloat16_rn(x)); }
__device__ __forceinline__ float bfround(float x) { return __bfloat162float(__float2bfloat16_rn(x)); }
__device__ __forceinline__ uint32_t pack2(float lo, float hi) { uint32_t r; asm("cvt.rn.bf16x2.f32 %0, %1, %2;" : "=r"(r) : "f"(hi), "f"(lo)); return r; }
__device__ __forceinline__ float ex2(float x) { float r; asm("ex2.approx.ftz.f32 %0, %1;" : "=f"(r) : "f"(x)); return r; }
__device__ __forceinline__ float lg2(float x) { float r; asm("lg2.approx.ftz.f32 %0, %1;" : "=f"(r) : "f"(x)); return r; }

__device__ __forceinline__ float rcp(float x) { float r; asm("rcp.approx.ftz.f32 %0, %1;" : "=f"(r) : "f"(x)); return r; }

__device__ __forceinline__ uint32_t clock_lo() { uint32_t t; asm volatile("mov.u32 %0, %clock;" : "=r"(t) :: "memory"); return t; }
__device__ __forceinline__ void sleep_ns(uint32_t ns) {
    const uint32_t t0 = clock_lo();
    do { __nanosleep(200); } while (clock_lo() - t0 < 2 * ns);
}

__device__ __forceinline__ void ll_store2(ulonglong2* p, float a, float b, uint32_t tag) {
    unsigned long long x = ((unsigned long long)tag << 32) | __float_as_uint(a);
    unsigned long long y = ((unsigned long long)tag << 32) | __float_as_uint(b);
    asm volatile("st.relaxed.gpu.global.v2.b64 [%0], {%1,%2};" ::"l"(p), "l"(x), "l"(y) : "memory");
}
__device__ __forceinline__ void ll_ld2(const void* p, unsigned long long& x, unsigned long long& y) {
    asm volatile("ld.relaxed.gpu.global.v2.b64 {%0,%1}, [%2];" : "=l"(x), "=l"(y) : "l"(p) : "memory");
}
__device__ __forceinline__ void ll_gather4(const ulonglong2* p, uint32_t tag, float& r0, float& r1) {
    unsigned long long x[4], y[4]; uint32_t it = 0;
    while (true) {
        bool ok = true;
#pragma unroll
        for (int k = 0; k < 4; k++) ll_ld2(p + k * 128, x[k], y[k]);
#pragma unroll
        for (int k = 0; k < 4; k++) ok = ok && (uint32_t)(x[k] >> 32) == tag && (uint32_t)(y[k] >> 32) == tag;
        if (ok) break;
        if (++it > SPIN_MAX) __trap();
        __nanosleep(BACKOFF);
    }
    r0 = (__uint_as_float((uint32_t)x[0]) + __uint_as_float((uint32_t)x[1])) + (__uint_as_float((uint32_t)x[2]) + __uint_as_float((uint32_t)x[3]));
    r1 = (__uint_as_float((uint32_t)y[0]) + __uint_as_float((uint32_t)y[1])) + (__uint_as_float((uint32_t)y[2]) + __uint_as_float((uint32_t)y[3]));
}
__device__ __forceinline__ void cnt_rendezvous(unsigned* c, uint32_t target, int tsk) {
    TS(tsk);
    asm volatile("red.release.gpu.global.add.u32 [%0], 1;" ::"l"(c) : "memory");
    if (tsk == 18) TS(tsk + 1);
    uint32_t v, it = 0;
    while (true) {
        asm volatile("ld.acquire.gpu.global.u32 %0, [%1];" : "=r"(v) : "l"(c) : "memory");
        if ((int)(v - target) >= 0) break;
        if (++it > SPIN_MAX) __trap();
        __nanosleep(BACKOFF);
    }
    asm volatile("fence.proxy.async.global;" ::: "memory");
}

__device__ __forceinline__ void matvec_loadA(uint32_t (&a)[8][4], uint32_t tile, uint32_t bar, int w, int lane) {
    const int i = lane >> 3, rr = lane & 7, chunk = 2 * w + (i & 1);
    const uint32_t a0 = tile + (chunk >> 3) * 8192 + (rr + 8 * (i >> 1)) * 128 + (((chunk & 7) ^ rr) << 4);
#pragma unroll
    for (int hh = 0; hh < 2; hh++) {
        mbar_wait(bar + hh * 8, 0);
#pragma unroll
        for (int k = 0; k < 4; k++) ldsm4t(a[hh * 4 + k], a0 + hh * CH + k * 2048);
    }
}
__device__ __forceinline__ void matvec_mma(float (&c)[4], const uint32_t (&a)[8][4], uint32_t vec, int nvec, int lane) {
    const uint32_t va = vec + (lane & (nvec - 1)) * VROW + (lane >> 3) * 16;
    float d[4][4];
#pragma unroll
    for (int q = 0; q < 4; q++) {
        uint32_t b[4];
        ldsm4(b, va + q * 64);
        d[q][0] = d[q][1] = d[q][2] = d[q][3] = 0.f;
        mma(d[q], a[2 * q], b[0], b[1]);
        mma(d[q], a[2 * q + 1], b[2], b[3]);
    }
#pragma unroll
    for (int k = 0; k < 4; k++) c[k] = (d[0][k] + d[1][k]) + (d[2][k] + d[3][k]);
}
__device__ __forceinline__ void matvecT(float (&c)[4], uint32_t tile, uint32_t vec, int nvec, uint32_t bar, int w, int lane) {
    uint32_t a[8][4];
    matvec_loadA(a, tile, bar, w, lane);
    matvec_mma(c, a, vec, nvec, lane);
}
template <class T> __device__ __forceinline__ T* pin(T* p) { asm volatile("" : "+l"(p)); return p; }
__device__ __forceinline__ void mail_put(void* p, uint32_t v) { asm volatile("st.relaxed.gpu.global.b32 [%0], %1;" ::"l"(p), "r"(v) : "memory"); }
__device__ __forceinline__ void mail_put(void* p, float v) { mail_put(p, __float_as_uint(v)); }
__device__ __forceinline__ void out_add(__nv_bfloat16* p, float x, float y) {
    asm volatile("red.relaxed.gpu.global.add.noftz.bf16x2 [%0], %1;" ::"l"(p), "r"(pack2(x, y)) : "memory");
}
__device__ __forceinline__ bool mail_missing(const uint4& v) { return v.x == EMPTY || v.y == EMPTY || v.z == EMPTY || v.w == EMPTY; }
__device__ __forceinline__ void mail_get(uint4& v, const uint4* p, bool need = true) {
    asm volatile("{\n.reg .pred q;\nsetp.ne.u32 q, %5, 0;\n@q ld.relaxed.gpu.global.v4.b32 {%0,%1,%2,%3}, [%4];\n}"
                 : "+r"(v.x), "+r"(v.y), "+r"(v.z), "+r"(v.w) : "l"(p), "r"((uint32_t)need) : "memory");
}
__device__ __forceinline__ void sts64(uint32_t a, uint32_t x, uint32_t y) { asm volatile("st.shared.v2.b32 [%0], {%1,%2};" ::"r"(a), "r"(x), "r"(y) : "memory"); }
__device__ __forceinline__ float2 ldsf2(uint32_t a) { float2 v; asm volatile("ld.shared.v2.f32 {%0,%1}, [%2];" : "=f"(v.x), "=f"(v.y) : "r"(a) : "memory"); return v; }

__global__ void __launch_bounds__(NTHREADS, 1)
fused_decode_kernel(const char* __restrict__ wqraw, const __grid_constant__ Maps maps, const char* __restrict__ Kc, const char* __restrict__ Vc,
                    const __nv_bfloat16* __restrict__ xA, const __nv_bfloat16* __restrict__ xB,
                    __nv_bfloat16* __restrict__ out, const uint32_t zero) {
    if (threadIdx.x == 0) asm volatile("cp.async.bulk.prefetch.L2.global [%0], 32768;" ::"l"(wqraw + (size_t)blockIdx.x * 32768u) : "memory");
    asm volatile("nanosleep.u32 60;" ::: "memory");
    asm volatile("barrier.cta.sync.aligned 7, %0;" ::"n"(NTHREADS) : "memory");
    asm volatile("{\n.reg .pred p;\n.reg .u32 s;\nmov.u32 s, %smid;\nsetp.eq.u32 p, s, 0xffff;\n@p exit;\n}" ::: "memory");
    extern __shared__ char smem_raw[];
    const uint32_t sm = ((uint32_t)__cvta_generic_to_shared(smem_raw) + 1023u) & ~1023u;
    const uint32_t bars = sm + OFF_BAR;
    const int cta = blockIdx.x, h = cta >> 2, j = cta & 3;
    const int col = ((h >> 3) * 4 + j) * 32;
    uint64_t pol = 0;
    if (threadIdx.x == 0) {
        TS(0);
        asm volatile("createpolicy.fractional.L2::evict_first.b64 %0, 1.0;" : "=l"(pol));
#pragma unroll
        for (int i = 0; i < WIN; i++) mbar_init(bars + (B_WQB + i) * 8, 1);
        asm volatile("fence.mbarrier_init.release.cluster;" ::: "memory");
#pragma unroll
        for (int i = 0; i < WIN; i++) {
            mbar_expect(bars + (B_WQB + i) * 8, CH);
            tma3d(sm + OFF_S0 + i * CH, &maps.wqB + (i >> 1), j * 128 + (i & 1) * 64, h * 2, bars + (B_WQB + i) * 8, pol);
        }
    }
    const int tid = threadIdx.x < 64 ? threadIdx.x + 384 : threadIdx.x - 64, warp = tid >> 5, lane = tid & 31;

    if (warp == 12) {
        const size_t kvoff = (size_t)cta * (NTILE / 2 * CH);
        const char* kp = Kc + kvoff;
        const char* vp = Vc + kvoff;
        __syncwarp();
        bar_arrive(0, NTHREADS);
        bar_sync(3, 64);
        if (lane == 0) {
            uint32_t pb[WHI];
#pragma unroll
            for (int i = 0; i < WHI; i++) pb[i] = i < WHI - WIN ? (bars + B_WO * 8) | 1u : bars + (B_WQB + i - (WHI - WIN)) * 8;
            auto pace = [&](uint32_t bar, uint32_t par) {
                uint32_t it = 0;
                while (true) {
                    const uint32_t win = ldsv(sm + OFF_WIN);
                    uint32_t busy = 0;
#pragma unroll
                    for (int i = 0; i < WHI; i++) busy += mbar_test(pb[i] & ~1u, pb[i] & 1u) ^ 1u;
                    if (busy < win) break;
                    if (++it > SPIN_MAX) __trap();
                }
#pragma unroll
                for (int i = 0; i + 1 < WHI; i++) pb[i] = pb[i + 1];
                pb[WHI - 1] = bar | par;
            };
            auto side = [&](const CUtensorMap* m, uint32_t dst, int bidx, int c1, int c2) {
                const uint32_t bar = bars + bidx * 8;
                pace(bar, 0);
                mbar_expect(bar, CH);
                tma3d(dst, m, c1, c2, bar, pol);
            };
#pragma unroll 1
            for (int i = WIN; i < 6; i++)
                side(&maps.wqB + (i >> 1), sm + OFF_S0 + i * CH, B_WQB + i, j * 128 + (i & 1) * 64, h * 2);
            TS(1);
            uint32_t slot = 0, use = 0, tend = 0;
            int nuv = 0;
#pragma unroll 1
            for (int n = 0; n < 2 * NTILE; n++) {
                if (n == RING) {
                    mbar_wait(bars + B_FREE * 8, 0);
#pragma unroll 1
                    for (int q = 0; q < 4; q++) side(&maps.ckv, sm + OFF_S0 + q * CH, B_CKV + q, cta * 64 + q * 16, 0);
                }
                if (nuv < 2 && n > RING && (n >= 2 * NTILE - 8 || mbar_test(bars + B_FREE * 8, 1))) {
                    mbar_wait(bars + B_FREE * 8, 1);
                    side(&maps.wuv, sm + OFF_S1 + nuv * CH, B_WUV + nuv, j * 128 + nuv * 64, h * 2);
                    nuv++;
                }
                const uint32_t fb = bars + slot * 8;
                pace(fb, use & 1);
                mbar_wait(fb + B_EMPTY * 8, (use & 1) ^ 1);
                mbar_expect(fb, CH);
                bulk1d(sm + OFF_RING + slot * CH, ((n & RUN) ? vp : kp) + (size_t)(n / NTILE * (NCTA * NTILE / 2) + n % NTILE / (2 * RUN) * RUN + n % RUN) * CH, fb, pol);
                stsv(sm + OFF_NOW, n + 1);
                if (((n + cta) & 3) == 0) {
                    if (n >= 2 * NTILE - 6 && n < 2 * NTILE - 2) {
                        const uint32_t left = -atomicAdd(&g_cnt[2], 4u) & (NCTA * 2 * NTILE - 1);
                        stsv(sm + OFF_NOW, n + 1 + (left & zero));
                        tend = clock_lo() + left * OP_CLK16 / 16;
                    } else {
                        asm volatile("red.relaxed.gpu.global.add.u32 [%0], 4;" ::"l"(&g_cnt[2]) : "memory");
                    }
                }
                if (++slot == RING) { slot = 0; use++; }
            }
            TS(2);
            mbar_wait(bars + B_FREE * 8, 0);
#pragma unroll 1
            for (int i = 0; i < 8; i++) {
                uint32_t it = 0;
                while (true) {
                    uint32_t busy = i;
#pragma unroll
                    for (int k = 0; k < 4; k++) busy += 2 * (mbar_test(pb[WHI - 4 + k] & ~1u, pb[WHI - 4 + k] & 1u) ^ 1u);
#pragma unroll
                    for (int k = 0; k < 5; k++) busy -= mbar_test(bars + (B_WO + k) * 8, 0);
                    const uint32_t due = tend - BOX_FIRST + i * BOX_CLK;
                    if (busy < TAIL_LO) break;
                    if (busy < TAIL_HI && (int)(due - clock_lo()) < 400) {
                        while ((int)(due - clock_lo()) > 0) {}
                        break;
                    }
                    if (++it > SPIN_MAX) __trap();
                }
                if (i & 1) TS(32 + (i >> 1));
                mbar_expect(bars + (B_WO + i) * 8, CH / 2);
                tma3d(sm + OFF_S0 + i * (CH / 2), &maps.woB + (i >> 2), 0, (i & 3) * 8 + (h & 7), bars + (B_WO + i) * 8, pol, col);
            }
            TS(3);
        }
    } else if (warp == 13) {
        if (lane == 0) {
#pragma unroll
            for (int i = 0; i < NBAR; i++)
                if (i < B_WQB || i >= B_WQB + WIN)
                    mbar_init(bars + i * 8, i == B_FREE ? 8 : (i >= B_EMPTY && i < B_EMPTY + RING) ? 4 : 1);
            asm volatile("fence.mbarrier_init.release.cluster;" ::: "memory");
#pragma unroll
            for (int i = 2; i < 8; i++) asm volatile("prefetch.tensormap [%0];" ::"l"(&maps.wqB + i) : "memory");
            stsv(sm + OFF_NOW, 0); stsv(sm + OFF_WIN, WIN);
        }
        __syncwarp();
        bar_arrive(3, 64);
        bar_sync(0, NTHREADS);
        if (lane == 0) {
            const uint32_t base = (lds32(sm + OFF_TAG) - 1u) * (NCTA * 2 * NTILE);
            mbar_wait(bars + (B_WUK + 1) * 8, 0);
            uint32_t it = 0;
            while (true) {
                const uint32_t n = ldsv(sm + OFF_NOW);
                uint32_t v;
                asm volatile("ld.relaxed.gpu.global.u32 %0, [%1];" : "=r"(v) : "l"(&g_cnt[2]) : "memory");
                v -= base;
                if (v >= NCTA * 2 * NTILE - GATE_W) break;
                const int diff = (int)(n * NCTA) - (int)v;
                stsv(sm + OFF_WIN, diff < -THETA ? WHI : WIN - (diff > THETA) - (v >= NCTA * END_V));
                if (++it > SPIN_MAX) __trap();
                __nanosleep(BACKOFF2);
            }
            stsv(sm + OFF_WIN, WHI);
            TS(24);
        }
    } else if (warp < 4) {
        const int g = lane >> 2, t = lane & 3, i = lane >> 3, rr = lane & 7;
        if (tid == 0) {
            unsigned e;
            asm volatile("ld.relaxed.gpu.global.u32 %0, [%1];" : "=r"(e) : "l"(&g_cnt[1]) : "memory");
            sts32(sm + OFF_TAG, (e >> 7) + 1u);
        }
        bar_sync(0, NTHREADS);
        const uint32_t tag = lds32(sm + OFF_TAG);
        {
            mbar_wait(bars + 8, 0);
            float q0, q1;
            ll_gather4(&g_e1[0][h * 4][tid], tag, q0, q1);
            sts16(sm + OFF_QB + tid * 2, f2bf(q0)); sts16(sm + OFF_QB + 256 + tid * 2, f2bf(q1));
        }
        bar_sync(1, 128);
        if (tid == 0) TS(4);
        uint32_t qf[8][2];
        float acc[8][4], m, l;
        auto start = [&](int b) {
#pragma unroll
            for (int c = 0; c < 8; c++) {
                const uint32_t a = sm + OFF_QB + b * 256 + (((c + g) & 7) * 8 + 2 * t) * 2;
                qf[c][0] = lds32(a); qf[c][1] = lds32(a + 128);
                acc[c][0] = acc[c][1] = acc[c][2] = acc[c][3] = 0.f;
            }
            m = -INFINITY; l = 0.f;
        };
        auto stats = [&](int b) {
#pragma unroll
            for (int o = 16; o; o >>= 1) l += __shfl_xor_sync(0xffffffffu, l, o);
            if (lane == 0) stsf2(sm + OFF_ML + b * 32 + warp * 8, m, l);
        };
        auto quad_sum = [&](float (&r)[4]) {
            float v[2][8];
#pragma unroll
            for (int c = 0; c < 8; c++) { v[0][c] = acc[c][0] + acc[(c + 7) & 7][1]; v[1][c] = acc[c][2] + acc[(c + 7) & 7][3]; }
#pragma unroll
            for (int c = 0; c < 4; c++) { v[0][c] += __shfl_xor_sync(0xffffffffu, v[0][c + 4], 2); v[1][c] += __shfl_xor_sync(0xffffffffu, v[1][c + 4], 2); }
            const int src = (lane & ~3) | ((lane + 3) & 3);
#pragma unroll
            for (int c = 0; c < 4; c++) r[c] = v[c >> 1][c & 1] + __shfl_sync(0xffffffffu, v[c >> 1][(c & 1) + 2], src);
        };
        auto factor = [&](int b, float& lse) {
            bar_sync(1, 128);
            const uint4 ml0 = lds128(sm + OFF_ML + b * 32), ml1 = lds128(sm + OFF_ML + b * 32 + 16);
            const float m0 = __uint_as_float(ml0.x), m1 = __uint_as_float(ml0.z), m2 = __uint_as_float(ml1.x), m3 = __uint_as_float(ml1.z);
            const float M = fmaxf(fmaxf(m0, m1), fmaxf(m2, m3));
            const float L = (ex2((m0 - M) * LOG2E) * __uint_as_float(ml0.y) + ex2((m1 - M) * LOG2E) * __uint_as_float(ml0.w))
                          + (ex2((m2 - M) * LOG2E) * __uint_as_float(ml1.y) + ex2((m3 - M) * LOG2E) * __uint_as_float(ml1.w));
            lse = M * LOG2E + lg2(L);
            return ex2((ldsf(sm + OFF_ML + b * 32 + warp * 8) - M) * LOG2E) * rcp(L);
        };
        auto publish = [&](uint32_t* dst, const float (&r)[4], float f) {
            const uint32_t wa = sm + OFF_S2 + warp * 640 + (t * 16 + (t >> 1) * 8 + g) * 4;
            const uint32_t ra = sm + OFF_S2 + ((tid >> 4 & 1) * 40 + (tid & 2) * 40 + (tid >> 5 & 1) * 16 + (tid & 1) * 8 + (tid >> 2 & 3) * 2) * 4;
#pragma unroll
            for (int c = 0; c < 4; c++) sts32(wa + (c >> 1) * 320 + (c & 1) * 32, __float_as_uint(r[c] * f));
            bar_sync(1, 128);
            const float2 r0 = ldsf2(ra), r1 = ldsf2(ra + 640), r2 = ldsf2(ra + 1280), r3 = ldsf2(ra + 1920);
            if (tid < 64) mail_put(dst, pack2((r0.x + r1.x) + (r2.x + r3.x), (r0.y + r1.y) + (r2.y + r3.y)));
        };
        float o0[4] = {0.f, 0.f, 0.f, 0.f};
        start(0);
        const bool diag = (t == (g >> 1));
        const uint32_t krow = sm + OFF_RING + (warp * 16 + rr + 8 * (i & 1)) * 256 + (i >> 1) * 128;
        const uint32_t vrow = sm + OFF_RING + (warp * 16 + rr + 8 * (i >> 1)) * 256 + (i & 1) * 128;
        uint32_t slot = 0, ph = 0;
        uint32_t a[8][4] = {}, b0[RUN], b1[RUN];
        auto release = [&]() {
            __syncwarp();
            if (lane == 0) mbar_arrive(bars + (B_EMPTY + slot) * 8 + ((a[0][0] | a[1][0] | a[2][0] | a[3][0] | a[4][0] | a[5][0] | a[6][0] | a[7][0]) & zero));
            if (++slot == RING) { slot = 0; ph ^= 1; }
        };
        auto load_v = [&]() {
            mbar_wait(bars + slot * 8, ph);
#pragma unroll
            for (int c = 0; c < 8; c++) ldsm4t(a[c], vrow + slot * CH + (((c + rr) & 7) << 4));
        };
#pragma unroll 1
        for (int run = 0;; run++) {
            float slo[RUN], shi[RUN], mx = -INFINITY;
#pragma unroll
            for (int u = 0; u < RUN; u++) {
                mbar_wait(bars + slot * 8, ph);
#pragma unroll
                for (int c = 0; c < 8; c++) ldsm4(a[c], krow + slot * CH + (((c + rr) & 7) << 4));
                release();
                float s0[4] = {0.f, 0.f, 0.f, 0.f}, s1[4] = {0.f, 0.f, 0.f, 0.f};
#pragma unroll
                for (int c = 0; c < 8; c += 2) { mma(s0, a[c], qf[c][0], qf[c][1]); mma(s1, a[c + 1], qf[c + 1][0], qf[c + 1][1]); }
                slo[u] = diag ? bfround(bfround((g & 1) ? s0[1] + s1[1] : s0[0] + s1[0]) * SCALE) : -INFINITY;
                shi[u] = diag ? bfround(bfround((g & 1) ? s0[3] + s1[3] : s0[2] + s1[2]) * SCALE) : -INFINITY;
                mx = fmaxf(mx, fmaxf(slo[u], shi[u]));
            }
            int key = __float_as_int(mx);
            key ^= (key >> 31) & 0x7fffffff;
            key = __reduce_max_sync(0xffffffffu, key);
            key ^= (key >> 31) & 0x7fffffff;
            const float mn = fmaxf(m, __int_as_float(key));
            const float alpha = ex2((m - mn) * LOG2E);
            m = mn;
            l *= alpha;
#pragma unroll
            for (int u = 0; u < RUN; u++) {
                const float plo = ex2((slo[u] - mn) * LOG2E), phi = ex2((shi[u] - mn) * LOG2E);
                l += plo + phi;
                b0[u] = (g & 1) ? pack2(0.f, plo) : pack2(plo, 0.f);
                b1[u] = (g & 1) ? pack2(0.f, phi) : pack2(phi, 0.f);
            }
#pragma unroll
            for (int c = 0; c < 8; c++) { acc[c][0] *= alpha; acc[c][1] *= alpha; acc[c][2] *= alpha; acc[c][3] *= alpha; }
            if (run == NTILE / RUN - 1) break;
#pragma unroll
            for (int u = 0; u < RUN; u++) {
                load_v();
                release();
#pragma unroll
                for (int c = 0; c < 8; c++) mma(acc[c], a[c], b0[u], b1[u]);
            }
            if (run == NTILE / RUN / 2 - 1) { stats(0); quad_sum(o0); start(1); }
            if (run == NTILE / RUN - 2) {
                float lse;
                mbar_wait(bars + B_S2 * 8, 0);
                publish((uint32_t*)g_e5[cta] + tid, o0, factor(0, lse));
                if (tid == 96) mail_put((float*)g_l5[h] + j, lse);
            }
        }
        {
            float lse;
            stats(1);
            const float f = factor(1, lse);
            uint32_t* const e5own = pin((uint32_t*)g_e5[cta] + 64 + tid);
            float* const l5own = pin((float*)g_l5[h] + 4 + j);
#pragma unroll
            for (int u = 0; u < RUN; u++) {
                load_v();
                if (++slot == RING) { slot = 0; ph ^= 1; }
                if (u == RUN - 1 && tid == 96) mail_put(l5own, lse);
#pragma unroll
                for (int c = 0; c < 8; c++) mma(acc[c], a[c], b0[u], b1[u]);
            }
            if (tid == 0) TS(5);
            quad_sum(o0);
            publish(e5own, o0, f);
        }
        if (tid == 0) TS(6);
        {
            uint32_t x[4][4][4];
            float d[4][4];
            bar_sync(4, 256 + 128);
#pragma unroll
            for (int k = 0; k < 16; k++) ldsm4(x[k >> 2][k & 3], sm + OFF_CA + ((k >> 2) * 2 + (lane & 1)) * VROW + (k & 3) * 64 + (i & 1) * 32 + (i >> 1) * 16);
            const uint32_t wa = sm + OFF_S1 + lane * 64 + ((warp ^ (rr >> 1)) << 4);
            __nv_bfloat16* const outp = pin(out + (g & 1) * 1024 + col + warp * 8 + t * 2);
            mbar_wait(bars + (B_WO + 4) * 8, 0);
            uint32_t it = 0;
            while (true) {
                bool ok = true;
#pragma unroll
                for (int k = 0; k < 4; k++) d[k][0] = d[k][1] = d[k][2] = d[k][3] = 0.f;
#pragma unroll
                for (int q = 0; q < 5; q++) {
                    if (q < 4) ok &= box_load(a[(q & 1) * 4], a[(q & 1) * 4 + 1], a[(q & 1) * 4 + 2], a[(q & 1) * 4 + 3], bars + (B_WO + 4 + q) * 8, wa + q * 8192);
#pragma unroll
                    for (int k = 0; k < (q ? 8 : 0); k++) {
                        const uint32_t (&u)[4] = a[(~q & 1) * 4 + (k >> 1)];
                        mma(d[k & 3], x[q - 1][k >> 1], u[(k & 1) * 2], u[(k & 1) * 2 + 1]);
                    }
                }
                asm volatile("{\n.reg .pred p;\nsetp.ne.u32 p, %0, 0;\n@p exit;\n}" ::"r"((uint32_t)(ok && lane >= 8)) : "memory");
                if (ok) break;
                if (++it > SPIN_MAX) __trap();
            }
            out_add(outp, (d[0][0] + d[1][2]) + (d[2][0] + d[3][2]), (d[0][1] + d[1][3]) + (d[2][1] + d[3][3]));
            if (tid == 0) TS(15);
        }
    } else {
        const int st = tid - 128, w = warp - 4;
        const int g = lane >> 2, t = lane & 3, i = lane >> 3, rr = lane & 7;
        if (t == 0) {
#pragma unroll
            for (int k = 0; k < 4; k++) ll_store2(&g_e1[k >> 1][cta][w * 16 + g + (k & 1) * 8], 0.f, 0.f, 0u);
        }
        if (st < 64) {
            const int which = st >> 5, b = (st >> 4) & 1, c = st & 15;
            const uint4 v = __ldg((const uint4*)((which ? xA : xB) + b * 512 + j * 128) + c);
            sts128(sm + OFF_XB + (which * 2 + b) * VROW + c * 16, v);
        }
        bar_sync(0, NTHREADS);
        const uint32_t tag = lds32(sm + OFF_TAG);
        float c[4];
#pragma unroll 1
        for (int which = 0; which < 2; which++) {
            matvecT(c, sm + OFF_S0 + which * 2 * CH, sm + OFF_XB + which * 2 * VROW, 2, bars + (B_WQB + which * 2) * 8, w, lane);
            if (t == 0) {
                ll_store2(&g_e1[which][cta][w * 16 + g], c[0], c[1], tag);
                ll_store2(&g_e1[which][cta][w * 16 + g + 8], c[2], c[3], tag);
            }
        }
        __syncwarp();
        if (lane == 0) mbar_arrive(bars + B_FREE * 8);
        if (st == 0) TS(8);
        if (st < 128) {
            float q0, q1;
            sleep_ns(POLL_DELAY);
            ll_gather4(&g_e1[1][h * 4][st], tag, q0, q1);
            sts16(sm + OFF_QA + st * 2, f2bf(q0)); sts16(sm + OFF_QA + VROW + st * 2, f2bf(q1));
        }
        bar_sync(2, 256);
        if (st == 0) TS(9);
        {
            const int row = w * 16 + rr + 8 * (i & 1);
            const uint32_t a0 = sm + OFF_S2 + (row >> 6) * CH + (row & 63) * 128;
            const uint32_t va = sm + OFF_QA + g * VROW + t * 4;
            float d[4] = {0.f, 0.f, 0.f, 0.f};
            c[0] = c[1] = c[2] = c[3] = 0.f;
            mbar_wait(bars + (B_WUK + (w >> 2)) * 8, 0);
#pragma unroll
            for (int ks = 0; ks < 8; ks++) {
                const int chunk = 2 * ks + (i >> 1);
                uint32_t a[4];
                ldsm4(a, a0 + (chunk >> 3) * 8192 + (((chunk & 7) ^ rr) << 4));
                const uint32_t b0 = (g < 2) ? lds32(va + ks * 32) : 0u, b1 = (g < 2) ? lds32(va + ks * 32 + 16) : 0u;
                if (ks & 1) mma(d, a, b0, b1); else mma(c, a, b0, b1);
            }
            if (t == 0) {
                const uint32_t qs = sm + OFF_QS + (w * 16 + g) * 2;
                sts16(qs, f2bf(c[0] + d[0])); sts16(qs + VROW, f2bf(c[1] + d[1]));
                sts16(qs + 16, f2bf(c[2] + d[2])); sts16(qs + VROW + 16, f2bf(c[3] + d[3]));
            }
            bar_sync(2, 256);
            if (w == 0) {
                const int b = lane >> 4, cc = lane & 15;
                g_qabs[(b * 32 + h) * 64 + ((j * 16 + cc) ^ (h & 7))] = lds128(sm + OFF_QS + b * VROW + cc * 16);
                __syncwarp();
                if (lane == 0) {
                    cnt_rendezvous(&g_cnt[0], tag * 128u, 18);
                    TS(10);
                    mbar_expect(bars + B_GATH * 8, 2 * CH);
                    bulk1d_n(sm + OFF_S2, g_qabs + (cta >> 6) * 2048, 2 * CH, bars + B_GATH * 8);
                }
                __syncwarp();
            }
        }
        mbar_wait(bars + B_GATH * 8, 0);
        if (st == 0) TS(11);
        {
            const int mt = w & 1, kg = w >> 1;
            const uint32_t qa = sm + OFF_S2 + (mt * 16 + rr + 8 * (i & 1)) * 1024;
            const uint32_t ka = sm + OFF_S0 + kg * CH + (rr + 8 * (i >> 1)) * 128;
            float s0[4] = {0.f, 0.f, 0.f, 0.f}, s1[4] = {0.f, 0.f, 0.f, 0.f};
            mbar_wait(bars + (B_CKV + kg) * 8, 0);
#pragma unroll 2
            for (int gq = 0; gq < 8; gq++) {
#pragma unroll
                for (int k4 = 0; k4 < 4; k4++) {
                    uint32_t a[4], b[4];
                    ldsm4(a, qa + gq * 128 + (((2 * k4 + (i >> 1)) ^ rr) << 4));
                    ldsm4(b, ka + gq * 2048 + (((2 * k4 + (i & 1)) ^ rr) << 4));
                    mma(s0, a, b[0], b[1]);
                    mma(s1, a, b[2], b[3]);
                }
            }
            const uint32_t sa = sm + OFF_SC + ((mt * 16 + g) * 68 + kg * 16 + 2 * t) * 4;
            stsf2(sa, s0[0], s0[1]); stsf2(sa + 32, s1[0], s1[1]);
            stsf2(sa + 8 * 68 * 4, s0[2], s0[3]); stsf2(sa + 8 * 68 * 4 + 32, s1[2], s1[3]);
        }
        bar_sync(2, 256);
        {
            const int head = w * 4 + i;
            const uint32_t sa = sm + OFF_SC + (head * 68 + rr * 8) * 4;
            const uint4 u0 = lds128(sa), u1 = lds128(sa + 16);
            float s[8] = {__uint_as_float(u0.x), __uint_as_float(u0.y), __uint_as_float(u0.z), __uint_as_float(u0.w),
                          __uint_as_float(u1.x), __uint_as_float(u1.y), __uint_as_float(u1.z), __uint_as_float(u1.w)};
            float mx = s[0];
#pragma unroll
            for (int k = 1; k < 8; k++) mx = fmaxf(mx, s[k]);
#pragma unroll
            for (int o = 1; o < 8; o <<= 1) mx = fmaxf(mx, __shfl_xor_sync(0xffffffffu, mx, o));
            float sum = 0.f;
#pragma unroll
            for (int k = 0; k < 8; k++) { s[k] = ex2((s[k] - mx) * (SCALE * LOG2E)); sum += s[k]; }
#pragma unroll
            for (int o = 1; o < 8; o <<= 1) sum += __shfl_xor_sync(0xffffffffu, sum, o);
            const float inv = __fdividef(1.f, sum);
            uint4 p;
            p.x = pack2(s[0] * inv, s[1] * inv); p.y = pack2(s[2] * inv, s[3] * inv);
            p.z = pack2(s[4] * inv, s[5] * inv); p.w = pack2(s[6] * inv, s[7] * inv);
            sts128(sm + OFF_P + head * 128 + ((rr ^ (head & 7)) << 4), p);
            if (rr == 0) ((float*)g_lse)[head * 128 + cta] = mx * (SCALE * LOG2E) + lg2(sum);
        }
        bar_sync(2, 256);
        {
            float o[2][8][4];
#pragma unroll
            for (int mt = 0; mt < 2; mt++)
#pragma unroll
                for (int n = 0; n < 8; n++) { o[mt][n][0] = o[mt][n][1] = o[mt][n][2] = o[mt][n][3] = 0.f; }
            const uint32_t pa = sm + OFF_P + (rr + 8 * (i & 1)) * 128;
            const uint32_t va = sm + OFF_S0 + w * 2048 + (rr + 8 * (i & 1)) * 128;
#pragma unroll 1
            for (int kq = 0; kq < 4; kq++) {
                uint32_t a0[4], a1[4];
                ldsm4(a0, pa + (((2 * kq + (i >> 1)) ^ rr) << 4));
                ldsm4(a1, pa + 2048 + (((2 * kq + (i >> 1)) ^ rr) << 4));
#pragma unroll
                for (int n = 0; n < 8; n += 2) {
                    uint32_t b[4];
                    ldsm4t(b, va + kq * CH + (((n + (i >> 1)) ^ rr) << 4));
                    mma(o[0][n], a0, b[0], b[1]); mma(o[1][n], a1, b[0], b[1]);
                    mma(o[0][n + 1], a0, b[2], b[3]); mma(o[1][n + 1], a1, b[2], b[3]);
                }
            }
#pragma unroll
            for (int mt = 0; mt < 2; mt++)
#pragma unroll
                for (int hf = 0; hf < 2; hf++) {
                    const uint32_t dst = sm + OFF_S2 + (mt * 16 + hf * 8 + g) * 1024 + w * 128 + t * 16;
#pragma unroll
                    for (int nb = 0; nb < 2; nb++) {
                        uint4 v;
                        v.x = pack2(o[mt][nb * 4 + 0][hf * 2], o[mt][nb * 4 + 0][hf * 2 + 1]);
                        v.y = pack2(o[mt][nb * 4 + 1][hf * 2], o[mt][nb * 4 + 1][hf * 2 + 1]);
                        v.z = pack2(o[mt][nb * 4 + 2][hf * 2], o[mt][nb * 4 + 2][hf * 2 + 1]);
                        v.w = pack2(o[mt][nb * 4 + 3][hf * 2], o[mt][nb * 4 + 3][hf * 2 + 1]);
                        sts128(dst + nb * 64, v);
                    }
                }
            asm volatile("fence.proxy.async.shared::cta;" ::: "memory");
            __syncwarp();
            if (lane == 0) mbar_arrive(bars + B_FREE * 8);
            if (st < 98) *(st < 64 ? &g_e4[cta][st] : st < 96 ? &g_e5[cta][st - 64] : &g_l5[h][j * 2 + st - 96]) = make_uint4(EMPTY, EMPTY, EMPTY, EMPTY);
            else if (st < 100) ((uint4*)out)[cta * 2 + st - 98] = make_uint4(0u, 0u, 0u, 0u);
        }
        bar_sync(2, 256);
        if (st == 0) {
            TS(12);
#pragma unroll 1
            for (int k = 0; k < ST_SPLIT; k++) {
                asm volatile("cp.async.bulk.tensor.3d.global.shared::cta.bulk_group [%0, {%2,%3,%4}], [%1];"
                             ::"l"(&maps.ctxp), "r"(sm + OFF_S2 + k * (2 * CH / ST_SPLIT)), "r"(0), "r"(cta), "r"(k * (128 / ST_SPLIT)) : "memory");
                if (k + 1 < ST_SPLIT) __nanosleep(ST_GAP);
            }
            asm volatile("cp.async.bulk.commit_group;" ::: "memory");
            asm volatile("cp.async.bulk.wait_group 0;" ::: "memory");
            cnt_rendezvous(&g_cnt[1], tag * 128u, 20);
            TS(13);
            mbar_expect(bars + B_GATH * 8, 2 * CH + 512);
            bulk1d_n(sm + OFF_LSE, g_lse + h * 32, 512, bars + B_GATH * 8);
#pragma unroll 1
            for (int k = 0; k < G_SPLIT; k++) {
                bulk1d_n(sm + OFF_S2 + k * (2 * CH / G_SPLIT), g_ctxp + cta * 2048 + k * (2048 / G_SPLIT), 2 * CH / G_SPLIT, bars + B_GATH * 8);
                if (k + 1 < G_SPLIT) __nanosleep(G_GAP);
            }
        }
        __syncwarp();
        {
            mbar_wait(bars + B_GATH * 8, 1);
            if (st == 0) TS(22);
            uint4 v[8];
#pragma unroll
            for (int k = 0; k < 8; k++) v[k] = lds128(sm + OFF_S2 + (k * 256 + st) * 16);
            float ls[4];
#pragma unroll
            for (int k = 0; k < 4; k++) ls[k] = ldsf(sm + OFF_LSE + (k * 32 + lane) * 4);
            float m0 = fmaxf(ls[0], ls[1]), m1 = fmaxf(ls[2], ls[3]);
#pragma unroll
            for (int o = 16; o; o >>= 1) { m0 = fmaxf(m0, __shfl_xor_sync(0xffffffffu, m0, o)); m1 = fmaxf(m1, __shfl_xor_sync(0xffffffffu, m1, o)); }
            ls[0] = ex2(ls[0] - m0); ls[1] = ex2(ls[1] - m0); ls[2] = ex2(ls[2] - m1); ls[3] = ex2(ls[3] - m1);
            float z0 = ls[0] + ls[1], z1 = ls[2] + ls[3];
#pragma unroll
            for (int o = 16; o; o >>= 1) { z0 += __shfl_xor_sync(0xffffffffu, z0, o); z1 += __shfl_xor_sync(0xffffffffu, z1, o); }
            z0 = __fdividef(1.f, z0); z1 = __fdividef(1.f, z1);
            ls[0] *= z0; ls[1] *= z0; ls[2] *= z1; ls[3] *= z1;
            float a[2][8];
#pragma unroll
            for (int e = 0; e < 8; e++) a[0][e] = a[1][e] = 0.f;
            const int rg = st >> 4;
#pragma unroll
            for (int k = 0; k < 8; k++) {
                const float wt = __shfl_sync(0xffffffffu, ls[k >> 1], rg + 16 * (k & 1));
                const uint32_t u[4] = {v[k].x, v[k].y, v[k].z, v[k].w};
#pragma unroll
                for (int e = 0; e < 4; e++) {
                    a[k >> 2][2 * e] += wt * __uint_as_float(u[e] << 16);
                    a[k >> 2][2 * e + 1] += wt * __uint_as_float(u[e] & 0xffff0000u);
                }
            }
            const int b = lane >> 4, u16 = lane & 15;
            const uint32_t ra = sm + OFF_SC + (w * 256 + b * 128 + (u16 >> 3) * 64 + ((u16 >> 2) & 1) * 32 + (u16 & 3) * 2) * 4;
#pragma unroll
            for (int e = 0; e < 8; e += 2) {
                const float k0 = b ? a[1][e] : a[0][e], k1 = b ? a[1][e + 1] : a[0][e + 1];
                const float s0 = b ? a[0][e] : a[1][e], s1 = b ? a[0][e + 1] : a[1][e + 1];
                stsf2(ra + (e >> 1) * 32, k0 + __shfl_xor_sync(0xffffffffu, s0, 16), k1 + __shfl_xor_sync(0xffffffffu, s1, 16));
            }
            bar_sync(2, 256);
            if (st == 0) mbar_arrive(bars + B_S2 * 8);
            float s = 0.f;
#pragma unroll
            for (int k = 0; k < 8; k++) s += ldsf(sm + OFF_SC + (k * 256 + st) * 4);
            const float hi = bfround(s);
            const uint32_t ca = sm + OFF_CC + (st >> 7) * VROW + (st & 127) * 2;
            sts16(ca, f2bf(hi)); sts16(ca + 2 * VROW, f2bf(s - hi));
            bar_sync(2, 256);
        }
        matvecT(c, sm + OFF_S1, sm + OFF_CC, 4, bars + B_WUV * 8, w, lane);
#pragma unroll
        for (int k = 0; k < 4; k++) c[k] += __shfl_down_sync(0xffffffffu, c[k], 1);
        if (t == 0) {
            float* const e = (float*)g_e4[cta] + w * 16 + g;
            mail_put(e, c[0]); mail_put(e + 128, c[1]); mail_put(e + 8, c[2]); mail_put(e + 136, c[3]);
        }
        __syncwarp();
        if (lane == 0) mbar_arrive(bars + B_FREE * 8);
        if (st == 0) TS(23);
        {
            const uint4* const pv = &g_e4[(w >> 1) * 32 + (cta & 28)][(w & 1) * 32 + lane];
            uint4 x[4];
            uint32_t it = 0;
            sleep_ns(POLL_DELAY2);
            while (true) {
#pragma unroll
                for (int k = 0; k < 4; k++) { x[k].x = x[k].y = x[k].z = x[k].w = 0u; mail_get(x[k], pv + k * 64); }
                if (!__any_sync(0xffffffffu, mail_missing(x[0]) | mail_missing(x[1]) | mail_missing(x[2]) | mail_missing(x[3]))) break;
                if (++it > SPIN_MAX) __trap();
                __nanosleep(BACKOFF);
            }
#define SUM4(e) ((__uint_as_float(x[0].e) + __uint_as_float(x[1].e)) + (__uint_as_float(x[2].e) + __uint_as_float(x[3].e)))
            sts64(sm + OFF_CA + w * VROW + lane * 8, pack2(SUM4(x), SUM4(y)), pack2(SUM4(z), SUM4(w)));
#undef SUM4
        }
        if (st == 0) TS(14);
        bar_sync(4, 256 + 128);
        {
            const uint32_t a0 = sm + OFF_S0 + (w >> 1) * 8192 + (w & 1) * 1024 + (rr + 8 * (i >> 1)) * 64 + (((i & 1) ^ (rr >> 1)) << 4);
            const uint4* const pv = pin(&g_e5[(w >> 1) * 32 + (cta & 28) + (g & 3)][(g >> 2) * 16 + (w & 1) * 8 + t]);
            const uint32_t* const pl = pin((const uint32_t*)g_l5[(w >> 1) * 8 + (h & 7)] + rr);
            const uint32_t wa = sm + OFF_SC + ((w * 2 + (t & 1)) * 80 + (t >> 1) * 40 + g) * 4;
            __nv_bfloat16* const outp = pin(out + (lane >> 4) * 1024 + 512 + col + (lane & 15) * 2);
            uint32_t a[4][2][4], xl = 0u, it = 0;
            uint4 x[2] = {make_uint4(0u, 0u, 0u, 0u), make_uint4(0u, 0u, 0u, 0u)};
            while (true) {
                if (lane < 8) asm volatile("atom.relaxed.gpu.global.or.b32 %0, [%1], 0;" : "=r"(xl) : "l"(pl) : "memory");
                if (!__any_sync(0xffffffffu, xl == EMPTY)) break;
                if (++it > SPIN_MAX) __trap();
            }
            if (st == 0) TS(25);
            mail_get(x[0], pv); mail_get(x[1], pv + 4);
            float w0 = __uint_as_float(xl), w1 = fmaxf(w0, __shfl_xor_sync(0xffffffffu, w0, 1));
            w0 = ex2(w0 - fmaxf(w1, __shfl_xor_sync(0xffffffffu, w1, 2)));
            w1 = w0 + __shfl_xor_sync(0xffffffffu, w0, 1);
            w0 *= rcp(w1 + __shfl_xor_sync(0xffffffffu, w1, 2));
            w1 = __shfl_sync(0xffffffffu, w0, 2 * t + 1);
            w0 = __shfl_sync(0xffffffffu, w0, 2 * t);
            mbar_wait(bars + (B_WO + (w >> 1)) * 8, 0);
#pragma unroll
            for (int q = 0; q < 4; q++) {
                ldsm4t(a[q][0], a0 + q * 2048);
                ldsm4t(a[q][1], (a0 ^ 32) + q * 2048);
            }
            if (st == 0) TS(26);
            while (true) {
                const bool n0 = mail_missing(x[0]), n1 = mail_missing(x[1]);
                if (!__any_sync(0xffffffffu, n0 | n1)) break;
                mail_get(x[0], pv, n0); mail_get(x[1], pv + 4, n1);
                if (++it > SPIN_MAX) __trap();
            }
            if (st == 0) TS(16);
            float d[2][2][4];
#pragma unroll
            for (int k = 0; k < 4; k++) {
                float (&dk)[4] = d[k >> 1][k & 1];
                dk[0] = dk[1] = dk[2] = dk[3] = 0.f;
                mma(dk, a[k >> 1][k & 1], x[k >> 1].x, x[k >> 1].y);
            }
#pragma unroll
            for (int k = 0; k < 4; k++) mma(d[k >> 1][k & 1], a[2 + (k >> 1)][k & 1], x[k >> 1].z, x[k >> 1].w);
#pragma unroll
            for (int k = 0; k < 4; k++) {
                const int e = (k & 1) * 2;
                sts32(wa + k * 32, __float_as_uint(w0 * (d[0][k >> 1][e] + d[1][k >> 1][e]) + w1 * (d[0][k >> 1][e + 1] + d[1][k >> 1][e + 1])));
            }
            if (st == 0) TS(17);
            if (w == 0) {
                bar_sync(5, 256);
                const uint32_t ra = sm + OFF_SC + ((lane >> 4) * 40 + (lane & 15) * 2) * 4;
                float2 r[16];
#pragma unroll
                for (int k = 0; k < 16; k++) r[k] = ldsf2(ra + k * 320);
#pragma unroll
                for (int o = 1; o < 16; o <<= 1)
#pragma unroll
                    for (int k = 0; k < 16; k += 2 * o) { r[k].x += r[k + o].x; r[k].y += r[k + o].y; }
                out_add(outp, r[0].x, r[0].y);
            } else {
                bar_arrive(5, 256);
            }
        }
    }
}

typedef CUresult (*EncodeFn)(CUtensorMap*, CUtensorMapDataType, cuuint32_t, void*, const cuuint64_t*, const cuuint64_t*,
                             const cuuint32_t*, const cuuint32_t*, CUtensorMapInterleave, CUtensorMapSwizzle,
                             CUtensorMapL2promotion, CUtensorMapFloatOOBfill);

void make_map(EncodeFn enc, CUtensorMap* m, void* p, unsigned rows, unsigned cols, unsigned br, unsigned bg) {
    cuuint64_t gd[3] = {64, rows, cols / 64};
    cuuint64_t gs[2] = {(cuuint64_t)cols * 2, 128};
    cuuint32_t bx[3] = {64, br, bg};
    cuuint32_t es[3] = {1, 1, 1};
    enc(m, CU_TENSOR_MAP_DATA_TYPE_BFLOAT16, 3, p, gd, gs, bx, es, CU_TENSOR_MAP_INTERLEAVE_NONE,
        CU_TENSOR_MAP_SWIZZLE_128B, CU_TENSOR_MAP_L2_PROMOTION_L2_128B, CU_TENSOR_MAP_FLOAT_OOB_FILL_NONE);
}

}

extern "C" void kernel_launch(void* const* d_in, const int* in_sizes, int n_in, void* d_out, int out_size) {
    static EncodeFn enc = nullptr;
    if (!enc) {
        void* fn = nullptr;
        cudaDriverEntryPointQueryResult qr;
        cudaGetDriverEntryPoint("cuTensorMapEncodeTiled", &fn, cudaEnableDefault, &qr);
        enc = (EncodeFn)fn;
        cudaFuncSetAttribute(fused_decode_kernel, cudaFuncAttributeMaxDynamicSharedMemorySize, SMEM_BYTES);
    }
    Maps maps;
    make_map(enc, &maps.wqB, d_in[9], 512, 4096, 64, 2);
    make_map(enc, &maps.wqA, d_in[2], 512, 4096, 64, 2);
    make_map(enc, &maps.wuk, d_in[3], 512, 4096, 64, 2);
    make_map(enc, &maps.wuv, d_in[4], 512, 4096, 64, 2);
    for (int k = 0; k < 2; k++) {
        cuuint64_t gd[3] = {512, 128, 32};
        cuuint64_t gs[2] = {1024, 131072};
        cuuint32_t bx[3] = {32, 128, 1};
        cuuint32_t es[3] = {1, 1, 1};
        enc(&maps.woB + k, CU_TENSOR_MAP_DATA_TYPE_BFLOAT16, 3, d_in[k ? 5 : 10], gd, gs, bx, es, CU_TENSOR_MAP_INTERLEAVE_NONE,
            CU_TENSOR_MAP_SWIZZLE_64B, CU_TENSOR_MAP_L2_PROMOTION_L2_128B, CU_TENSOR_MAP_FLOAT_OOB_FILL_NONE);
    }
    make_map(enc, &maps.ckv, d_in[1], 8192, 512, 16, 8);
    {
        void* p = nullptr;
        cudaGetSymbolAddress(&p, g_ctxp);
        cuuint64_t gd[3] = {128, 128, 128};
        cuuint64_t gs[2] = {256, 32768};
        cuuint32_t bx[3] = {128, 1, 128 / ST_SPLIT};
        cuuint32_t es[3] = {1, 1, 1};
        enc(&maps.ctxp, CU_TENSOR_MAP_DATA_TYPE_BFLOAT16, 3, p, gd, gs, bx, es, CU_TENSOR_MAP_INTERLEAVE_NONE,
            CU_TENSOR_MAP_SWIZZLE_NONE, CU_TENSOR_MAP_L2_PROMOTION_NONE, CU_TENSOR_MAP_FLOAT_OOB_FILL_NONE);
    }
    fused_decode_kernel<<<NCTA, NTHREADS, SMEM_BYTES>>>((const char*)d_in[9], maps, (const char*)d_in[7], (const char*)d_in[8],
                                                         (const __nv_bfloat16*)d_in[0], (const __nv_bfloat16*)d_in[6],
                                                         (__nv_bfloat16*)d_out, 0u);
}
```

```cpp
#include <cuda_runtime.h>
#include <cuda.h>
#include <cuda_bf16.h>
#include <stdint.h>

#define RING 7
#define WIN 4
#define WHI 5
#define THETA 64
#define END_V 40
#define GATE_W 192
#define OP_CLK16 147
#define BOX_FIRST 250
#define BOX_CLK 600
#define TAIL_LO 3
#define TAIL_HI 7
#define POLL_DELAY 2500
#define POLL_DELAY2 3000
#define ST_SPLIT 32
#define ST_GAP 200
#define G_SPLIT 8
#define G_GAP 250
#define BACKOFF 200
#define BACKOFF2 100

namespace {

constexpr int NCTA = 128;
constexpr int NTHREADS = 448;
constexpr uint32_t CH = 16384;
constexpr int NTILE = 32;
constexpr int RUN = 4;

constexpr uint32_t OFF_RING = 0;
constexpr uint32_t OFF_S0 = RING * CH;
constexpr uint32_t OFF_S1 = OFF_S0 + 2 * CH;
constexpr uint32_t OFF_S2 = OFF_S1 + 2 * CH;
constexpr uint32_t OFF_P = OFF_S2 + 2 * CH;
constexpr uint32_t OFF_SC = OFF_P + 4096;
constexpr uint32_t VROW = 272;
constexpr uint32_t OFF_XB = OFF_SC + 8704;
constexpr uint32_t OFF_XA = OFF_XB + 2 * VROW;
constexpr uint32_t OFF_QA = OFF_XA + 2 * VROW;
constexpr uint32_t OFF_QS = OFF_QA + 2 * VROW;
constexpr uint32_t OFF_CC = OFF_QS + 2 * VROW;
constexpr uint32_t OFF_CA = OFF_P;
constexpr uint32_t OFF_QB = OFF_CC + 4 * VROW;
constexpr uint32_t OFF_LSE = OFF_QB + 512;
constexpr uint32_t OFF_ML = OFF_LSE + 512;
constexpr uint32_t OFF_TAG = OFF_ML + 64;
constexpr uint32_t OFF_NOW = OFF_TAG + 4;
constexpr uint32_t OFF_WIN = OFF_TAG + 8;
constexpr uint32_t OFF_BAR = OFF_TAG + 16;
constexpr int B_EMPTY = RING;
constexpr int B_WQB = 2 * RING;
constexpr int B_WQA = B_WQB + 2;
constexpr int B_WUK = B_WQA + 2;
constexpr int B_WUV = B_WUK + 2;
constexpr int B_CKV = B_WUV + 2;
constexpr int B_WO = B_CKV + 4;
constexpr int B_FREE = B_WO + 8;
constexpr int B_GATH = B_FREE + 1;
constexpr int B_S2 = B_GATH + 1;
constexpr int NBAR = B_S2 + 1;
constexpr uint32_t TS_OFF = OFF_BAR + NBAR * 8;
constexpr uint32_t SMEM_USED = TS_OFF;
constexpr uint32_t SMEM_BYTES = SMEM_USED + 1024;
static_assert(SMEM_BYTES <= 232448, "smem");
static_assert(RING >= RUN && RING >= WHI && WHI >= WIN && WHI >= 4 && WIN >= 3 && WIN <= 6 && TAIL_HI >= 4, "windows");

constexpr float LOG2E = 1.4426950408889634f;
constexpr float SCALE = 0.08838834764831845f;
#define SPIN_LOG 22
constexpr uint32_t SPIN_MAX = 1u << SPIN_LOG;

struct Maps { CUtensorMap wqB, wqA, wuk, wuv, woB, woA, ckv, ctxp; };

__device__ __align__(256) unsigned g_cnt[32];
__device__ __align__(256) ulonglong2 g_e1[2][NCTA][128];
__device__ __align__(256) uint4 g_qabs[2 * 32 * 64];
__device__ __align__(256) uint4 g_ctxp[NCTA * 128 * 16];
__device__ __align__(256) float4 g_lse[32 * 32];
__device__ __align__(256) uint4 g_e4[NCTA][64];
__device__ __align__(256) uint4 g_e5[NCTA][32];
__device__ __align__(256) uint4 g_l5[32][8];
constexpr uint32_t EMPTY = 0xffffffffu;

#define TS(k) do {} while (0)

__device__ __forceinline__ void mbar_init(uint32_t b, int c) { asm volatile("mbarrier.init.shared::cta.b64 [%0], %1;" ::"r"(b), "r"(c) : "memory"); }
__device__ __forceinline__ void mbar_expect(uint32_t b, uint32_t bytes) { asm volatile("mbarrier.arrive.expect_tx.shared::cta.b64 _, [%0], %1;" ::"r"(b), "r"(bytes) : "memory"); }
__device__ __forceinline__ void mbar_arrive(uint32_t b) { asm volatile("mbarrier.arrive.shared::cta.b64 _, [%0];" ::"r"(b) : "memory"); }
__device__ __forceinline__ void mbar_wait(uint32_t b, uint32_t ph) {
    asm volatile("{\n.reg .pred p;\n.reg .u32 n;\nmov.u32 n, 0;\n"
                 "W:\nmbarrier.try_wait.parity.shared::cta.b64 p, [%0], %1;\n@p bra D;\n"
                 "add.u32 n, n, 1;\nsetp.le.u32 p, n, %2;\n@p bra W;\ntrap;\nD:\n}" ::"r"(b), "r"(ph), "n"(SPIN_MAX) : "memory");
}
__device__ __forceinline__ uint32_t mbar_test(uint32_t b, uint32_t ph) {
    uint32_t ok;
    asm volatile("{\n.reg .pred p;\nmbarrier.test_wait.parity.shared::cta.b64 p, [%1], %2;\nselp.u32 %0, 1, 0, p;\n}" : "=r"(ok) : "r"(b), "r"(ph) : "memory");
    return ok;
}
__device__ __forceinline__ void bulk1d(uint32_t dst, const void* src, uint32_t bar, uint64_t pol) {
    asm volatile("cp.async.bulk.shared::cluster.global.mbarrier::complete_tx::bytes.L2::cache_hint [%0], [%1], %2, [%3], %4;"
                 ::"r"(dst), "l"(src), "n"(CH), "r"(bar), "l"(pol) : "memory");
}
__device__ __forceinline__ void bulk1d_n(uint32_t dst, const void* src, uint32_t bytes, uint32_t bar) {
    asm volatile("cp.async.bulk.shared::cluster.global.mbarrier::complete_tx::bytes [%0], [%1], %2, [%3];"
                 ::"r"(dst), "l"(src), "r"(bytes), "r"(bar) : "memory");
}
__device__ __forceinline__ void tma3d(uint32_t dst, const CUtensorMap* map, int c1, int c2, uint32_t bar, uint64_t pol, int c0 = 0) {
    asm volatile("cp.async.bulk.tensor.3d.shared::cluster.global.mbarrier::complete_tx::bytes.L2::cache_hint [%0], [%1, {%3,%4,%5}], [%2], %6;"
                 ::"r"(dst), "l"(map), "r"(bar), "r"(c0), "r"(c1), "r"(c2), "l"(pol) : "memory");
}
__device__ __forceinline__ void bar_sync(int id, int n) { asm volatile("barrier.cta.sync %0, %1;" ::"r"(id), "r"(n) : "memory"); }
__device__ __forceinline__ void bar_arrive(int id, int n) { asm volatile("barrier.cta.arrive %0, %1;" ::"r"(id), "r"(n) : "memory"); }
__device__ __forceinline__ void ldsm4(uint32_t (&r)[4], uint32_t a) {
    asm volatile("ldmatrix.sync.aligned.m8n8.x4.shared.b16 {%0,%1,%2,%3}, [%4];" : "=r"(r[0]), "=r"(r[1]), "=r"(r[2]), "=r"(r[3]) : "r"(a) : "memory");
}
__device__ __forceinline__ void ldsm4t(uint32_t (&r)[4], uint32_t a) {
    asm volatile("ldmatrix.sync.aligned.m8n8.x4.trans.shared.b16 {%0,%1,%2,%3}, [%4];" : "=r"(r[0]), "=r"(r[1]), "=r"(r[2]), "=r"(r[3]) : "r"(a) : "memory");
}
__device__ __forceinline__ bool box_load(uint32_t (&r)[4], uint32_t (&s)[4], uint32_t (&u)[4], uint32_t (&v)[4], uint32_t bar, uint32_t a) {
    uint32_t ok;
    asm volatile("{\n.reg .pred p;\nmbarrier.try_wait.parity.shared::cta.b64 p, [%17], 0;\n"
                 "@p ldmatrix.sync.aligned.m8n8.x4.trans.shared.b16 {%0,%1,%2,%3}, [%18];\n"
                 "@p ldmatrix.sync.aligned.m8n8.x4.trans.shared.b16 {%4,%5,%6,%7}, [%18 + 2048];\n"
                 "@p ldmatrix.sync.aligned.m8n8.x4.trans.shared.b16 {%8,%9,%10,%11}, [%18 + 4096];\n"
                 "@p ldmatrix.sync.aligned.m8n8.x4.trans.shared.b16 {%12,%13,%14,%15}, [%18 + 6144];\n"
                 "selp.u32 %16, 1, 0, p;\n}"
                 : "+r"(r[0]), "+r"(r[1]), "+r"(r[2]), "+r"(r[3]), "+r"(s[0]), "+r"(s[1]), "+r"(s[2]), "+r"(s[3]),
                   "+r"(u[0]), "+r"(u[1]), "+r"(u[2]), "+r"(u[3]), "+r"(v[0]), "+r"(v[1]), "+r"(v[2]), "+r"(v[3]), "=r"(ok)
                 : "r"(bar), "r"(a) : "memory");
    return ok != 0;
}
__device__ __forceinline__ void mma(float (&c)[4], const uint32_t (&a)[4], uint32_t b0, uint32_t b1) {
    asm volatile("mma.sync.aligned.m16n8k16.row.col.f32.bf16.bf16.f32 {%0,%1,%2,%3}, {%4,%5,%6,%7}, {%8,%9}, {%0,%1,%2,%3};"
                 : "+f"(c[0]), "+f"(c[1]), "+f"(c[2]), "+f"(c[3]) : "r"(a[0]), "r"(a[1]), "r"(a[2]), "r"(a[3]), "r"(b0), "r"(b1));
}
__device__ __forceinline__ uint32_t lds32(uint32_t a) { uint32_t v; asm volatile("ld.shared.b32 %0, [%1];" : "=r"(v) : "r"(a) : "memory"); return v; }
__device__ __forceinline__ uint32_t ldsv(uint32_t a) { uint32_t v; asm volatile("ld.volatile.shared.b32 %0, [%1];" : "=r"(v) : "r"(a) : "memory"); return v; }
__device__ __forceinline__ void stsv(uint32_t a, uint32_t v) { asm volatile("st.volatile.shared.b32 [%0], %1;" ::"r"(a), "r"(v) : "memory"); }
__device__ __forceinline__ float ldsf(uint32_t a) { float v; asm volatile("ld.shared.f32 %0, [%1];" : "=f"(v) : "r"(a) : "memory"); return v; }
__device__ __forceinline__ uint4 lds128(uint32_t a) { uint4 v; asm volatile("ld.shared.v4.b32 {%0,%1,%2,%3}, [%4];" : "=r"(v.x), "=r"(v.y), "=r"(v.z), "=r"(v.w) : "r"(a) : "memory"); return v; }
__device__ __forceinline__ void sts16(uint32_t a, uint16_t v) { asm volatile("st.shared.b16 [%0], %1;" ::"r"(a), "h"(v) : "memory"); }
__device__ __forceinline__ void sts32(uint32_t a, uint32_t v) { asm volatile("st.shared.b32 [%0], %1;" ::"r"(a), "r"(v) : "memory"); }
__device__ __forceinline__ void stsf2(uint32_t a, float x, float y) { asm volatile("st.shared.v2.f32 [%0], {%1,%2};" ::"r"(a), "f"(x), "f"(y) : "memory"); }
__device__ __forceinline__ void sts128(uint32_t a, uint4 v) { asm volatile("st.shared.v4.b32 [%0], {%1,%2,%3,%4};" ::"r"(a), "r"(v.x), "r"(v.y), "r"(v.z), "r"(v.w) : "memory"); }
__device__ __forceinline__ uint16_t f2bf(float x) { return __bfloat16_as_ushort(__float2bfloat16_rn(x)); }
__device__ __forceinline__ float bfround(float x) { return __bfloat162float(__float2bfloat16_rn(x)); }
__device__ __forceinline__ uint32_t pack2(float lo, float hi) { uint32_t r; asm("cvt.rn.bf16x2.f32 %0, %1, %2;" : "=r"(r) : "f"(hi), "f"(lo)); return r; }
__device__ __forceinline__ float ex2(float x) { float r; asm("ex2.approx.ftz.f32 %0, %1;" : "=f"(r) : "f"(x)); return r; }
__device__ __forceinline__ float lg2(float x) { float r; asm("lg2.approx.ftz.f32 %0, %1;" : "=f"(r) : "f"(x)); return r; }

__device__ __forceinline__ float rcp(float x) { float r; asm("rcp.approx.ftz.f32 %0, %1;" : "=f"(r) : "f"(x)); return r; }

__device__ __forceinline__ uint32_t clock_lo() { uint32_t t; asm volatile("mov.u32 %0, %clock;" : "=r"(t) :: "memory"); return t; }
__device__ __forceinline__ void sleep_ns(uint32_t ns) {
    const uint32_t t0 = clock_lo();
    do { __nanosleep(200); } while (clock_lo() - t0 < 2 * ns);
}

__device__ __forceinline__ void ll_store2(ulonglong2* p, float a, float b, uint32_t tag) {
    unsigned long long x = ((unsigned long long)tag << 32) | __float_as_uint(a);
    unsigned long long y = ((unsigned long long)tag << 32) | __float_as_uint(b);
    asm volatile("st.relaxed.gpu.global.v2.b64 [%0], {%1,%2};" ::"l"(p), "l"(x), "l"(y) : "memory");
}
__device__ __forceinline__ void ll_ld2(const void* p, unsigned long long& x, unsigned long long& y) {
    asm volatile("ld.relaxed.gpu.global.v2.b64 {%0,%1}, [%2];" : "=l"(x), "=l"(y) : "l"(p) : "memory");
}
__device__ __forceinline__ void ll_gather4(const ulonglong2* p, uint32_t tag, float& r0, float& r1) {
    unsigned long long x[4], y[4]; uint32_t it = 0;
    while (true) {
        bool ok = true;
#pragma unroll
        for (int k = 0; k < 4; k++) ll_ld2(p + k * 128, x[k], y[k]);
#pragma unroll
        for (int k = 0; k < 4; k++) ok = ok && (uint32_t)(x[k] >> 32) == tag && (uint32_t)(y[k] >> 32) == tag;
        if (ok) break;
        if (++it > SPIN_MAX) __trap();
        __nanosleep(BACKOFF);
    }
    r0 = (__uint_as_float((uint32_t)x[0]) + __uint_as_float((uint32_t)x[1])) + (__uint_as_float((uint32_t)x[2]) + __uint_as_float((uint32_t)x[3]));
    r1 = (__uint_as_float((uint32_t)y[0]) + __uint_as_float((uint32_t)y[1])) + (__uint_as_float((uint32_t)y[2]) + __uint_as_float((uint32_t)y[3]));
}
__device__ __forceinline__ void cnt_rendezvous(unsigned* c, uint32_t target, int tsk) {
    TS(tsk);
    asm volatile("red.release.gpu.global.add.u32 [%0], 1;" ::"l"(c) : "memory");
    if (tsk == 18) TS(tsk + 1);
    uint32_t v, it = 0;
    while (true) {
        asm volatile("ld.acquire.gpu.global.u32 %0, [%1];" : "=r"(v) : "l"(c) : "memory");
        if ((int)(v - target) >= 0) break;
        if (++it > SPIN_MAX) __trap();
        __nanosleep(BACKOFF);
    }
    asm volatile("fence.proxy.async.global;" ::: "memory");
}

__device__ __forceinline__ void matvec_loadA(uint32_t (&a)[8][4], uint32_t tile, uint32_t bar, int w, int lane) {
    const int i = lane >> 3, rr = lane & 7, chunk = 2 * w + (i & 1);
    const uint32_t a0 = tile + (chunk >> 3) * 8192 + (rr + 8 * (i >> 1)) * 128 + (((chunk & 7) ^ rr) << 4);
#pragma unroll
    for (int hh = 0; hh < 2; hh++) {
        mbar_wait(bar + hh * 8, 0);
#pragma unroll
        for (int k = 0; k < 4; k++) ldsm4t(a[hh * 4 + k], a0 + hh * CH + k * 2048);
    }
}
__device__ __forceinline__ void matvec_mma(float (&c)[4], const uint32_t (&a)[8][4], uint32_t vec, int nvec, int lane) {
    const uint32_t va = vec + (lane & (nvec - 1)) * VROW + (lane >> 3) * 16;
    float d[4][4];
#pragma unroll
    for (int q = 0; q < 4; q++) {
        uint32_t b[4];
        ldsm4(b, va + q * 64);
        d[q][0] = d[q][1] = d[q][2] = d[q][3] = 0.f;
        mma(d[q], a[2 * q], b[0], b[1]);
        mma(d[q], a[2 * q + 1], b[2], b[3]);
    }
#pragma unroll
    for (int k = 0; k < 4; k++) c[k] = (d[0][k] + d[1][k]) + (d[2][k] + d[3][k]);
}
__device__ __forceinline__ void matvecT(float (&c)[4], uint32_t tile, uint32_t vec, int nvec, uint32_t bar, int w, int lane) {
    uint32_t a[8][4];
    matvec_loadA(a, tile, bar, w, lane);
    matvec_mma(c, a, vec, nvec, lane);
}
template <class T> __device__ __forceinline__ T* pin(T* p) { asm volatile("" : "+l"(p)); return p; }
__device__ __forceinline__ void mail_put(void* p, uint32_t v) { asm volatile("st.relaxed.gpu.global.b32 [%0], %1;" ::"l"(p), "r"(v) : "memory"); }
__device__ __forceinline__ void mail_put(void* p, float v) { mail_put(p, __float_as_uint(v)); }
__device__ __forceinline__ void out_add(__nv_bfloat16* p, float x, float y) {
    asm volatile("red.relaxed.gpu.global.add.noftz.bf16x2 [%0], %1;" ::"l"(p), "r"(pack2(x, y)) : "memory");
}
__device__ __forceinline__ bool mail_missing(const uint4& v) { return v.x == EMPTY || v.y == EMPTY || v.z == EMPTY || v.w == EMPTY; }
__device__ __forceinline__ void mail_get(uint4& v, const uint4* p, bool need = true) {
    asm volatile("{\n.reg .pred q;\nsetp.ne.u32 q, %5, 0;\n@q ld.relaxed.gpu.global.v4.b32 {%0,%1,%2,%3}, [%4];\n}"
                 : "+r"(v.x), "+r"(v.y), "+r"(v.z), "+r"(v.w) : "l"(p), "r"((uint32_t)need) : "memory");
}
__device__ __forceinline__ void sts64(uint32_t a, uint32_t x, uint32_t y) { asm volatile("st.shared.v2.b32 [%0], {%1,%2};" ::"r"(a), "r"(x), "r"(y) : "memory"); }
__device__ __forceinline__ float2 ldsf2(uint32_t a) { float2 v; asm volatile("ld.shared.v2.f32 {%0,%1}, [%2];" : "=f"(v.x), "=f"(v.y) : "r"(a) : "memory"); return v; }

__global__ void __launch_bounds__(NTHREADS, 1)
fused_decode_kernel(const char* __restrict__ wqraw, const __grid_constant__ Maps maps, const char* __restrict__ Kc, const char* __restrict__ Vc,
                    const __nv_bfloat16* __restrict__ xA, const __nv_bfloat16* __restrict__ xB,
                    __nv_bfloat16* __restrict__ out, const uint32_t zero) {
    if (threadIdx.x == 0) asm volatile("cp.async.bulk.prefetch.L2.global [%0], 32768;" ::"l"(wqraw + (size_t)blockIdx.x * 32768u) : "memory");
    asm volatile("nanosleep.u32 60;" ::: "memory");
    asm volatile("barrier.cta.sync.aligned 7, %0;" ::"n"(NTHREADS) : "memory");
    asm volatile("{\n.reg .pred p;\n.reg .u32 s;\nmov.u32 s, %smid;\nsetp.eq.u32 p, s, 0xffff;\n@p exit;\n}" ::: "memory");
    extern __shared__ char smem_raw[];
    const uint32_t sm = ((uint32_t)__cvta_generic_to_shared(smem_raw) + 1023u) & ~1023u;
    const uint32_t bars = sm + OFF_BAR;
    const int cta = blockIdx.x, h = cta >> 2, j = cta & 3;
    const int col = ((h >> 3) * 4 + j) * 32;
    uint64_t pol = 0;
    if (threadIdx.x == 0) {
        TS(0);
        asm volatile("createpolicy.fractional.L2::evict_first.b64 %0, 1.0;" : "=l"(pol));
#pragma unroll
        for (int i = 0; i < WIN; i++) mbar_init(bars + (B_WQB + i) * 8, 1);
        asm volatile("fence.mbarrier_init.release.cluster;" ::: "memory");
#pragma unroll
        for (int i = 0; i < WIN; i++) {
            mbar_expect(bars + (B_WQB + i) * 8, CH);
            tma3d(sm + OFF_S0 + i * CH, &maps.wqB + (i >> 1), j * 128 + (i & 1) * 64, h * 2, bars + (B_WQB + i) * 8, pol);
        }
    }
    const int tid = threadIdx.x < 64 ? threadIdx.x + 384 : threadIdx.x - 64, warp = tid >> 5, lane = tid & 31;

    if (warp == 12) {
        const size_t kvoff = (size_t)cta * (NTILE / 2 * CH);
        const char* kp = Kc + kvoff;
        const char* vp = Vc + kvoff;
        __syncwarp();
        bar_arrive(0, NTHREADS);
        bar_sync(3, 64);
        if (lane == 0) {
            uint32_t pb[WHI];
#pragma unroll
            for (int i = 0; i < WHI; i++) pb[i] = i < WHI - WIN ? (bars + B_WO * 8) | 1u : bars + (B_WQB + i - (WHI - WIN)) * 8;
            auto pace = [&](uint32_t bar, uint32_t par) {
                uint32_t it = 0;
                while (true) {
                    const uint32_t win = ldsv(sm + OFF_WIN);
                    uint32_t busy = 0;
#pragma unroll
                    for (int i = 0; i < WHI; i++) busy += mbar_test(pb[i] & ~1u, pb[i] & 1u) ^ 1u;
                    if (busy < win) break;
                    if (++it > SPIN_MAX) __trap();
                }
#pragma unroll
                for (int i = 0; i + 1 < WHI; i++) pb[i] = pb[i + 1];
                pb[WHI - 1] = bar | par;
            };
            auto side = [&](const CUtensorMap* m, uint32_t dst, int bidx, int c1, int c2) {
                const uint32_t bar = bars + bidx * 8;
                pace(bar, 0);
                mbar_expect(bar, CH);
                tma3d(dst, m, c1, c2, bar, pol);
            };
#pragma unroll 1
            for (int i = WIN; i < 6; i++)
                side(&maps.wqB + (i >> 1), sm + OFF_S0 + i * CH, B_WQB + i, j * 128 + (i & 1) * 64, h * 2);
            TS(1);
            uint32_t slot = 0, use = 0, tend = 0;
            int nuv = 0;
#pragma unroll 1
            for (int n = 0; n < 2 * NTILE; n++) {
                if (n == RING) {
                    mbar_wait(bars + B_FREE * 8, 0);
#pragma unroll 1
                    for (int q = 0; q < 4; q++) side(&maps.ckv, sm + OFF_S0 + q * CH, B_CKV + q, cta * 64 + q * 16, 0);
                }
                if (nuv < 2 && n > RING && (n >= 2 * NTILE - 8 || mbar_test(bars + B_FREE * 8, 1))) {
                    mbar_wait(bars + B_FREE * 8, 1);
                    side(&maps.wuv, sm + OFF_S1 + nuv * CH, B_WUV + nuv, j * 128 + nuv * 64, h * 2);
                    nuv++;
                }
                const uint32_t fb = bars + slot * 8;
                pace(fb, use & 1);
                mbar_wait(fb + B_EMPTY * 8, (use & 1) ^ 1);
                mbar_expect(fb, CH);
                bulk1d(sm + OFF_RING + slot * CH, ((n & RUN) ? vp : kp) + (size_t)(n / NTILE * (NCTA * NTILE / 2) + n % NTILE / (2 * RUN) * RUN + n % RUN) * CH, fb, pol);
                stsv(sm + OFF_NOW, n + 1);
                if (((n + cta) & 3) == 0) {
                    if (n >= 2 * NTILE - 6 && n < 2 * NTILE - 2) {
                        const uint32_t left = -atomicAdd(&g_cnt[2], 4u) & (NCTA * 2 * NTILE - 1);
                        stsv(sm + OFF_NOW, n + 1 + (left & zero));
                        tend = clock_lo() + left * OP_CLK16 / 16;
                    } else {
                        asm volatile("red.relaxed.gpu.global.add.u32 [%0], 4;" ::"l"(&g_cnt[2]) : "memory");
                    }
                }
                if (++slot == RING) { slot = 0; use++; }
            }
            TS(2);
            mbar_wait(bars + B_FREE * 8, 0);
#pragma unroll 1
            for (int i = 0; i < 8; i++) {
                uint32_t it = 0;
                while (true) {
                    uint32_t busy = i;
#pragma unroll
                    for (int k = 0; k < 4; k++) busy += 2 * (mbar_test(pb[WHI - 4 + k] & ~1u, pb[WHI - 4 + k] & 1u) ^ 1u);
#pragma unroll
                    for (int k = 0; k < 5; k++) busy -= mbar_test(bars + (B_WO + k) * 8, 0);
                    const uint32_t due = tend - BOX_FIRST + i * BOX_CLK;
                    if (busy < TAIL_LO) break;
                    if (busy < TAIL_HI && (int)(due - clock_lo()) < 400) {
                        while ((int)(due - clock_lo()) > 0) {}
                        break;
                    }
                    if (++it > SPIN_MAX) __trap();
                }
                mbar_expect(bars + (B_WO + i) * 8, CH / 2);
                tma3d(sm + OFF_S0 + i * (CH / 2), &maps.woB + (i >> 2), 0, (i & 3) * 8 + (h & 7), bars + (B_WO + i) * 8, pol, col);
            }
            TS(3);
        }
    } else if (warp == 13) {
        if (lane == 0) {
#pragma unroll
            for (int i = 0; i < NBAR; i++)
                if (i < B_WQB || i >= B_WQB + WIN)
                    mbar_init(bars + i * 8, i == B_FREE ? 8 : (i >= B_EMPTY && i < B_EMPTY + RING) ? 4 : 1);
            asm volatile("fence.mbarrier_init.release.cluster;" ::: "memory");
#pragma unroll
            for (int i = 2; i < 8; i++) asm volatile("prefetch.tensormap [%0];" ::"l"(&maps.wqB + i) : "memory");
            stsv(sm + OFF_NOW, 0); stsv(sm + OFF_WIN, WIN);
        }
        __syncwarp();
        bar_arrive(3, 64);
        bar_sync(0, NTHREADS);
        if (lane == 0) {
            const uint32_t base = (lds32(sm + OFF_TAG) - 1u) * (NCTA * 2 * NTILE);
            mbar_wait(bars + (B_WUK + 1) * 8, 0);
            uint32_t it = 0;
            while (true) {
                const uint32_t n = ldsv(sm + OFF_NOW);
                uint32_t v;
                asm volatile("ld.relaxed.gpu.global.u32 %0, [%1];" : "=r"(v) : "l"(&g_cnt[2]) : "memory");
                v -= base;
                if (v >= NCTA * 2 * NTILE - GATE_W) break;
                const int diff = (int)(n * NCTA) - (int)v;
                stsv(sm + OFF_WIN, diff < -THETA ? WHI : WIN - (diff > THETA) - (v >= NCTA * END_V));
                if (++it > SPIN_MAX) __trap();
                __nanosleep(BACKOFF2);
            }
            stsv(sm + OFF_WIN, WHI);
            TS(24);
        }
    } else if (warp < 4) {
        const int g = lane >> 2, t = lane & 3, i = lane >> 3, rr = lane & 7;
        if (tid == 0) {
            unsigned e;
            asm volatile("ld.relaxed.gpu.global.u32 %0, [%1];" : "=r"(e) : "l"(&g_cnt[1]) : "memory");
            sts32(sm + OFF_TAG, (e >> 7) + 1u);
        }
        bar_sync(0, NTHREADS);
        const uint32_t tag = lds32(sm + OFF_TAG);
        {
            mbar_wait(bars + 8, 0);
            float q0, q1;
            ll_gather4(&g_e1[0][h * 4][tid], tag, q0, q1);
            sts16(sm + OFF_QB + tid * 2, f2bf(q0)); sts16(sm + OFF_QB + 256 + tid * 2, f2bf(q1));
        }
        bar_sync(1, 128);
        if (tid == 0) TS(4);
        uint32_t qf[8][2];
        float acc[8][4], m, l;
        auto start = [&](int b) {
#pragma unroll
            for (int c = 0; c < 8; c++) {
                const uint32_t a = sm + OFF_QB + b * 256 + (((c + g) & 7) * 8 + 2 * t) * 2;
                qf[c][0] = lds32(a); qf[c][1] = lds32(a + 128);
                acc[c][0] = acc[c][1] = acc[c][2] = acc[c][3] = 0.f;
            }
            m = -INFINITY; l = 0.f;
        };
        auto stats = [&](int b) {
#pragma unroll
            for (int o = 16; o; o >>= 1) l += __shfl_xor_sync(0xffffffffu, l, o);
            if (lane == 0) stsf2(sm + OFF_ML + b * 32 + warp * 8, m, l);
        };
        auto quad_sum = [&](float (&r)[4]) {
            float v[2][8];
#pragma unroll
            for (int c = 0; c < 8; c++) { v[0][c] = acc[c][0] + acc[(c + 7) & 7][1]; v[1][c] = acc[c][2] + acc[(c + 7) & 7][3]; }
#pragma unroll
            for (int c = 0; c < 4; c++) { v[0][c] += __shfl_xor_sync(0xffffffffu, v[0][c + 4], 2); v[1][c] += __shfl_xor_sync(0xffffffffu, v[1][c + 4], 2); }
            const int src = (lane & ~3) | ((lane + 3) & 3);
#pragma unroll
            for (int c = 0; c < 4; c++) r[c] = v[c >> 1][c & 1] + __shfl_sync(0xffffffffu, v[c >> 1][(c & 1) + 2], src);
        };
        auto factor = [&](int b, float& lse) {
            bar_sync(1, 128);
            const uint4 ml0 = lds128(sm + OFF_ML + b * 32), ml1 = lds128(sm + OFF_ML + b * 32 + 16);
            const float m0 = __uint_as_float(ml0.x), m1 = __uint_as_float(ml0.z), m2 = __uint_as_float(ml1.x), m3 = __uint_as_float(ml1.z);
            const float M = fmaxf(fmaxf(m0, m1), fmaxf(m2, m3));
            const float L = (ex2((m0 - M) * LOG2E) * __uint_as_float(ml0.y) + ex2((m1 - M) * LOG2E) * __uint_as_float(ml0.w))
                          + (ex2((m2 - M) * LOG2E) * __uint_as_float(ml1.y) + ex2((m3 - M) * LOG2E) * __uint_as_float(ml1.w));
            lse = M * LOG2E + lg2(L);
            return ex2((ldsf(sm + OFF_ML + b * 32 + warp * 8) - M) * LOG2E) * rcp(L);
        };
        auto publish = [&](uint32_t* dst, const float (&r)[4], float f) {
            const uint32_t wa = sm + OFF_S2 + warp * 640 + (t * 16 + (t >> 1) * 8 + g) * 4;
            const uint32_t ra = sm + OFF_S2 + ((tid >> 4 & 1) * 40 + (tid & 2) * 40 + (tid >> 5 & 1) * 16 + (tid & 1) * 8 + (tid >> 2 & 3) * 2) * 4;
#pragma unroll
            for (int c = 0; c < 4; c++) sts32(wa + (c >> 1) * 320 + (c & 1) * 32, __float_as_uint(r[c] * f));
            bar_sync(1, 128);
            const float2 r0 = ldsf2(ra), r1 = ldsf2(ra + 640), r2 = ldsf2(ra + 1280), r3 = ldsf2(ra + 1920);
            if (tid < 64) mail_put(dst, pack2((r0.x + r1.x) + (r2.x + r3.x), (r0.y + r1.y) + (r2.y + r3.y)));
        };
        float o0[4] = {0.f, 0.f, 0.f, 0.f};
        start(0);
        const bool diag = (t == (g >> 1));
        const uint32_t krow = sm + OFF_RING + (warp * 16 + rr + 8 * (i & 1)) * 256 + (i >> 1) * 128;
        const uint32_t vrow = sm + OFF_RING + (warp * 16 + rr + 8 * (i >> 1)) * 256 + (i & 1) * 128;
        uint32_t slot = 0, ph = 0;
        uint32_t a[8][4] = {}, b0[RUN], b1[RUN];
        auto release = [&]() {
            __syncwarp();
            if (lane == 0) mbar_arrive(bars + (B_EMPTY + slot) * 8 + ((a[0][0] | a[1][0] | a[2][0] | a[3][0] | a[4][0] | a[5][0] | a[6][0] | a[7][0]) & zero));
            if (++slot == RING) { slot = 0; ph ^= 1; }
        };
        auto load_v = [&]() {
            mbar_wait(bars + slot * 8, ph);
#pragma unroll
            for (int c = 0; c < 8; c++) ldsm4t(a[c], vrow + slot * CH + (((c + rr) & 7) << 4));
        };
#pragma unroll 1
        for (int run = 0;; run++) {
            float slo[RUN], shi[RUN], mx = -INFINITY;
#pragma unroll
            for (int u = 0; u < RUN; u++) {
                mbar_wait(bars + slot * 8, ph);
#pragma unroll
                for (int c = 0; c < 8; c++) ldsm4(a[c], krow + slot * CH + (((c + rr) & 7) << 4));
                release();
                float s0[4] = {0.f, 0.f, 0.f, 0.f}, s1[4] = {0.f, 0.f, 0.f, 0.f};
#pragma unroll
                for (int c = 0; c < 8; c += 2) { mma(s0, a[c], qf[c][0], qf[c][1]); mma(s1, a[c + 1], qf[c + 1][0], qf[c + 1][1]); }
                slo[u] = diag ? bfround(bfround((g & 1) ? s0[1] + s1[1] : s0[0] + s1[0]) * SCALE) : -INFINITY;
                shi[u] = diag ? bfround(bfround((g & 1) ? s0[3] + s1[3] : s0[2] + s1[2]) * SCALE) : -INFINITY;
                mx = fmaxf(mx, fmaxf(slo[u], shi[u]));
            }
            int key = __float_as_int(mx);
            key ^= (key >> 31) & 0x7fffffff;
            key = __reduce_max_sync(0xffffffffu, key);
            key ^= (key >> 31) & 0x7fffffff;
            const float mn = fmaxf(m, __int_as_float(key));
            const float alpha = ex2((m - mn) * LOG2E);
            m = mn;
            l *= alpha;
#pragma unroll
            for (int u = 0; u < RUN; u++) {
                const float plo = ex2((slo[u] - mn) * LOG2E), phi = ex2((shi[u] - mn) * LOG2E);
                l += plo + phi;
                b0[u] = (g & 1) ? pack2(0.f, plo) : pack2(plo, 0.f);
                b1[u] = (g & 1) ? pack2(0.f, phi) : pack2(phi, 0.f);
            }
#pragma unroll
            for (int c = 0; c < 8; c++) { acc[c][0] *= alpha; acc[c][1] *= alpha; acc[c][2] *= alpha; acc[c][3] *= alpha; }
            if (run == NTILE / RUN - 1) break;
#pragma unroll
            for (int u = 0; u < RUN; u++) {
                load_v();
                release();
#pragma unroll
                for (int c = 0; c < 8; c++) mma(acc[c], a[c], b0[u], b1[u]);
            }
            if (run == NTILE / RUN / 2 - 1) { stats(0); quad_sum(o0); start(1); }
            if (run == NTILE / RUN - 2) {
                float lse;
                mbar_wait(bars + B_S2 * 8, 0);
                publish((uint32_t*)g_e5[cta] + tid, o0, factor(0, lse));
                if (tid == 96) mail_put((float*)g_l5[h] + j, lse);
            }
        }
        {
            float lse;
            stats(1);
            const float f = factor(1, lse);
            uint32_t* const e5own = pin((uint32_t*)g_e5[cta] + 64 + tid);
            float* const l5own = pin((float*)g_l5[h] + 4 + j);
#pragma unroll
            for (int u = 0; u < RUN; u++) {
                load_v();
                if (++slot == RING) { slot = 0; ph ^= 1; }
                if (u == RUN - 1 && tid == 96) mail_put(l5own, lse);
#pragma unroll
                for (int c = 0; c < 8; c++) mma(acc[c], a[c], b0[u], b1[u]);
            }
            if (tid == 0) TS(5);
            quad_sum(o0);
            publish(e5own, o0, f);
        }
        if (tid == 0) TS(6);
        {
            uint32_t x[4][4][4];
            float d[4][4];
            bar_sync(4, 256 + 128);
#pragma unroll
            for (int k = 0; k < 16; k++) ldsm4(x[k >> 2][k & 3], sm + OFF_CA + ((k >> 2) * 2 + (lane & 1)) * VROW + (k & 3) * 64 + (i & 1) * 32 + (i >> 1) * 16);
            const uint32_t wa = sm + OFF_S1 + lane * 64 + ((warp ^ (rr >> 1)) << 4);
            __nv_bfloat16* const outp = pin(out + (g & 1) * 1024 + col + warp * 8 + t * 2);
            mbar_wait(bars + (B_WO + 4) * 8, 0);
            uint32_t it = 0;
            while (true) {
                bool ok = true;
#pragma unroll
                for (int k = 0; k < 4; k++) d[k][0] = d[k][1] = d[k][2] = d[k][3] = 0.f;
#pragma unroll
                for (int q = 0; q < 5; q++) {
                    if (q < 4) ok &= box_load(a[(q & 1) * 4], a[(q & 1) * 4 + 1], a[(q & 1) * 4 + 2], a[(q & 1) * 4 + 3], bars + (B_WO + 4 + q) * 8, wa + q * 8192);
#pragma unroll
                    for (int k = 0; k < (q ? 8 : 0); k++) {
                        const uint32_t (&u)[4] = a[(~q & 1) * 4 + (k >> 1)];
                        mma(d[k & 3], x[q - 1][k >> 1], u[(k & 1) * 2], u[(k & 1) * 2 + 1]);
                    }
                }
                asm volatile("{\n.reg .pred p;\nsetp.ne.u32 p, %0, 0;\n@p exit;\n}" ::"r"((uint32_t)(ok && lane >= 8)) : "memory");
                if (ok) break;
                if (++it > SPIN_MAX) __trap();
            }
            out_add(outp, (d[0][0] + d[1][2]) + (d[2][0] + d[3][2]), (d[0][1] + d[1][3]) + (d[2][1] + d[3][3]));
            if (tid == 0) TS(15);
        }
    } else {
        const int st = tid - 128, w = warp - 4;
        const int g = lane >> 2, t = lane & 3, i = lane >> 3, rr = lane & 7;
        if (t == 0) {
#pragma unroll
            for (int k = 0; k < 4; k++) ll_store2(&g_e1[k >> 1][cta][w * 16 + g + (k & 1) * 8], 0.f, 0.f, 0u);
        }
        if (st < 64) {
            const int which = st >> 5, b = (st >> 4) & 1, c = st & 15;
            const uint4 v = __ldg((const uint4*)((which ? xA : xB) + b * 512 + j * 128) + c);
            sts128(sm + OFF_XB + (which * 2 + b) * VROW + c * 16, v);
        }
        bar_sync(0, NTHREADS);
        const uint32_t tag = lds32(sm + OFF_TAG);
        float c[4];
#pragma unroll 1
        for (int which = 0; which < 2; which++) {
            matvecT(c, sm + OFF_S0 + which * 2 * CH, sm + OFF_XB + which * 2 * VROW, 2, bars + (B_WQB + which * 2) * 8, w, lane);
            if (t == 0) {
                ll_store2(&g_e1[which][cta][w * 16 + g], c[0], c[1], tag);
                ll_store2(&g_e1[which][cta][w * 16 + g + 8], c[2], c[3], tag);
            }
        }
        __syncwarp();
        if (lane == 0) mbar_arrive(bars + B_FREE * 8);
        if (st == 0) TS(8);
        if (st < 128) {
            float q0, q1;
            sleep_ns(POLL_DELAY);
            ll_gather4(&g_e1[1][h * 4][st], tag, q0, q1);
            sts16(sm + OFF_QA + st * 2, f2bf(q0)); sts16(sm + OFF_QA + VROW + st * 2, f2bf(q1));
        }
        bar_sync(2, 256);
        if (st == 0) TS(9);
        {
            const int row = w * 16 + rr + 8 * (i & 1);
            const uint32_t a0 = sm + OFF_S2 + (row >> 6) * CH + (row & 63) * 128;
            const uint32_t va = sm + OFF_QA + g * VROW + t * 4;
            float d[4] = {0.f, 0.f, 0.f, 0.f};
            c[0] = c[1] = c[2] = c[3] = 0.f;
            mbar_wait(bars + (B_WUK + (w >> 2)) * 8, 0);
#pragma unroll
            for (int ks = 0; ks < 8; ks++) {
                const int chunk = 2 * ks + (i >> 1);
                uint32_t a[4];
                ldsm4(a, a0 + (chunk >> 3) * 8192 + (((chunk & 7) ^ rr) << 4));
                const uint32_t b0 = (g < 2) ? lds32(va + ks * 32) : 0u, b1 = (g < 2) ? lds32(va + ks * 32 + 16) : 0u;
                if (ks & 1) mma(d, a, b0, b1); else mma(c, a, b0, b1);
            }
            if (t == 0) {
                const uint32_t qs = sm + OFF_QS + (w * 16 + g) * 2;
                sts16(qs, f2bf(c[0] + d[0])); sts16(qs + VROW, f2bf(c[1] + d[1]));
                sts16(qs + 16, f2bf(c[2] + d[2])); sts16(qs + VROW + 16, f2bf(c[3] + d[3]));
            }
            bar_sync(2, 256);
            if (w == 0) {
                const int b = lane >> 4, cc = lane & 15;
                g_qabs[(b * 32 + h) * 64 + ((j * 16 + cc) ^ (h & 7))] = lds128(sm + OFF_QS + b * VROW + cc * 16);
                __syncwarp();
                if (lane == 0) {
                    cnt_rendezvous(&g_cnt[0], tag * 128u, 18);
                    TS(10);
                    mbar_expect(bars + B_GATH * 8, 2 * CH);
                    bulk1d_n(sm + OFF_S2, g_qabs + (cta >> 6) * 2048, 2 * CH, bars + B_GATH * 8);
                }
                __syncwarp();
            }
        }
        mbar_wait(bars + B_GATH * 8, 0);
        if (st == 0) TS(11);
        {
            const int mt = w & 1, kg = w >> 1;
            const uint32_t qa = sm + OFF_S2 + (mt * 16 + rr + 8 * (i & 1)) * 1024;
            const uint32_t ka = sm + OFF_S0 + kg * CH + (rr + 8 * (i >> 1)) * 128;
            float s0[4] = {0.f, 0.f, 0.f, 0.f}, s1[4] = {0.f, 0.f, 0.f, 0.f};
            mbar_wait(bars + (B_CKV + kg) * 8, 0);
#pragma unroll 2
            for (int gq = 0; gq < 8; gq++) {
#pragma unroll
                for (int k4 = 0; k4 < 4; k4++) {
                    uint32_t a[4], b[4];
                    ldsm4(a, qa + gq * 128 + (((2 * k4 + (i >> 1)) ^ rr) << 4));
                    ldsm4(b, ka + gq * 2048 + (((2 * k4 + (i & 1)) ^ rr) << 4));
                    mma(s0, a, b[0], b[1]);
                    mma(s1, a, b[2], b[3]);
                }
            }
            const uint32_t sa = sm + OFF_SC + ((mt * 16 + g) * 68 + kg * 16 + 2 * t) * 4;
            stsf2(sa, s0[0], s0[1]); stsf2(sa + 32, s1[0], s1[1]);
            stsf2(sa + 8 * 68 * 4, s0[2], s0[3]); stsf2(sa + 8 * 68 * 4 + 32, s1[2], s1[3]);
        }
        bar_sync(2, 256);
        {
            const int head = w * 4 + i;
            const uint32_t sa = sm + OFF_SC + (head * 68 + rr * 8) * 4;
            const uint4 u0 = lds128(sa), u1 = lds128(sa + 16);
            float s[8] = {__uint_as_float(u0.x), __uint_as_float(u0.y), __uint_as_float(u0.z), __uint_as_float(u0.w),
                          __uint_as_float(u1.x), __uint_as_float(u1.y), __uint_as_float(u1.z), __uint_as_float(u1.w)};
            float mx = s[0];
#pragma unroll
            for (int k = 1; k < 8; k++) mx = fmaxf(mx, s[k]);
#pragma unroll
            for (int o = 1; o < 8; o <<= 1) mx = fmaxf(mx, __shfl_xor_sync(0xffffffffu, mx, o));
            float sum = 0.f;
#pragma unroll
            for (int k = 0; k < 8; k++) { s[k] = ex2((s[k] - mx) * (SCALE * LOG2E)); sum += s[k]; }
#pragma unroll
            for (int o = 1; o < 8; o <<= 1) sum += __shfl_xor_sync(0xffffffffu, sum, o);
            const float inv = __fdividef(1.f, sum);
            uint4 p;
            p.x = pack2(s[0] * inv, s[1] * inv); p.y = pack2(s[2] * inv, s[3] * inv);
            p.z = pack2(s[4] * inv, s[5] * inv); p.w = pack2(s[6] * inv, s[7] * inv);
            sts128(sm + OFF_P + head * 128 + ((rr ^ (head & 7)) << 4), p);
            if (rr == 0) ((float*)g_lse)[head * 128 + cta] = mx * (SCALE * LOG2E) + lg2(sum);
        }
        bar_sync(2, 256);
        {
            float o[2][8][4];
#pragma unroll
            for (int mt = 0; mt < 2; mt++)
#pragma unroll
                for (int n = 0; n < 8; n++) { o[mt][n][0] = o[mt][n][1] = o[mt][n][2] = o[mt][n][3] = 0.f; }
            const uint32_t pa = sm + OFF_P + (rr + 8 * (i & 1)) * 128;
            const uint32_t va = sm + OFF_S0 + w * 2048 + (rr + 8 * (i & 1)) * 128;
#pragma unroll 1
            for (int kq = 0; kq < 4; kq++) {
                uint32_t a0[4], a1[4];
                ldsm4(a0, pa + (((2 * kq + (i >> 1)) ^ rr) << 4));
                ldsm4(a1, pa + 2048 + (((2 * kq + (i >> 1)) ^ rr) << 4));
#pragma unroll
                for (int n = 0; n < 8; n += 2) {
                    uint32_t b[4];
                    ldsm4t(b, va + kq * CH + (((n + (i >> 1)) ^ rr) << 4));
                    mma(o[0][n], a0, b[0], b[1]); mma(o[1][n], a1, b[0], b[1]);
                    mma(o[0][n + 1], a0, b[2], b[3]); mma(o[1][n + 1], a1, b[2], b[3]);
                }
            }
#pragma unroll
            for (int mt = 0; mt < 2; mt++)
#pragma unroll
                for (int hf = 0; hf < 2; hf++) {
                    const uint32_t dst = sm + OFF_S2 + (mt * 16 + hf * 8 + g) * 1024 + w * 128 + t * 16;
#pragma unroll
                    for (int nb = 0; nb < 2; nb++) {
                        uint4 v;
                        v.x = pack2(o[mt][nb * 4 + 0][hf * 2], o[mt][nb * 4 + 0][hf * 2 + 1]);
                        v.y = pack2(o[mt][nb * 4 + 1][hf * 2], o[mt][nb * 4 + 1][hf * 2 + 1]);
                        v.z = pack2(o[mt][nb * 4 + 2][hf * 2], o[mt][nb * 4 + 2][hf * 2 + 1]);
                        v.w = pack2(o[mt][nb * 4 + 3][hf * 2], o[mt][nb * 4 + 3][hf * 2 + 1]);
                        sts128(dst + nb * 64, v);
                    }
                }
            asm volatile("fence.proxy.async.shared::cta;" ::: "memory");
            __syncwarp();
            if (lane == 0) mbar_arrive(bars + B_FREE * 8);
            if (st < 98) *(st < 64 ? &g_e4[cta][st] : st < 96 ? &g_e5[cta][st - 64] : &g_l5[h][j * 2 + st - 96]) = make_uint4(EMPTY, EMPTY, EMPTY, EMPTY);
            else if (st < 100) ((uint4*)out)[cta * 2 + st - 98] = make_uint4(0u, 0u, 0u, 0u);
        }
        bar_sync(2, 256);
        if (st == 0) {
            TS(12);
#pragma unroll 1
            for (int k = 0; k < ST_SPLIT; k++) {
                asm volatile("cp.async.bulk.tensor.3d.global.shared::cta.bulk_group [%0, {%2,%3,%4}], [%1];"
                             ::"l"(&maps.ctxp), "r"(sm + OFF_S2 + k * (2 * CH / ST_SPLIT)), "r"(0), "r"(cta), "r"(k * (128 / ST_SPLIT)) : "memory");
                if (k + 1 < ST_SPLIT) __nanosleep(ST_GAP);
            }
            asm volatile("cp.async.bulk.commit_group;" ::: "memory");
            asm volatile("cp.async.bulk.wait_group 0;" ::: "memory");
            cnt_rendezvous(&g_cnt[1], tag * 128u, 20);
            TS(13);
            mbar_expect(bars + B_GATH * 8, 2 * CH + 512);
            bulk1d_n(sm + OFF_LSE, g_lse + h * 32, 512, bars + B_GATH * 8);
#pragma unroll 1
            for (int k = 0; k < G_SPLIT; k++) {
                bulk1d_n(sm + OFF_S2 + k * (2 * CH / G_SPLIT), g_ctxp + cta * 2048 + k * (2048 / G_SPLIT), 2 * CH / G_SPLIT, bars + B_GATH * 8);
                if (k + 1 < G_SPLIT) __nanosleep(G_GAP);
            }
        }
        __syncwarp();
        {
            mbar_wait(bars + B_GATH * 8, 1);
            if (st == 0) TS(22);
            uint4 v[8];
#pragma unroll
            for (int k = 0; k < 8; k++) v[k] = lds128(sm + OFF_S2 + (k * 256 + st) * 16);
            float ls[4];
#pragma unroll
            for (int k = 0; k < 4; k++) ls[k] = ldsf(sm + OFF_LSE + (k * 32 + lane) * 4);
            float m0 = fmaxf(ls[0], ls[1]), m1 = fmaxf(ls[2], ls[3]);
#pragma unroll
            for (int o = 16; o; o >>= 1) { m0 = fmaxf(m0, __shfl_xor_sync(0xffffffffu, m0, o)); m1 = fmaxf(m1, __shfl_xor_sync(0xffffffffu, m1, o)); }
            ls[0] = ex2(ls[0] - m0); ls[1] = ex2(ls[1] - m0); ls[2] = ex2(ls[2] - m1); ls[3] = ex2(ls[3] - m1);
            float z0 = ls[0] + ls[1], z1 = ls[2] + ls[3];
#pragma unroll
            for (int o = 16; o; o >>= 1) { z0 += __shfl_xor_sync(0xffffffffu, z0, o); z1 += __shfl_xor_sync(0xffffffffu, z1, o); }
            z0 = __fdividef(1.f, z0); z1 = __fdividef(1.f, z1);
            ls[0] *= z0; ls[1] *= z0; ls[2] *= z1; ls[3] *= z1;
            float a[2][8];
#pragma unroll
            for (int e = 0; e < 8; e++) a[0][e] = a[1][e] = 0.f;
            const int rg = st >> 4;
#pragma unroll
            for (int k = 0; k < 8; k++) {
                const float wt = __shfl_sync(0xffffffffu, ls[k >> 1], rg + 16 * (k & 1));
                const uint32_t u[4] = {v[k].x, v[k].y, v[k].z, v[k].w};
#pragma unroll
                for (int e = 0; e < 4; e++) {
                    a[k >> 2][2 * e] += wt * __uint_as_float(u[e] << 16);
                    a[k >> 2][2 * e + 1] += wt * __uint_as_float(u[e] & 0xffff0000u);
                }
            }
            const int b = lane >> 4, u16 = lane & 15;
            const uint32_t ra = sm + OFF_SC + (w * 256 + b * 128 + (u16 >> 3) * 64 + ((u16 >> 2) & 1) * 32 + (u16 & 3) * 2) * 4;
#pragma unroll
            for (int e = 0; e < 8; e += 2) {
                const float k0 = b ? a[1][e] : a[0][e], k1 = b ? a[1][e + 1] : a[0][e + 1];
                const float s0 = b ? a[0][e] : a[1][e], s1 = b ? a[0][e + 1] : a[1][e + 1];
                stsf2(ra + (e >> 1) * 32, k0 + __shfl_xor_sync(0xffffffffu, s0, 16), k1 + __shfl_xor_sync(0xffffffffu, s1, 16));
            }
            bar_sync(2, 256);
            if (st == 0) mbar_arrive(bars + B_S2 * 8);
            float s = 0.f;
#pragma unroll
            for (int k = 0; k < 8; k++) s += ldsf(sm + OFF_SC + (k * 256 + st) * 4);
            const float hi = bfround(s);
            const uint32_t ca = sm + OFF_CC + (st >> 7) * VROW + (st & 127) * 2;
            sts16(ca, f2bf(hi)); sts16(ca + 2 * VROW, f2bf(s - hi));
            bar_sync(2, 256);
        }
        matvecT(c, sm + OFF_S1, sm + OFF_CC, 4, bars + B_WUV * 8, w, lane);
#pragma unroll
        for (int k = 0; k < 4; k++) c[k] += __shfl_down_sync(0xffffffffu, c[k], 1);
        if (t == 0) {
            float* const e = (float*)g_e4[cta] + w * 16 + g;
            mail_put(e, c[0]); mail_put(e + 128, c[1]); mail_put(e + 8, c[2]); mail_put(e + 136, c[3]);
        }
        __syncwarp();
        if (lane == 0) mbar_arrive(bars + B_FREE * 8);
        if (st == 0) TS(23);
        {
            const uint4* const pv = &g_e4[(w >> 1) * 32 + (cta & 28)][(w & 1) * 32 + lane];
            uint4 x[4];
            uint32_t it = 0;
            sleep_ns(POLL_DELAY2);
            while (true) {
#pragma unroll
                for (int k = 0; k < 4; k++) { x[k].x = x[k].y = x[k].z = x[k].w = 0u; mail_get(x[k], pv + k * 64); }
                if (!__any_sync(0xffffffffu, mail_missing(x[0]) | mail_missing(x[1]) | mail_missing(x[2]) | mail_missing(x[3]))) break;
                if (++it > SPIN_MAX) __trap();
                __nanosleep(BACKOFF);
            }
#define SUM4(e) ((__uint_as_float(x[0].e) + __uint_as_float(x[1].e)) + (__uint_as_float(x[2].e) + __uint_as_float(x[3].e)))
            sts64(sm + OFF_CA + w * VROW + lane * 8, pack2(SUM4(x), SUM4(y)), pack2(SUM4(z), SUM4(w)));
#undef SUM4
        }
        if (st == 0) TS(14);
        bar_sync(4, 256 + 128);
        {
            const uint32_t a0 = sm + OFF_S0 + (w >> 1) * 8192 + (w & 1) * 1024 + (rr + 8 * (i >> 1)) * 64 + (((i & 1) ^ (rr >> 1)) << 4);
            const uint4* const pv = pin(&g_e5[(w >> 1) * 32 + (cta & 28) + (g & 3)][(g >> 2) * 16 + (w & 1) * 8 + t]);
            const uint32_t* const pl = pin((const uint32_t*)g_l5[(w >> 1) * 8 + (h & 7)] + rr);
            const uint32_t wa = sm + OFF_SC + ((w * 2 + (t & 1)) * 80 + (t >> 1) * 40 + g) * 4;
            __nv_bfloat16* const outp = pin(out + (lane >> 4) * 1024 + 512 + col + (lane & 15) * 2);
            uint32_t a[4][2][4], xl = 0u, it = 0;
            uint4 x[2] = {make_uint4(0u, 0u, 0u, 0u), make_uint4(0u, 0u, 0u, 0u)};
            while (true) {
                if (lane < 8) asm volatile("atom.relaxed.gpu.global.or.b32 %0, [%1], 0;" : "=r"(xl) : "l"(pl) : "memory");
                if (!__any_sync(0xffffffffu, xl == EMPTY)) break;
                if (++it > SPIN_MAX) __trap();
            }
            if (st == 0) TS(25);
            mail_get(x[0], pv); mail_get(x[1], pv + 4);
            float w0 = __uint_as_float(xl), w1 = fmaxf(w0, __shfl_xor_sync(0xffffffffu, w0, 1));
            w0 = ex2(w0 - fmaxf(w1, __shfl_xor_sync(0xffffffffu, w1, 2)));
            w1 = w0 + __shfl_xor_sync(0xffffffffu, w0, 1);
            w0 *= rcp(w1 + __shfl_xor_sync(0xffffffffu, w1, 2));
            w1 = __shfl_sync(0xffffffffu, w0, 2 * t + 1);
            w0 = __shfl_sync(0xffffffffu, w0, 2 * t);
            mbar_wait(bars + (B_WO + (w >> 1)) * 8, 0);
#pragma unroll
            for (int q = 0; q < 4; q++) {
                ldsm4t(a[q][0], a0 + q * 2048);
                ldsm4t(a[q][1], (a0 ^ 32) + q * 2048);
            }
            if (st == 0) TS(26);
            while (true) {
                const bool n0 = mail_missing(x[0]), n1 = mail_missing(x[1]);
                if (!__any_sync(0xffffffffu, n0 | n1)) break;
                mail_get(x[0], pv, n0); mail_get(x[1], pv + 4, n1);
                if (++it > SPIN_MAX) __trap();
            }
            if (st == 0) TS(16);
            float d[2][2][4];
#pragma unroll
            for (int k = 0; k < 4; k++) {
                float (&dk)[4] = d[k >> 1][k & 1];
                dk[0] = dk[1] = dk[2] = dk[3] = 0.f;
                mma(dk, a[k >> 1][k & 1], x[k >> 1].x, x[k >> 1].y);
            }
#pragma unroll
            for (int k = 0; k < 4; k++) mma(d[k >> 1][k & 1], a[2 + (k >> 1)][k & 1], x[k >> 1].z, x[k >> 1].w);
#pragma unroll
            for (int k = 0; k < 4; k++) {
                const int e = (k & 1) * 2;
                sts32(wa + k * 32, __float_as_uint(w0 * (d[0][k >> 1][e] + d[1][k >> 1][e]) + w1 * (d[0][k >> 1][e + 1] + d[1][k >> 1][e + 1])));
            }
            if (st == 0) TS(17);
            if (w == 0) {
                bar_sync(5, 256);
                const uint32_t ra = sm + OFF_SC + ((lane >> 4) * 40 + (lane & 15) * 2) * 4;
                float2 r[16];
#pragma unroll
                for (int k = 0; k < 16; k++) r[k] = ldsf2(ra + k * 320);
#pragma unroll
                for (int o = 1; o < 16; o <<= 1)
#pragma unroll
                    for (int k = 0; k < 16; k += 2 * o) { r[k].x += r[k + o].x; r[k].y += r[k + o].y; }
                out_add(outp, r[0].x, r[0].y);
            } else {
                bar_arrive(5, 256);
            }
        }
    }
}

typedef CUresult (*EncodeFn)(CUtensorMap*, CUtensorMapDataType, cuuint32_t, void*, const cuuint64_t*, const cuuint64_t*,
                             const cuuint32_t*, const cuuint32_t*, CUtensorMapInterleave, CUtensorMapSwizzle,
                             CUtensorMapL2promotion, CUtensorMapFloatOOBfill);

void make_map(EncodeFn enc, CUtensorMap* m, void* p, unsigned rows, unsigned cols, unsigned br, unsigned bg) {
    cuuint64_t gd[3] = {64, rows, cols / 64};
    cuuint64_t gs[2] = {(cuuint64_t)cols * 2, 128};
    cuuint32_t bx[3] = {64, br, bg};
    cuuint32_t es[3] = {1, 1, 1};
    enc(m, CU_TENSOR_MAP_DATA_TYPE_BFLOAT16, 3, p, gd, gs, bx, es, CU_TENSOR_MAP_INTERLEAVE_NONE,
        CU_TENSOR_MAP_SWIZZLE_128B, CU_TENSOR_MAP_L2_PROMOTION_L2_128B, CU_TENSOR_MAP_FLOAT_OOB_FILL_NONE);
}

}

extern "C" void kernel_launch(void* const* d_in, const int* in_sizes, int n_in, void* d_out, int out_size) {
    static EncodeFn enc = nullptr;
    if (!enc) {
        void* fn = nullptr;
        cudaDriverEntryPointQueryResult qr;
        cudaGetDriverEntryPoint("cuTensorMapEncodeTiled", &fn, cudaEnableDefault, &qr);
        enc = (EncodeFn)fn;
        cudaFuncSetAttribute(fused_decode_kernel, cudaFuncAttributeMaxDynamicSharedMemorySize, SMEM_BYTES);
    }
    Maps maps;
    make_map(enc, &maps.wqB, d_in[9], 512, 4096, 64, 2);
    make_map(enc, &maps.wqA, d_in[2], 512, 4096, 64, 2);
    make_map(enc, &maps.wuk, d_in[3], 512, 4096, 64, 2);
    make_map(enc, &maps.wuv, d_in[4], 512, 4096, 64, 2);
    for (int k = 0; k < 2; k++) {
        cuuint64_t gd[3] = {512, 128, 32};
        cuuint64_t gs[2] = {1024, 131072};
        cuuint32_t bx[3] = {32, 128, 1};
        cuuint32_t es[3] = {1, 1, 1};
        enc(&maps.woB + k, CU_TENSOR_MAP_DATA_TYPE_BFLOAT16, 3, d_in[k ? 5 : 10], gd, gs, bx, es, CU_TENSOR_MAP_INTERLEAVE_NONE,
            CU_TENSOR_MAP_SWIZZLE_64B, CU_TENSOR_MAP_L2_PROMOTION_L2_128B, CU_TENSOR_MAP_FLOAT_OOB_FILL_NONE);
    }
    make_map(enc, &maps.ckv, d_in[1], 8192, 512, 16, 8);
    {
        void* p = nullptr;
        cudaGetSymbolAddress(&p, g_ctxp);
        cuuint64_t gd[3] = {128, 128, 128};
        cuuint64_t gs[2] = {256, 32768};
        cuuint32_t bx[3] = {128, 1, 128 / ST_SPLIT};
        cuuint32_t es[3] = {1, 1, 1};
        enc(&maps.ctxp, CU_TENSOR_MAP_DATA_TYPE_BFLOAT16, 3, p, gd, gs, bx, es, CU_TENSOR_MAP_INTERLEAVE_NONE,
            CU_TENSOR_MAP_SWIZZLE_NONE, CU_TENSOR_MAP_L2_PROMOTION_NONE, CU_TENSOR_MAP_FLOAT_OOB_FILL_NONE);
    }
    fused_decode_kernel<<<NCTA, NTHREADS, SMEM_BYTES>>>((const char*)d_in[9], maps, (const char*)d_in[7], (const char*)d_in[8],
                                                         (const __nv_bfloat16*)d_in[0], (const __nv_bfloat16*)d_in[6],
                                                         (__nv_bfloat16*)d_out, 0u);
}
```
